```python
import torch

def _softmax(x, axis=-1):
    return torch.softmax(x, dim=axis)

def _gelu(x):
    return torch.nn.functional.gelu(x, approximate='tanh')

def _silu(x):
    return torch.nn.functional.silu(x)

def _sigmoid(x):
    return torch.sigmoid(x)

def _layernorm(x, axis=-1, eps=1e-05):
    m = x.mean(dim=axis, keepdim=True)
    v = x.var(dim=axis, keepdim=True, unbiased=False)
    return (x - m) / torch.sqrt(v + eps)

def _scatter_add(tgt, idx, src, axis=0):
    return tgt.clone().index_add_(axis, idx, src)

def _segment_sum(src, seg, n):
    out = torch.zeros((n,) + src.shape[1:], dtype=src.dtype)
    return out.index_add_(0, seg, src)

def _pad(x, pw):
    flat = tuple((v for pair in reversed(pw) for v in pair))
    return torch.nn.functional.pad(x, flat)
kernel_name = 'adaLN_cond__memory_aug_recurrent_mem_tr__geglu_ffn__prompt'

def setup_inputs():

    _w = lambda a: (lambda t: t.to(torch.bfloat16) if t.is_floating_point() else t)(torch.as_tensor(a))

    def _A_setup():
        B, S, Dm = (1, 2048, 640)
        H, Dh = (32, 128)
        M, seg = (8, 32)
        seg = min(seg, S)
        S = S // seg * seg
        return {'x': _w((lambda *s: torch.randn(*s, dtype=torch.bfloat16) * 0.05)(B, S, Dm)), 'mem0': _w((lambda *s: torch.randn(*s, dtype=torch.bfloat16) * 0.4)(B, M, Dm)), 'Wq': _w((lambda *s: torch.randn(*s, dtype=torch.bfloat16) * 3.2)(Dm, H, Dh) * Dm ** (-0.5)), 'Wk': _w((lambda *s: torch.randn(*s, dtype=torch.bfloat16) * 3.2)(Dm, H, Dh) * Dm ** (-0.5)), 'Wv': _w((lambda *s: torch.randn(*s, dtype=torch.bfloat16) * 0.4)(Dm, H, Dh) * Dm ** (-0.5)), 'Wo': _w((lambda *s: torch.randn(*s, dtype=torch.bfloat16) * 0.4)(H, Dh, Dm) * (H * Dh) ** (-0.5)), 'seg_len': seg}
    _A_in = _A_setup()

    def _B_setup():
        B, S, D, F = (1, 2048, 640, 1728)
        return {'x': _w((lambda *s: torch.randn(*s, dtype=torch.bfloat16) * 0.05)(B, S, D)), 'w_gate': _w((lambda *s: torch.randn(*s, dtype=torch.bfloat16) * 0.05)(D, F)), 'w_up': _w((lambda *s: torch.randn(*s, dtype=torch.bfloat16) * 0.05)(D, F)), 'w_down': _w((lambda *s: torch.randn(*s, dtype=torch.bfloat16) * 0.05)(F, D))}
    _B_in = _B_setup()
    return {'A_x': _A_in['x'], 'A_mem0': _A_in['mem0'], 'A_Wq': _A_in['Wq'], 'A_Wk': _A_in['Wk'], 'A_Wv': _A_in['Wv'], 'A_Wo': _A_in['Wo'], 'A_seg_len': _A_in['seg_len'], 'B_x': _B_in['x'], 'B_w_gate': _B_in['w_gate'], 'B_w_up': _B_in['w_up'], 'B_w_down': _B_in['w_down'], 'c': _w((lambda *s: torch.randn(*s, dtype=torch.bfloat16) * 0.1)(1, 640) * 8.0), 'w_mod': _w((lambda *s: torch.randn(*s, dtype=torch.bfloat16) * 0.1)(640, 6 * 640) * 640 ** (-0.5) * 8.0)}

def reference(A_x, A_mem0, A_Wq, A_Wk, A_Wv, A_Wo, A_seg_len, B_x, B_w_gate, B_w_up, B_w_down, c, w_mod):

    def _A_ref(x, mem0, Wq, Wk, Wv, Wo, seg_len):
        B, S, Dm = x.shape
        H, Dh = (Wq.shape[1], Wq.shape[2])
        M = mem0.shape[1]
        scale = Dh ** (-0.5)
        n_seg = S // seg_len
        L = M + seg_len
        idx = torch.arange(L)
        mask = (idx[:, None] < M) | (idx[:, None] >= idx[None, :])
        mem = mem0
        outs = []
        for s in range(n_seg):
            xs = x[:, s * seg_len:(s + 1) * seg_len, :].clone()
            h = torch.concatenate([mem, xs], axis=1)
            q = torch.einsum('btd,dhe->bhte', h, Wq)
            k = torch.einsum('btd,dhe->bhte', h, Wk)
            v = torch.einsum('btd,dhe->bhte', h, Wv)
            scores = torch.einsum('bhqe,bhke->bhqk', q, k) * scale
            scores = torch.where(mask[None, None], scores, -1000000000.0)
            p = _softmax(scores, axis=-1)
            o = torch.einsum('bhqk,bhke->bhqe', p, v)
            o = torch.einsum('bhte,hed->btd', o, Wo)
            mem = o[:, :M, :].clone()
            outs.append(o[:, M:, :])
        return torch.concatenate(outs, axis=1)

    def _B_ref(x, w_gate, w_up, w_down):
        return _gelu(x @ w_gate) * (x @ w_up) @ w_down
    x = A_x
    mod = (_silu(c) @ w_mod).reshape(c.shape[0], 6, 1, -1)
    sa, ca, ga, sb, cb, gb = (mod[:, 0].clone(), mod[:, 1].clone(), mod[:, 2].clone(), mod[:, 3].clone(), mod[:, 4].clone(), mod[:, 5].clone())
    h = _layernorm(x, axis=-1) * (1 + ca) + sa
    x = x + ga * _A_ref(h, A_mem0, A_Wq, A_Wk, A_Wv, A_Wo, A_seg_len)
    h = _layernorm(x, axis=-1) * (1 + cb) + sb
    x = x + gb * _B_ref(h, B_w_gate, B_w_up, B_w_down)
    return x
```

```cpp
#include <cuda_runtime.h>
#include <cuda_bf16.h>
#include <cuda.h>
#include <stdint.h>

typedef __nv_bfloat16 bf16;

__device__ __forceinline__ uint32_t smem_u32(const void* p) { return (uint32_t)__cvta_generic_to_shared(p); }
__device__ __forceinline__ uint32_t mapa_u32(uint32_t a, uint32_t r) { uint32_t o; asm volatile("mapa.shared::cluster.u32 %0, %1, %2;" : "=r"(o) : "r"(a), "r"(r)); return o; }
__device__ __forceinline__ void mbar_init(uint32_t bar, uint32_t cnt) { asm volatile("mbarrier.init.shared::cta.b64 [%0], %1;" :: "r"(bar), "r"(cnt) : "memory"); }
__device__ __forceinline__ void mbar_expect_tx(uint32_t bar, uint32_t bytes) { asm volatile("mbarrier.arrive.expect_tx.shared::cta.b64 _, [%0], %1;" :: "r"(bar), "r"(bytes) : "memory"); }
__device__ __forceinline__ void mbar_arrive(uint32_t bar) { asm volatile("mbarrier.arrive.shared::cta.b64 _, [%0];" :: "r"(bar) : "memory"); }
#define SPIN_LIMIT 4000000
__device__ __forceinline__ void mbar_wait(uint32_t bar, uint32_t ph) {
    uint32_t ok = 0; int lim = 0;
    while (true) {
        asm volatile("{ .reg .pred p; mbarrier.try_wait.parity.shared::cta.b64 p, [%1], %2; selp.u32 %0, 1, 0, p; }" : "=r"(ok) : "r"(bar), "r"(ph) : "memory");
        if (ok) break;
        if (++lim > SPIN_LIMIT) break;
    }
}
__device__ __forceinline__ void mbar_wait_cluster(uint32_t bar, uint32_t ph) {
    uint32_t ok = 0; int lim = 0;
    while (true) {
        asm volatile("{ .reg .pred p; mbarrier.try_wait.parity.acquire.cluster.shared::cta.b64 p, [%1], %2; selp.u32 %0, 1, 0, p; }" : "=r"(ok) : "r"(bar), "r"(ph) : "memory");
        if (ok) break;
        if (++lim > SPIN_LIMIT) break;
    }
}
__device__ __forceinline__ void st_async_v4(uint32_t addr, uint32_t a, uint32_t b, uint32_t c, uint32_t d, uint32_t bar) {
    asm volatile("st.async.weak.shared::cluster.mbarrier::complete_tx::bytes.v4.b32 [%0], {%1,%2,%3,%4}, [%5];" :: "r"(addr), "r"(a), "r"(b), "r"(c), "r"(d), "r"(bar) : "memory");
}
__device__ __forceinline__ void ldsm_x4(uint32_t* r, uint32_t addr) {
    asm volatile("ldmatrix.sync.aligned.m8n8.x4.shared.b16 {%0,%1,%2,%3}, [%4];" : "=r"(r[0]), "=r"(r[1]), "=r"(r[2]), "=r"(r[3]) : "r"(addr) : "memory");
}
__device__ __forceinline__ void ldsm_x4_t(uint32_t* r, uint32_t addr) {
    asm volatile("ldmatrix.sync.aligned.m8n8.x4.trans.shared.b16 {%0,%1,%2,%3}, [%4];" : "=r"(r[0]), "=r"(r[1]), "=r"(r[2]), "=r"(r[3]) : "r"(addr) : "memory");
}
__device__ __forceinline__ void mma16816(float* d, const uint32_t* a, uint32_t b0, uint32_t b1) {
    asm volatile("mma.sync.aligned.m16n8k16.row.col.f32.bf16.bf16.f32 {%0,%1,%2,%3}, {%4,%5,%6,%7}, {%8,%9}, {%0,%1,%2,%3};"
        : "+f"(d[0]), "+f"(d[1]), "+f"(d[2]), "+f"(d[3]) : "r"(a[0]), "r"(a[1]), "r"(a[2]), "r"(a[3]), "r"(b0), "r"(b1));
}
__device__ __forceinline__ uint32_t pack_bf16(float lo, float hi) {
    uint32_t r; asm("cvt.rn.bf16x2.f32 %0, %1, %2;" : "=r"(r) : "f"(hi), "f"(lo)); return r;
}
__device__ __forceinline__ float bf16r(float x) { return __bfloat162float(__float2bfloat16_rn(x)); }
__device__ __forceinline__ uint4 lds128(uint32_t a) { uint4 v; asm volatile("ld.shared.v4.u32 {%0,%1,%2,%3}, [%4];" : "=r"(v.x), "=r"(v.y), "=r"(v.z), "=r"(v.w) : "r"(a) : "memory"); return v; }
__device__ __forceinline__ void sts128(uint32_t a, uint4 v) { asm volatile("st.shared.v4.u32 [%0], {%1,%2,%3,%4};" :: "r"(a), "r"(v.x), "r"(v.y), "r"(v.z), "r"(v.w) : "memory"); }
__device__ __forceinline__ void sts32(uint32_t a, uint32_t v) { asm volatile("st.shared.u32 [%0], %1;" :: "r"(a), "r"(v) : "memory"); }
__device__ __forceinline__ void sts64(uint32_t a, uint32_t x, uint32_t y) { asm volatile("st.shared.v2.u32 [%0], {%1,%2};" :: "r"(a), "r"(x), "r"(y) : "memory"); }
__device__ __forceinline__ void sts16(uint32_t a, uint16_t v) { asm volatile("st.shared.u16 [%0], %1;" :: "r"(a), "h"(v) : "memory"); }
__device__ __forceinline__ uint2 lds64(uint32_t a) { uint2 v; asm volatile("ld.shared.v2.u32 {%0,%1}, [%2];" : "=r"(v.x), "=r"(v.y) : "r"(a) : "memory"); return v; }
__device__ __forceinline__ void cp_async16(uint32_t dst, const void* src) { asm volatile("cp.async.cg.shared.global [%0], [%1], 16;" :: "r"(dst), "l"(src) : "memory"); }
__device__ __forceinline__ void cp_async_wait_all() { asm volatile("cp.async.wait_all;" ::: "memory"); }
__device__ __forceinline__ void bar_sync(int id, int n) { asm volatile("bar.sync %0, %1;" :: "r"(id), "r"(n) : "memory"); }
__device__ __forceinline__ uint4 ld_relaxed_v4(const void* p) {
    uint4 v; asm volatile("ld.relaxed.gpu.global.v4.u32 {%0,%1,%2,%3}, [%4];" : "=r"(v.x), "=r"(v.y), "=r"(v.z), "=r"(v.w) : "l"(p) : "memory"); return v;
}
__device__ __forceinline__ void st_relaxed_v4(void* p, uint4 v) {
    asm volatile("st.relaxed.gpu.global.v4.u32 [%0], {%1,%2,%3,%4};" :: "l"(p), "r"(v.x), "r"(v.y), "r"(v.z), "r"(v.w) : "memory");
}
__device__ __forceinline__ uint32_t ld_acquire(const uint32_t* p) { uint32_t v; asm volatile("ld.acquire.gpu.global.u32 %0, [%1];" : "=r"(v) : "l"(p) : "memory"); return v; }
__device__ __forceinline__ uint32_t ld_relaxed(const uint32_t* p) { uint32_t v; asm volatile("ld.relaxed.gpu.global.u32 %0, [%1];" : "=r"(v) : "l"(p) : "memory"); return v; }
__device__ __forceinline__ void st_release(uint32_t* p, uint32_t v) { asm volatile("st.release.gpu.global.u32 [%0], %1;" :: "l"(p), "r"(v) : "memory"); }
__device__ __forceinline__ void cluster_sync_all() {
    asm volatile("barrier.cluster.arrive.release.aligned;" ::: "memory");
    asm volatile("barrier.cluster.wait.acquire.aligned;" ::: "memory");
}

__device__ bf16 g_k[2048 * 4096];
__device__ bf16 g_v[2048 * 4096];
__device__ bf16 g_km[64 * 8 * 4096];
__device__ bf16 g_vm[64 * 8 * 4096];
__device__ uint4 g_gx[2][4][16][80];
__device__ uint32_t g_rprog[64 * 32];
__device__ uint32_t g_kvflag[16 * 64];
__device__ uint32_t g_epoch;

namespace rk {
constexpr int MEM_STRIDE = 1296;
constexpr int T_STRIDE = 272;
constexpr int OFF_W = 0;
constexpr int OFF_KX = 163840;
constexpr int OFF_VX = OFF_KX + 8192;
constexpr int OFF_MEM = OFF_VX + 8192;
constexpr int OFF_Q = OFF_MEM + 8 * MEM_STRIDE;
constexpr int OFF_KM = OFF_Q + 8 * T_STRIDE;
constexpr int OFF_VM = OFF_KM + 8 * T_STRIDE;
constexpr int OFF_O = OFF_VM + 8 * T_STRIDE;
constexpr int OFF_SC = OFF_O + 8 * T_STRIDE;
constexpr int OFF_RED = OFF_SC + 8 * 56 * 4;
constexpr int OFF_RS = OFF_RED + 6144;
constexpr int OFF_ST = OFF_RS + 8 * 80 * 16;
constexpr int OFF_BAR = OFF_ST + 640;
constexpr int OFF_TL = OFF_BAR + 64;
constexpr int SMEM_BYTES = OFF_TL + 512;

__device__ __forceinline__ void load_frag(uint32_t* a, const bf16* __restrict__ W, int ld, int k0, int cb, int g, int t) {
    const uint32_t* p = (const uint32_t*)(W + (size_t)(k0 + 2 * t) * ld + cb + 2 * g);
    int ldw = ld / 2;
    uint32_t w0 = __ldg(p), w1 = __ldg(p + ldw), w2 = __ldg(p + 8 * ldw), w3 = __ldg(p + 9 * ldw);
    a[0] = __byte_perm(w0, w1, 0x5410); a[1] = __byte_perm(w0, w1, 0x7632);
    a[2] = __byte_perm(w2, w3, 0x5410); a[3] = __byte_perm(w2, w3, 0x7632);
}
}

#define TL(i)
#define TG(i)

__device__ __forceinline__ void tma_load_2d(uint32_t dst, const CUtensorMap* map, int c0, int c1, uint32_t bar) {
    asm volatile("cp.async.bulk.tensor.2d.shared::cluster.global.mbarrier::complete_tx::bytes [%0], [%1, {%3, %4}], [%2];"
        :: "r"(dst), "l"(map), "r"(bar), "r"(c0), "r"(c1) : "memory");
}
__device__ __forceinline__ void stg128(void* p, uint4 v) { asm volatile("st.global.v4.u32 [%0], {%1,%2,%3,%4};" :: "l"(p), "r"(v.x), "r"(v.y), "r"(v.z), "r"(v.w) : "memory"); }

__global__ void __launch_bounds__(256, 1)
r_kernel(const __grid_constant__ CUtensorMap tmK, const __grid_constant__ CUtensorMap tmV, const bf16* __restrict__ mem0, const bf16* __restrict__ Wq, const bf16* __restrict__ Wk, const bf16* __restrict__ Wv, const bf16* __restrict__ Wo, int wait_kv)
{
    using namespace rk;
    extern __shared__ __align__(1024) uint8_t smem[];
    const uint32_t sb = smem_u32(smem);
    const int tid = threadIdx.x, warp = tid >> 5, lane = tid & 31, g = lane >> 2, t = lane & 3;
    uint32_t rank, cid;
    asm volatile("mov.u32 %0, %%cluster_ctarank;" : "=r"(rank));
    asm volatile("mov.u32 %0, %%clusterid.x;" : "=r"(cid));
    const int hh = rank >> 1, j = rank & 1, h = cid * 8 + hh;
    const int kh = warp & 1, mb = warp >> 1;
    const uint32_t b_mem = sb + OFF_BAR, b_qkv = b_mem + 8, b_rs = b_mem + 16, b_kv = b_mem + 24;

    asm volatile("griddepcontrol.launch_dependents;");
    const uint32_t epoch = ld_relaxed(&g_epoch);

    if (tid == 0) {
        mbar_init(b_mem, 1); mbar_init(b_qkv, 9); mbar_init(b_rs, 1); mbar_init(b_kv, 1);
        asm volatile("fence.mbarrier_init.release.cluster;" ::: "memory");
    }
    const uint32_t wsm = sb + OFF_W + (warp < 4 ? warp * 22528 : 4 * 22528 + (warp - 4) * 18432) + lane * 16;
    uint32_t wq[20][4], wk[20][4];
    {
        const int cb = h * 128 + 64 * j + 16 * mb;
#pragma unroll
        for (int i = 0; i < 20; i++) load_frag(wq[i], Wq, 4096, (20 * kh + i) * 16, cb, g, t);
#pragma unroll
        for (int i = 0; i < 20; i++) load_frag(wk[i], Wk, 4096, (20 * kh + i) * 16, cb, g, t);
#pragma unroll 4
        for (int i = 0; i < 20; i++) { uint32_t a[4]; load_frag(a, Wv, 4096, (20 * kh + i) * 16, cb, g, t); sts128(wsm + i * 512, make_uint4(a[0], a[1], a[2], a[3])); }
        const bf16* Woh = Wo + (size_t)h * 128 * 640;
        const int c3 = 320 * j + 16 * warp;
        const int n3 = warp < 4 ? 24 : 16;
#pragma unroll 4
        for (int i = 0; i < n3; i++) { uint32_t a[4]; load_frag(a, Woh, 640, (i & 7) * 16, c3 + 128 * (i >> 3), g, t); sts128(wsm + (20 + i) * 512, make_uint4(a[0], a[1], a[2], a[3])); }
    }
    for (int i = tid; i < 640; i += 256) {
        int row = i / 80, c = i % 80;
        uint4 v = __ldg((const uint4*)(mem0 + row * 640 + c * 8));
        sts128(sb + OFF_MEM + row * MEM_STRIDE + c * 16, v);
    }
    auto prefetch_kv = [&](int s) {
        if ((wait_kv & 1) && (s & 3) == 0) {
            const uint32_t* fk = &g_kvflag[(s >> 2) * 64 + h];
            int lim = 0;
            while (ld_acquire(fk) != epoch + 1) { if (++lim > SPIN_LIMIT) break; }
            while (ld_acquire(fk + 32) != epoch + 1) { if (++lim > SPIN_LIMIT) break; }
            asm volatile("fence.proxy.async.global;" ::: "memory");
        }
        mbar_expect_tx(b_kv, 16384);
        tma_load_2d(sb + OFF_KX, &tmK, h * 128, s * 32, b_kv);
        tma_load_2d(sb + OFF_KX + 4096, &tmK, h * 128 + 64, s * 32, b_kv);
        tma_load_2d(sb + OFF_VX, &tmV, h * 128, s * 32, b_kv);
        tma_load_2d(sb + OFF_VX + 4096, &tmV, h * 128 + 64, s * 32, b_kv);
    };
    __syncthreads();
    if (tid == 128) prefetch_kv(0);
    __syncthreads();
    cluster_sync_all();

    const uint32_t peer_off = mapa_u32(sb, rank ^ 1) - sb;
    const uint32_t memb_addr = sb + OFF_MEM + (lane & 7) * MEM_STRIDE + (20 * kh * 16 + (lane >> 3) * 8) * 2;
    const uint32_t cofs = (64 * j + 16 * mb) * 2;
    const float scale = 0.08838834764831845f;

    for (int s = 0; s < 64; s++) {
        const uint32_t ph = s & 1;
        TL(0);
        uint4 va[4];
        va[0] = lds128(wsm); va[1] = lds128(wsm + 512);
        if (s > 0) mbar_wait(b_mem, ph ^ 1);
        TL(1); TG(15);
        {
            float aq0[4] = {0, 0, 0, 0}, aq1[4] = {0, 0, 0, 0}, ak0[4] = {0, 0, 0, 0}, ak1[4] = {0, 0, 0, 0}, av0[4] = {0, 0, 0, 0}, av1[4] = {0, 0, 0, 0};
            uint32_t b[2][4];
            ldsm_x4(b[0], memb_addr);
            if (tid == 0) {
                mbar_expect_tx(b_qkv, 3072);
                if (s < 63) { mbar_expect_tx(b_rs, 10240); mbar_expect_tx(b_mem, 10240); }
            }
#pragma unroll
            for (int i = 0; i < 10; i++) {
                if (i + 1 < 10) {
                    ldsm_x4(b[(i + 1) % 2], memb_addr + (i + 1) * 64);
                    va[(2 * i + 2) % 4] = lds128(wsm + (2 * i + 2) * 512); va[(2 * i + 3) % 4] = lds128(wsm + (2 * i + 3) * 512);
                }
                const uint32_t* bb = b[i % 2];
                mma16816(aq0, wq[2 * i], bb[0], bb[1]); mma16816(ak0, wk[2 * i], bb[0], bb[1]); mma16816(av0, (uint32_t*)&va[(2 * i) % 4], bb[0], bb[1]);
                mma16816(aq1, wq[2 * i + 1], bb[2], bb[3]); mma16816(ak1, wk[2 * i + 1], bb[2], bb[3]); mma16816(av1, (uint32_t*)&va[(2 * i + 1) % 4], bb[2], bb[3]);
            }
            float snd[4], fin[4];
#pragma unroll
            for (int i = 0; i < 4; i++) { float q = aq0[i] + aq1[i], k = ak0[i] + ak1[i]; snd[i] = kh ? q : k; fin[i] = kh ? k : q; av0[i] += av1[i]; }
            sts128(sb + OFF_RED + warp * 512 + lane * 16, make_uint4(__float_as_uint(snd[0]), __float_as_uint(snd[1]), __float_as_uint(snd[2]), __float_as_uint(snd[3])));
            sts64(sb + OFF_RED + 4096 + warp * 256 + lane * 8, __float_as_uint(kh ? av0[0] : av0[1]), __float_as_uint(kh ? av0[2] : av0[3]));
            bar_sync(1 + mb, 64);
            uint4 r = lds128(sb + OFF_RED + (warp ^ 1) * 512 + lane * 16);
            uint2 r2 = lds64(sb + OFF_RED + 4096 + (warp ^ 1) * 256 + lane * 8);
            fin[0] += __uint_as_float(r.x); fin[1] += __uint_as_float(r.y); fin[2] += __uint_as_float(r.z); fin[3] += __uint_as_float(r.w);
            float f0 = (kh ? av0[1] : av0[0]) + __uint_as_float(r2.x), f1 = (kh ? av0[3] : av0[2]) + __uint_as_float(r2.y);
            TL(2);
            const uint32_t buf = sb + (kh ? OFF_KM : OFF_Q) + cofs;
            sts32(buf + (2 * t) * T_STRIDE + g * 4, pack_bf16(fin[0], fin[2]));
            sts32(buf + (2 * t + 1) * T_STRIDE + g * 4, pack_bf16(fin[1], fin[3]));
            sts32(sb + OFF_VM + cofs + (2 * t + kh) * T_STRIDE + g * 4, pack_bf16(f0, f1));
            __syncwarp();
            if (lane < 24) {
                const int row = lane < 16 ? (lane >> 1) : 2 * ((lane - 16) >> 1) + kh;
                const uint32_t a = (lane < 16 ? buf : sb + OFF_VM + cofs) + row * T_STRIDE + (lane & 1) * 16;
                uint4 v = lds128(a);
                st_async_v4(a + peer_off, v.x, v.y, v.z, v.w, b_qkv + peer_off);
                if ((kh || lane >= 16) && !(wait_kv & 8)) {
                    bf16* dst = (lane < 16 ? g_km : g_vm) + ((uint32_t)(s * 8 + row) * 4096u + h * 128 + 64 * j + 16 * mb + (lane & 1) * 8);
                    stg128(dst, v);
                }
            }
            if (lane == 0) mbar_arrive(b_qkv);
        }
        TL(3);
        if (s == 63) {
            __syncthreads();
            if (tid == 0) st_release(&g_rprog[blockIdx.x * 32], epoch * 64 + 64);
            break;
        }
        uint4 wa[8], wb[8];
        uint32_t a0[4], a1[4];
        const uint32_t eofs = (16 * warp + ((lane >> 3) & 1) * 8) * 2;
        if (!(wait_kv & 2) || s == 0) mbar_wait(b_kv, ph);
        if (warp >= 4 && warp < 7) {
            const int kw = warp - 4;
            uint32_t ka[8][4];
            const uint32_t qa = sb + OFF_Q + (lane & 7) * T_STRIDE + (lane >> 3) * 16;
            if (kw < 2) {
                const uint32_t kaddr = sb + OFF_KX + (16 * kw + (lane & 15)) * 128;
#pragma unroll
                for (int i = 0; i < 8; i++) ldsm_x4(ka[i], kaddr + (i >> 2) * 4096 + ((((2 * i + (lane >> 4)) & 7) ^ (lane & 7)) << 4));
                mbar_wait(b_qkv, ph);
            } else {
                mbar_wait(b_qkv, ph);
                const uint32_t kaddr = sb + OFF_KM + (lane & 7) * T_STRIDE + (lane >> 4) * 16;
#pragma unroll
                for (int i = 0; i < 8; i++) ldsm_x4(ka[i], kaddr + i * 32);
            }
            TL(5);
            uint32_t qb[4][4];
#pragma unroll
            for (int i = 0; i < 4; i++) ldsm_x4(qb[i], qa + i * 64);
            float s0[4] = {0, 0, 0, 0}, s1[4] = {0, 0, 0, 0}, s2[4] = {0, 0, 0, 0}, s3[4] = {0, 0, 0, 0};
            mma16816(s0, ka[0], qb[0][0], qb[0][1]); mma16816(s1, ka[1], qb[0][2], qb[0][3]);
            mma16816(s2, ka[2], qb[1][0], qb[1][1]); mma16816(s3, ka[3], qb[1][2], qb[1][3]);
            mma16816(s0, ka[4], qb[2][0], qb[2][1]); mma16816(s1, ka[5], qb[2][2], qb[2][3]);
            mma16816(s2, ka[6], qb[3][0], qb[3][1]); mma16816(s3, ka[7], qb[3][2], qb[3][3]);
            const uint32_t sc = sb + OFF_SC + (16 * kw + g) * 4;
            sts32(sc + (2 * t) * 224, __float_as_uint(bf16r(bf16r((s0[0] + s1[0]) + (s2[0] + s3[0])) * scale)));
            sts32(sc + (2 * t + 1) * 224, __float_as_uint(bf16r(bf16r((s0[1] + s1[1]) + (s2[1] + s3[1])) * scale)));
            if (kw < 2) {
                sts32(sc + 32 + (2 * t) * 224, __float_as_uint(bf16r(bf16r((s0[2] + s1[2]) + (s2[2] + s3[2])) * scale)));
                sts32(sc + 32 + (2 * t + 1) * 224, __float_as_uint(bf16r(bf16r((s0[3] + s1[3]) + (s2[3] + s3[3])) * scale)));
            }
        } else {
#pragma unroll
            for (int i = 0; i < 8; i++) wa[i] = lds128(wsm + (20 + i) * 512);
            mbar_wait(b_qkv, ph);
        }
        __syncthreads();
        TL(6);
        {
            float x[10];
#pragma unroll
            for (int i = 0; i < 5; i++) { uint2 v = lds64(sb + OFF_SC + g * 224 + (8 * i + 2 * t) * 4); x[2 * i] = __uint_as_float(v.x); x[2 * i + 1] = __uint_as_float(v.y); }
            uint32_t a2[4];
            {
                const uint32_t vx = sb + OFF_VX + (warp >> 2) * 4096 + ((lane >> 4) * 8 + (lane & 7)) * 128 + ((((2 * warp + ((lane >> 3) & 1)) & 7) ^ (lane & 7)) << 4);
                ldsm_x4_t(a0, vx); ldsm_x4_t(a1, vx + 16 * 128);
                ldsm_x4_t(a2, sb + OFF_VM + (lane & 7) * T_STRIDE + eofs);
            }
            if (warp >= 4 && warp < 7) {
#pragma unroll
                for (int i = 0; i < 8; i++) wa[i] = lds128(wsm + (20 + i) * 512);
            }
            float m = fmaxf(fmaxf(fmaxf(x[0], x[1]), fmaxf(x[2], x[3])), fmaxf(fmaxf(x[4], x[5]), fmaxf(x[6], x[7])));
            m = fmaxf(m, fmaxf(x[8], x[9]));
            m = fmaxf(m, __shfl_xor_sync(0xffffffff, m, 1)); m = fmaxf(m, __shfl_xor_sync(0xffffffff, m, 2));
            float sum0 = 0, sum1 = 0;
#pragma unroll
            for (int i = 0; i < 5; i++) { x[2 * i] = __expf(x[2 * i] - m); sum0 += x[2 * i]; x[2 * i + 1] = __expf(x[2 * i + 1] - m); sum1 += x[2 * i + 1]; }
            float sum = sum0 + sum1;
            sum += __shfl_xor_sync(0xffffffff, sum, 1); sum += __shfl_xor_sync(0xffffffff, sum, 2);
            float inv = __fdividef(1.0f, sum);
            uint32_t pb[5];
#pragma unroll
            for (int i = 0; i < 5; i++) pb[i] = pack_bf16(x[2 * i] * inv, x[2 * i + 1] * inv);
            float o0[4] = {0, 0, 0, 0}, o1[4] = {0, 0, 0, 0}, o2[4] = {0, 0, 0, 0};
            mma16816(o0, a0, pb[0], pb[1]); mma16816(o1, a1, pb[2], pb[3]); mma16816(o2, a2, pb[4], 0u);
            const uint32_t oa = sb + OFF_O + (16 * warp + g) * 2;
            sts16(oa + (2 * t) * T_STRIDE, __bfloat16_as_ushort(__float2bfloat16_rn((o0[0] + o1[0]) + o2[0])));
            sts16(oa + (2 * t + 1) * T_STRIDE, __bfloat16_as_ushort(__float2bfloat16_rn((o0[1] + o1[1]) + o2[1])));
            sts16(oa + 16 + (2 * t) * T_STRIDE, __bfloat16_as_ushort(__float2bfloat16_rn((o0[2] + o1[2]) + o2[2])));
            sts16(oa + 16 + (2 * t + 1) * T_STRIDE, __bfloat16_as_ushort(__float2bfloat16_rn((o0[3] + o1[3]) + o2[3])));
        }
#pragma unroll
        for (int i = 0; i < 8; i++) wb[i] = lds128(wsm + (28 + i) * 512);
        __syncthreads();
        TL(7);
        {
            uint32_t ob[16];
            const uint32_t oa = sb + OFF_O + (lane & 7) * T_STRIDE + (lane >> 3) * 16;
#pragma unroll
            for (int i = 0; i < 4; i++) ldsm_x4(ob + 4 * i, oa + i * 64);
            const uint32_t rs_base = sb + OFF_RS + hh * 1280 + t * 16;
            auto send = [&](int mt, const float* d0, const float* d1) {
                int col = 16 * mt + 2 * g; int own = col / 40; int cp = (col - own * 40) >> 1;
                uint32_t doff = mapa_u32(sb, 2 * own + j) - sb;
                st_async_v4(rs_base + cp * 64 + doff, __float_as_uint(d0[0] + d1[0]), __float_as_uint(d0[1] + d1[1]), __float_as_uint(d0[2] + d1[2]), __float_as_uint(d0[3] + d1[3]), b_rs + doff);
            };
            float dA0[4] = {0, 0, 0, 0}, dA1[4] = {0, 0, 0, 0}, dB0[4] = {0, 0, 0, 0}, dB1[4] = {0, 0, 0, 0};
#pragma unroll
            for (int i = 0; i < 4; i++) {
                mma16816(dA0, (uint32_t*)&wa[2 * i], ob[4 * i], ob[4 * i + 1]); mma16816(dA1, (uint32_t*)&wa[2 * i + 1], ob[4 * i + 2], ob[4 * i + 3]);
                mma16816(dB0, (uint32_t*)&wb[2 * i], ob[4 * i], ob[4 * i + 1]); mma16816(dB1, (uint32_t*)&wb[2 * i + 1], ob[4 * i + 2], ob[4 * i + 3]);
            }
            if (warp < 4) {
#pragma unroll
                for (int i = 0; i < 8; i++) wa[i] = lds128(wsm + (36 + i) * 512);
            }
            send(warp, dA0, dA1);
            send(warp + 8, dB0, dB1);
            if (warp < 4) {
                float dC0[4] = {0, 0, 0, 0}, dC1[4] = {0, 0, 0, 0}, dC2[4] = {0, 0, 0, 0}, dC3[4] = {0, 0, 0, 0};
                mma16816(dC0, (uint32_t*)&wa[0], ob[0], ob[1]); mma16816(dC1, (uint32_t*)&wa[1], ob[2], ob[3]);
                mma16816(dC2, (uint32_t*)&wa[2], ob[4], ob[5]); mma16816(dC3, (uint32_t*)&wa[3], ob[6], ob[7]);
                mma16816(dC0, (uint32_t*)&wa[4], ob[8], ob[9]); mma16816(dC1, (uint32_t*)&wa[5], ob[10], ob[11]);
                mma16816(dC2, (uint32_t*)&wa[6], ob[12], ob[13]); mma16816(dC3, (uint32_t*)&wa[7], ob[14], ob[15]);
#pragma unroll
                for (int i = 0; i < 4; i++) { dC0[i] += dC2[i]; dC1[i] += dC3[i]; }
                send(warp + 16, dC0, dC1);
            }
        }
        TL(8);
        if (warp >= 5) {
            const int x = tid - 160;
            const int ot = x < 80 ? x : 79;
            const uint32_t gs = epoch * 64 + s; const uint32_t tag = (gs + 1) & 15u; const int slot = gs & 1;
            uint4* gp = &g_gx[slot][0][rank][ot];
            mbar_wait(b_rs, ph);
            TL(9); TG(12);
            uint4 u[8];
#pragma unroll
            for (int q = 0; q < 8; q++) u[q] = lds128(sb + OFF_RS + q * 1280 + ot * 16);
            float4 a;
            a.x = ((__uint_as_float(u[0].x) + __uint_as_float(u[1].x)) + (__uint_as_float(u[2].x) + __uint_as_float(u[3].x))) + ((__uint_as_float(u[4].x) + __uint_as_float(u[5].x)) + (__uint_as_float(u[6].x) + __uint_as_float(u[7].x)));
            a.y = ((__uint_as_float(u[0].y) + __uint_as_float(u[1].y)) + (__uint_as_float(u[2].y) + __uint_as_float(u[3].y))) + ((__uint_as_float(u[4].y) + __uint_as_float(u[5].y)) + (__uint_as_float(u[6].y) + __uint_as_float(u[7].y)));
            a.z = ((__uint_as_float(u[0].z) + __uint_as_float(u[1].z)) + (__uint_as_float(u[2].z) + __uint_as_float(u[3].z))) + ((__uint_as_float(u[4].z) + __uint_as_float(u[5].z)) + (__uint_as_float(u[6].z) + __uint_as_float(u[7].z)));
            a.w = ((__uint_as_float(u[0].w) + __uint_as_float(u[1].w)) + (__uint_as_float(u[2].w) + __uint_as_float(u[3].w))) + ((__uint_as_float(u[4].w) + __uint_as_float(u[5].w)) + (__uint_as_float(u[6].w) + __uint_as_float(u[7].w)));
            uint4 mine = make_uint4((__float_as_uint(a.x) & ~15u) | tag, (__float_as_uint(a.y) & ~15u) | tag, (__float_as_uint(a.z) & ~15u) | tag, (__float_as_uint(a.w) & ~15u) | tag);
            if (x < 80) st_relaxed_v4(gp + cid * 1280, mine);
            uint4 v[3];
            const uint4* rp0 = gp + (cid ^ 1) * 1280; const uint4* rp1 = gp + (cid ^ 2) * 1280; const uint4* rp2 = gp + (cid ^ 3) * 1280;
            int lim = 0;
            while (true) {
                v[0] = ld_relaxed_v4(rp0); v[1] = ld_relaxed_v4(rp1); v[2] = ld_relaxed_v4(rp2);
                uint32_t bad = 0;
#pragma unroll
                for (int c = 0; c < 3; c++) bad |= (v[c].x ^ tag) | (v[c].y ^ tag) | (v[c].z ^ tag) | (v[c].w ^ tag);
                if ((bad & 15u) == 0) break;
                if (++lim > SPIN_LIMIT) break;
            }
            float f0 = (__uint_as_float(mine.x) + __uint_as_float(v[0].x)) + (__uint_as_float(v[1].x) + __uint_as_float(v[2].x));
            float f1 = (__uint_as_float(mine.y) + __uint_as_float(v[0].y)) + (__uint_as_float(v[1].y) + __uint_as_float(v[2].y));
            float f2 = (__uint_as_float(mine.z) + __uint_as_float(v[0].z)) + (__uint_as_float(v[1].z) + __uint_as_float(v[2].z));
            float f3 = (__uint_as_float(mine.w) + __uint_as_float(v[0].w)) + (__uint_as_float(v[1].w) + __uint_as_float(v[2].w));
            const int cp = ot >> 2, tt = ot & 3;
            sts32(sb + OFF_ST + (2 * tt) * 80 + cp * 4, pack_bf16(f0, f2));
            sts32(sb + OFF_ST + (2 * tt + 1) * 80 + cp * 4, pack_bf16(f1, f3));
            TL(10); TG(13);
            bar_sync(5, 128);
            if (x < 80) {
                const int c = x % 40, d0 = x / 40;
                const int row = c / 5, c8 = c - row * 5;
                uint4 w = lds128(sb + OFF_ST + c * 16);
                const uint32_t off = OFF_MEM + row * MEM_STRIDE + (320 * j + 40 * hh) * 2 + c8 * 16;
#pragma unroll
                for (int i = 0; i < 8; i++) {
                    int d = (d0 * 8 + i + rank) & 15;
                    uint32_t rb = mapa_u32(sb, d); st_async_v4(rb + off, w.x, w.y, w.z, w.w, rb + OFF_BAR);
                }
            }
        } else if (warp == 4) {
            if (lane == 0 && (s & 3) == 3 && !(wait_kv & 4)) st_release(&g_rprog[blockIdx.x * 32], epoch * 64 + s + 1);
            __syncwarp();
        } else if (warp == 3) {
            bar_sync(5, 128);
            if (lane == 0 && s < 62 && !(wait_kv & 2)) prefetch_kv(s + 1);
            __syncwarp();
        }
        TL(11);
    }
    cluster_sync_all();
}

__device__ float g_mod[3840];
__device__ bf16 g_h[2048 * 640];
__device__ bf16 g_q[2048 * 4096];
__device__ bf16 g_o[2048 * 4096];
__device__ bf16 g_x1[2048 * 640];
__device__ bf16 g_h2[2048 * 640];
__device__ bf16 g_act[2048 * 1728];
__device__ float g_slab[2048 * 640];
struct GState {
    uint32_t ticket, done, c_mod_a, c_mod_all;
    uint32_t pad[28];
    uint32_t f_h[16 * 32];
    uint32_t qflag[16 * 32];
    uint32_t c_o[16 * 32];
    uint32_t c_wo[16 * 32];
    uint32_t c_x1[16 * 32];
    uint32_t f_h2[16 * 32];
    uint32_t c_act[16 * 32];
    uint32_t c_f2[16 * 32];
};
__device__ GState g_st;

namespace gk {
constexpr int STAGES = 4;
constexpr int STAGE_BYTES = 49152;
constexpr int OFF_SCR = STAGES * STAGE_BYTES;
constexpr int OFF_BAR = OFF_SCR + 32768;
constexpr int SMEM_BYTES = OFF_BAR + 256;
constexpr int WO_SPLIT = 4, F2_SPLIT = 3;
constexpr int N_MOD = 60, N_L1 = 64, N_KV = 32, N_Q = 16;
constexpr int N_AT = 32, N_WO = 5 * WO_SPLIT, N_L2 = 4, N_F1 = 14, N_F2 = 5 * F2_SPLIT;
constexpr int KV_LEAD = 3;
constexpr int WAVE = N_KV + N_Q + N_AT + N_WO + N_L2 + N_F1 + N_F2;
constexpr int I_L1 = N_MOD, I_W = I_L1 + N_L1;
constexpr int W0 = KV_LEAD;
constexpr int N_ITEMS = I_W + (20 + W0) * WAVE;
enum { T_MOD, T_L1, T_KV, T_Q, T_AT, T_WO, T_L2, T_F1, T_F2, T_SKIP, T_END };
struct Item { int type, rb, nt, ks; };
__host__ __device__ __forceinline__ Item decode(int t) {
    Item it; it.rb = 0; it.nt = 0; it.ks = 0;
    if (t >= N_ITEMS) { it.type = T_END; return it; }
    if (t < I_L1) { it.type = T_MOD; it.nt = t; return it; }
    if (t < I_W) { it.type = T_L1; it.rb = (t - I_L1) >> 2; it.nt = (t - I_L1) & 3; return it; }
    t -= I_W;
    int w = t / WAVE; t -= w * WAVE; w -= W0;
    if (t < N_KV) { it.type = T_KV; it.rb = w + KV_LEAD; it.nt = t; }
    else if ((t -= N_KV) < N_F2) { it.type = T_F2; it.rb = w - 4; it.ks = t / 5; it.nt = t % 5; }
    else if ((t -= N_F2) < N_F1) { it.type = T_F1; it.rb = w - 3; it.nt = t; }
    else if ((t -= N_F1) < N_L2) { it.type = T_L2; it.rb = w - 2; it.nt = t; }
    else if ((t -= N_L2) < N_WO) { it.type = T_WO; it.rb = w - 1; it.ks = t / 5; it.nt = t % 5; }
    else if ((t -= N_WO) < N_Q) { it.type = T_Q; it.rb = w + 1; it.nt = t; }
    else { t -= N_Q; it.type = T_AT; it.rb = w; it.nt = t; }
    if (it.rb < 0 || it.rb > 15) it.type = T_SKIP;
    return it;
}
}

struct GParams {
    CUtensorMap tA_h, tA_o, tA_h2, tA_act, tB_q, tB_k, tB_v, tB_o, tB_g, tB_u, tB_d, tS_q, tS_k, tS_v, tS_act;
};

__device__ __forceinline__ void wait_ge(const uint32_t* p, uint32_t target) {
    int lim = 0;
    while ((int32_t)(ld_acquire(p) - target) < 0) { __nanosleep(64); if (++lim > SPIN_LIMIT) break; }
}
__device__ __forceinline__ uint32_t atom_add_acqrel(uint32_t* p, uint32_t v) {
    uint32_t o; asm volatile("atom.acq_rel.gpu.global.add.u32 %0, [%1], %2;" : "=r"(o) : "l"(p), "r"(v) : "memory"); return o;
}
__device__ __forceinline__ void red_add_release(uint32_t* p, uint32_t v) { asm volatile("red.release.gpu.global.add.u32 [%0], %1;" :: "l"(p), "r"(v) : "memory"); }

__device__ __forceinline__ void wgmma_fence() { asm volatile("wgmma.fence.sync.aligned;" ::: "memory"); }
__device__ __forceinline__ void wgmma_commit() { asm volatile("wgmma.commit_group.sync.aligned;" ::: "memory"); }
template<int N> __device__ __forceinline__ void wgmma_wait() { asm volatile("wgmma.wait_group.sync.aligned %0;" :: "n"(N) : "memory"); }

#define ACC8(b) "+f"(d[b]), "+f"(d[b+1]), "+f"(d[b+2]), "+f"(d[b+3]), "+f"(d[b+4]), "+f"(d[b+5]), "+f"(d[b+6]), "+f"(d[b+7])
#define ACC32(b) ACC8(b), ACC8(b+8), ACC8(b+16), ACC8(b+24)
__device__ __forceinline__ void wgmma_n128(float* d, uint64_t da, uint64_t db, int scale_d) {
    asm volatile("{ .reg .pred p; setp.ne.b32 p, %66, 0;\n"
        "wgmma.mma_async.sync.aligned.m64n128k16.f32.bf16.bf16 {%0,%1,%2,%3,%4,%5,%6,%7,%8,%9,%10,%11,%12,%13,%14,%15,%16,%17,%18,%19,%20,%21,%22,%23,%24,%25,%26,%27,%28,%29,%30,%31,"
        "%32,%33,%34,%35,%36,%37,%38,%39,%40,%41,%42,%43,%44,%45,%46,%47,%48,%49,%50,%51,%52,%53,%54,%55,%56,%57,%58,%59,%60,%61,%62,%63}, %64, %65, p, 1, 1, 0, 1; }"
        : ACC32(0), ACC32(32) : "l"(da), "l"(db), "r"(scale_d));
}
__device__ __forceinline__ void wgmma_n256(float* d, uint64_t da, uint64_t db, int scale_d) {
    asm volatile("{ .reg .pred p; setp.ne.b32 p, %130, 0;\n"
        "wgmma.mma_async.sync.aligned.m64n256k16.f32.bf16.bf16 {%0,%1,%2,%3,%4,%5,%6,%7,%8,%9,%10,%11,%12,%13,%14,%15,%16,%17,%18,%19,%20,%21,%22,%23,%24,%25,%26,%27,%28,%29,%30,%31,"
        "%32,%33,%34,%35,%36,%37,%38,%39,%40,%41,%42,%43,%44,%45,%46,%47,%48,%49,%50,%51,%52,%53,%54,%55,%56,%57,%58,%59,%60,%61,%62,%63,"
        "%64,%65,%66,%67,%68,%69,%70,%71,%72,%73,%74,%75,%76,%77,%78,%79,%80,%81,%82,%83,%84,%85,%86,%87,%88,%89,%90,%91,%92,%93,%94,%95,"
        "%96,%97,%98,%99,%100,%101,%102,%103,%104,%105,%106,%107,%108,%109,%110,%111,%112,%113,%114,%115,%116,%117,%118,%119,%120,%121,%122,%123,%124,%125,%126,%127}, %128, %129, p, 1, 1, 0, 1; }"
        : ACC32(0), ACC32(32), ACC32(64), ACC32(96) : "l"(da), "l"(db), "r"(scale_d));
}
__device__ __forceinline__ uint64_t make_desc(uint32_t addr, uint32_t lbo, uint32_t sbo) {
    return (uint64_t)((addr & 0x3FFFF) >> 4) | ((uint64_t)(lbo >> 4) << 16) | ((uint64_t)(sbo >> 4) << 32) | ((uint64_t)1 << 62);
}

__device__ __forceinline__ float div_fix(float a, float b, float rb) { float q = a * rb; float r = fmaf(-q, b, a); return fmaf(r, rb, q); }
__device__ __forceinline__ void ln_rows(const bf16* __restrict__ xin, bf16* __restrict__ out, const float* __restrict__ shift, const float* __restrict__ scl, int lane, int nr) {
    uint2 nx[5];
#pragma unroll
    for (int i = 0; i < 5; i++) nx[i] = __ldcg((const uint2*)(xin + i * 128 + lane * 4));
    float4 sh[5], sc[5];
#pragma unroll
    for (int i = 0; i < 5; i++) {
        sh[i] = __ldcg((const float4*)(shift + i * 128 + lane * 4)); sc[i] = __ldcg((const float4*)(scl + i * 128 + lane * 4));
        sc[i].x = bf16r(1.0f + sc[i].x); sc[i].y = bf16r(1.0f + sc[i].y); sc[i].z = bf16r(1.0f + sc[i].z); sc[i].w = bf16r(1.0f + sc[i].w);
    }
#pragma unroll 1
    for (int r = 0; r < nr; r++) {
        float x[20];
#pragma unroll
        for (int i = 0; i < 5; i++) {
            x[4 * i] = __uint_as_float(nx[i].x << 16); x[4 * i + 1] = __uint_as_float(nx[i].x & 0xffff0000u);
            x[4 * i + 2] = __uint_as_float(nx[i].y << 16); x[4 * i + 3] = __uint_as_float(nx[i].y & 0xffff0000u);
        }
        if (r + 1 < nr) {
#pragma unroll
            for (int i = 0; i < 5; i++) nx[i] = __ldcg((const uint2*)(xin + (r + 1) * 640 + i * 128 + lane * 4));
        }
        float s = 0;
#pragma unroll
        for (int i = 0; i < 20; i++) s += x[i];
#pragma unroll
        for (int o = 16; o; o >>= 1) s += __shfl_xor_sync(0xffffffff, s, o);
        const float mean = s * (1.0f / 640.0f);
        float q = 0;
#pragma unroll
        for (int i = 0; i < 20; i++) { float d = x[i] - mean; q += d * d; }
#pragma unroll
        for (int o = 16; o; o >>= 1) q += __shfl_xor_sync(0xffffffff, q, o);
        const float m16 = bf16r(mean);
        const float sd = bf16r(sqrtf(bf16r(bf16r(q * (1.0f / 640.0f)) + 1e-5f)));
        const float rs = __frcp_rn(sd);
#pragma unroll
        for (int i = 0; i < 5; i++) {
            float y0 = bf16r(bf16r(div_fix(bf16r(x[4 * i] - m16), sd, rs)) * sc[i].x) + sh[i].x;
            float y1 = bf16r(bf16r(div_fix(bf16r(x[4 * i + 1] - m16), sd, rs)) * sc[i].y) + sh[i].y;
            float y2 = bf16r(bf16r(div_fix(bf16r(x[4 * i + 2] - m16), sd, rs)) * sc[i].z) + sh[i].z;
            float y3 = bf16r(bf16r(div_fix(bf16r(x[4 * i + 3] - m16), sd, rs)) * sc[i].w) + sh[i].w;
            *(uint2*)(out + r * 640 + i * 128 + lane * 4) = make_uint2(pack_bf16(y0, y1), pack_bf16(y2, y3));
        }
    }
}

__device__ __forceinline__ float gelu_tanh(float x) {
    float u2 = x * fmaf(x * x, 2.0f * 0.7978845608028654f * 0.044715f * 1.4426950408889634f, 2.0f * 0.7978845608028654f * 1.4426950408889634f);
    float e; asm("ex2.approx.ftz.f32 %0, %1;" : "=f"(e) : "f"(-u2));
    return __fdividef(x, 1.0f + e);
}
__device__ __forceinline__ uint32_t movmatrix_t(uint32_t a) { uint32_t d; asm volatile("movmatrix.sync.aligned.m8n8.trans.b16 %0, %1;" : "=r"(d) : "r"(a)); return d; }
__device__ __forceinline__ uint4 ldg128(const void* p) { uint4 v; asm volatile("ld.global.v4.u32 {%0,%1,%2,%3}, [%4];" : "=r"(v.x), "=r"(v.y), "=r"(v.z), "=r"(v.w) : "l"(p) : "memory"); return v; }
__device__ __forceinline__ float4 ldcg_f4(const float* p) { float4 v; asm volatile("ld.global.cg.v4.f32 {%0,%1,%2,%3}, [%4];" : "=f"(v.x), "=f"(v.y), "=f"(v.z), "=f"(v.w) : "l"(p) : "memory"); return v; }
__device__ __forceinline__ uint4 ldcg128(const void* p) { uint4 v; asm volatile("ld.global.cg.v4.u32 {%0,%1,%2,%3}, [%4];" : "=r"(v.x), "=r"(v.y), "=r"(v.z), "=r"(v.w) : "l"(p) : "memory"); return v; }

__device__ __forceinline__ void attn_task(int seg, int h, int mt, int lane) {
    const int g = lane >> 2, t = lane & 3;
    const size_t row0 = (size_t)seg * 32 + mt * 16;
    const bf16* qp = g_q + (row0 + g) * 4096 + h * 128 + t * 8;
    uint4 qa[4], qb[4];
#pragma unroll
    for (int c = 0; c < 4; c++) { qa[c] = ldcg128(qp + c * 32); qb[c] = ldcg128(qp + 8 * 4096 + c * 32); }
    float s[5][4];
    uint4 kv[5][4];
#pragma unroll
    for (int kt = 0; kt < 5; kt++) {
        const bf16* kp = (kt == 0) ? g_km + ((size_t)seg * 8 + g) * 4096 + h * 128 + t * 8
                                   : g_k + ((size_t)seg * 32 + (kt - 1) * 8 + g) * 4096 + h * 128 + t * 8;
#pragma unroll
        for (int c = 0; c < 4; c++) kv[kt][c] = ldcg128(kp + c * 32);
    }
#pragma unroll
    for (int kt = 0; kt < 5; kt++) {
        s[kt][0] = s[kt][1] = s[kt][2] = s[kt][3] = 0.f;
#pragma unroll
        for (int c = 0; c < 4; c++) {
            uint32_t a0[4] = {qa[c].x, qb[c].x, qa[c].y, qb[c].y};
            uint32_t a1[4] = {qa[c].z, qb[c].z, qa[c].w, qb[c].w};
            mma16816(s[kt], a0, kv[kt][c].x, kv[kt][c].y);
            mma16816(s[kt], a1, kv[kt][c].z, kv[kt][c].w);
        }
    }
    const bf16* vmp = g_vm + ((size_t)seg * 8 + g) * 4096 + h * 128 + t * 8;
    const bf16* vxp = g_v + ((size_t)seg * 32 + g) * 4096 + h * 128 + t * 8;
#pragma unroll
    for (int c = 0; c < 4; c++) {
        kv[0][c] = ldcg128(vmp + c * 32);
#pragma unroll
        for (int kt = 1; kt < 5; kt++) kv[kt][c] = ldcg128(vxp + (size_t)(kt - 1) * 8 * 4096 + c * 32);
    }
    const float scale = 0.08838834764831845f;
    const int r0 = mt * 16 + g, r1 = r0 + 8;
    float m0 = -INFINITY, m1 = -INFINITY;
#pragma unroll
    for (int kt = 0; kt < 5; kt++) {
#pragma unroll
        for (int i = 0; i < 4; i++) {
            float v = bf16r(bf16r(s[kt][i]) * scale);
            if (kt > 0) { int key = (kt - 1) * 8 + 2 * t + (i & 1); if (key > (i < 2 ? r0 : r1)) v = -1.0e9f; }
            s[kt][i] = v;
            if (i < 2) m0 = fmaxf(m0, v); else m1 = fmaxf(m1, v);
        }
    }
    m0 = fmaxf(m0, __shfl_xor_sync(0xffffffff, m0, 1)); m0 = fmaxf(m0, __shfl_xor_sync(0xffffffff, m0, 2));
    m1 = fmaxf(m1, __shfl_xor_sync(0xffffffff, m1, 1)); m1 = fmaxf(m1, __shfl_xor_sync(0xffffffff, m1, 2));
    float l0 = 0, l1 = 0;
#pragma unroll
    for (int kt = 0; kt < 5; kt++) {
        s[kt][0] = __expf(s[kt][0] - m0); s[kt][1] = __expf(s[kt][1] - m0); l0 += s[kt][0] + s[kt][1];
        s[kt][2] = __expf(s[kt][2] - m1); s[kt][3] = __expf(s[kt][3] - m1); l1 += s[kt][2] + s[kt][3];
    }
    l0 += __shfl_xor_sync(0xffffffff, l0, 1); l0 += __shfl_xor_sync(0xffffffff, l0, 2);
    l1 += __shfl_xor_sync(0xffffffff, l1, 1); l1 += __shfl_xor_sync(0xffffffff, l1, 2);
    const float i0 = __fdividef(1.0f, l0), i1 = __fdividef(1.0f, l1);
    uint32_t p[6][2];
#pragma unroll
    for (int kt = 0; kt < 5; kt++) { p[kt][0] = pack_bf16(s[kt][0] * i0, s[kt][1] * i0); p[kt][1] = pack_bf16(s[kt][2] * i1, s[kt][3] * i1); }
    p[5][0] = p[5][1] = 0;
    bf16* op = g_o + (row0 + g) * 4096 + h * 128 + t * 8;
#pragma unroll
    for (int c = 0; c < 4; c++) {
        float o[4][4];
#pragma unroll
        for (int i = 0; i < 4; i++) {
            o[i][0] = o[i][1] = o[i][2] = o[i][3] = 0.f;
            uint32_t bt[6];
#pragma unroll
            for (int kt = 0; kt < 5; kt++) { uint32_t w = i == 0 ? kv[kt][c].x : (i == 1 ? kv[kt][c].y : (i == 2 ? kv[kt][c].z : kv[kt][c].w)); bt[kt] = movmatrix_t(w); }
            bt[5] = 0;
#pragma unroll
            for (int ks = 0; ks < 3; ks++) {
                uint32_t a[4] = {p[2 * ks][0], p[2 * ks][1], p[2 * ks + 1][0], p[2 * ks + 1][1]};
                mma16816(o[i], a, bt[2 * ks], bt[2 * ks + 1]);
            }
        }
        stg128(op + c * 32, make_uint4(pack_bf16(o[0][0], o[0][1]), pack_bf16(o[1][0], o[1][1]), pack_bf16(o[2][0], o[2][1]), pack_bf16(o[3][0], o[3][1])));
        stg128(op + 8 * 4096 + c * 32, make_uint4(pack_bf16(o[0][2], o[0][3]), pack_bf16(o[1][2], o[1][3]), pack_bf16(o[2][2], o[2][3]), pack_bf16(o[3][2], o[3][3])));
    }
}

__device__ __forceinline__ void stsm_x4(uint32_t addr, uint32_t a, uint32_t b, uint32_t c, uint32_t d) {
    asm volatile("stmatrix.sync.aligned.m8n8.x4.shared.b16 [%0], {%1,%2,%3,%4};" :: "r"(addr), "r"(a), "r"(b), "r"(c), "r"(d) : "memory");
}
__device__ __forceinline__ void tma_store_2d(const CUtensorMap* map, uint32_t src, int c0, int c1) {
    asm volatile("cp.async.bulk.tensor.2d.global.shared::cta.bulk_group [%0, {%2, %3}], [%1];" :: "l"(map), "r"(src), "r"(c0), "r"(c1) : "memory");
}

__global__ void __launch_bounds__(384, 1)
g_kernel(const __grid_constant__ GParams P, const bf16* __restrict__ x, const bf16* __restrict__ cvec, const bf16* __restrict__ w_mod, bf16* __restrict__ out, int nctas, int wait_r)
{
    using namespace gk;
    extern __shared__ __align__(1024) uint8_t smem[];
    const uint32_t sb = smem_u32(smem);
    const int tid = threadIdx.x, warp = tid >> 5, lane = tid & 31;
    const uint32_t b_full = sb + OFF_BAR, b_empty = b_full + 8 * STAGES, b_wfull = b_empty + 8 * STAGES, b_wempty = b_wfull + 16;
    volatile int* wslot = (volatile int*)(smem + OFF_BAR + 128);
    volatile int* lastflag = (volatile int*)(smem + OFF_BAR + 144);
    const uint32_t epoch = ld_relaxed(&g_epoch);
    const uint32_t e1 = epoch + 1;
    if (tid == 0) {
        for (int i = 0; i < STAGES; i++) { mbar_init(b_full + 8 * i, 1); mbar_init(b_empty + 8 * i, 2); }
        for (int i = 0; i < 2; i++) { mbar_init(b_wfull + 8 * i, 1); mbar_init(b_wempty + 8 * i, 2); }
        asm volatile("fence.mbarrier_init.release.cluster;" ::: "memory");
    }
    __syncthreads();

    if (warp < 4) {
        asm volatile("setmaxnreg.dec.sync.aligned.u32 40;");
        if (warp == 0 && lane == 0) {
            uint32_t stage = 0, sph = 1, wi = 0, wph = 1;
            const uint32_t tbase = epoch * (uint32_t)(N_ITEMS + nctas);
            while (true) {
                int tk = (int)(atomicAdd(&g_st.ticket, 1u) - tbase);
                Item it = decode(tk);
                if (it.type == T_SKIP) continue;
                switch (it.type) {
                    case T_L1: wait_ge(&g_st.c_mod_a, e1 * 20); break;
                    case T_KV: case T_Q: wait_ge(&g_st.f_h[it.rb * 32], e1 * 4); break;
                    case T_AT:
                        wait_ge(&g_st.qflag[it.rb * 32 + it.nt], e1);
                        wait_ge(&g_kvflag[it.rb * 64 + it.nt], e1); wait_ge(&g_kvflag[it.rb * 64 + 32 + it.nt], e1);
                        if (wait_r) { wait_ge(&g_rprog[(2 * it.nt) * 32], epoch * 64 + 4 * it.rb + 4); wait_ge(&g_rprog[(2 * it.nt + 1) * 32], epoch * 64 + 4 * it.rb + 4); }
                        break;
                    case T_WO: wait_ge(&g_st.c_o[it.rb * 32 + it.ks * 8], e1 * (32 / WO_SPLIT)); wait_ge(&g_st.c_mod_all, e1 * 60); break;
                    case T_L2: wait_ge(&g_st.c_x1[it.rb * 32], e1 * 5); break;
                    case T_F1: wait_ge(&g_st.f_h2[it.rb * 32], e1 * 4); break;
                    case T_F2: wait_ge(&g_st.c_act[it.rb * 32], e1 * 14); break;
                    default: break;
                }
                asm volatile("fence.proxy.async.global;" ::: "memory");
                mbar_wait(b_wempty + 8 * wi, wph);
                wslot[wi] = tk;
                mbar_arrive(b_wfull + 8 * wi);
                if (++wi == 2) { wi = 0; wph ^= 1; }
                if (it.type == T_END) break;
                int nkb = 0, kb0 = 0;
                const CUtensorMap *mA = nullptr, *mB0 = nullptr, *mB1 = nullptr; int n0 = 0, n1 = 0, nbox = 4;
                switch (it.type) {
                    case T_KV: nkb = 10; mA = &P.tA_h; mB0 = mB1 = (it.nt < 16) ? &P.tB_k : &P.tB_v; n0 = (it.nt & 15) * 256; n1 = n0 + 128; break;
                    case T_Q: nkb = 10; mA = &P.tA_h; mB0 = mB1 = &P.tB_q; n0 = it.nt * 256; n1 = n0 + 128; break;
                    case T_F1: nkb = 10; mA = &P.tA_h2; mB0 = &P.tB_g; mB1 = &P.tB_u; n0 = n1 = it.nt * 128; break;
                    case T_WO: nkb = 64 / WO_SPLIT; kb0 = it.ks * nkb; mA = &P.tA_o; mB0 = &P.tB_o; n0 = it.nt * 128; nbox = 2; break;
                    case T_F2: nkb = 27 / F2_SPLIT; kb0 = it.ks * nkb; mA = &P.tA_act; mB0 = &P.tB_d; n0 = it.nt * 128; nbox = 2; break;
                    default: break;
                }
                for (int kb = 0; kb < nkb; kb++) {
                    mbar_wait(b_empty + 8 * stage, sph);
                    const uint32_t st = sb + stage * STAGE_BYTES, bar = b_full + 8 * stage;
                    mbar_expect_tx(bar, 16384 + nbox * 8192);
                    const int k = (kb0 + kb) * 64;
                    tma_load_2d(st, mA, k, it.rb * 128, bar);
                    tma_load_2d(st + 16384, mB0, n0, k, bar);
                    tma_load_2d(st + 16384 + 8192, mB0, n0 + 64, k, bar);
                    if (nbox == 4) {
                        tma_load_2d(st + 16384 + 16384, mB1, n1, k, bar);
                        tma_load_2d(st + 16384 + 24576, mB1, n1 + 64, k, bar);
                    }
                    if (++stage == STAGES) { stage = 0; sph ^= 1; }
                }
            }
        }
    } else {
        asm volatile("setmaxnreg.inc.sync.aligned.u32 232;");
        const int ct = tid - 128, cw = warp - 4, wg = cw >> 2;
        const int g = lane >> 2, t = lane & 3;
        uint32_t stage = 0, sph = 0, wi = 0, wph = 0;
        while (true) {
            mbar_wait(b_wfull + 8 * wi, wph);
            const int tk = wslot[wi];
            __syncwarp();
            bar_sync(1 + wg, 128);
            if ((ct & 127) == 0) mbar_arrive(b_wempty + 8 * wi);
            if (++wi == 2) { wi = 0; wph ^= 1; }
            const Item it = decode(tk);
            if (it.type == T_END) break;
            const int rowb = it.rb * 128 + wg * 64 + (cw & 3) * 16 + g;
            if (it.type == T_KV || it.type == T_Q || it.type == T_F1) {
                float d[128];
#pragma unroll
                for (int i = 0; i < 128; i++) d[i] = 0.f;
                for (int kb = 0; kb < 10; kb++) {
                    mbar_wait(b_full + 8 * stage, sph);
                    const uint32_t st = sb + stage * STAGE_BYTES;
                    const uint64_t da = make_desc(st + wg * 8192, 16, 1024), db = make_desc(st + 16384, 8192, 1024);
                    wgmma_fence();
#pragma unroll
                    for (int k = 0; k < 4; k++) wgmma_n256(d, da + k * 2, db + k * 128, 1);
                    wgmma_commit();
                    wgmma_wait<1>();
                    if (kb > 0 && (ct & 127) == 0) mbar_arrive(b_empty + 8 * ((stage + STAGES - 1) % STAGES));
                    if (++stage == STAGES) { stage = 0; sph ^= 1; }
                }
                wgmma_wait<0>();
                if ((ct & 127) == 0) mbar_arrive(b_empty + 8 * ((stage + STAGES - 1) % STAGES));
                {
                    const uint32_t stg = sb + OFF_SCR + wg * 16384;
                    const int srow = (cw & 3) * 16 + ((lane >> 3) & 1) * 8 + (lane & 7);
                    const uint32_t sbase = stg + srow * 128;
                    const int sx = lane & 7, hi = lane >> 4;
                    const bool elect = (ct & 127) == 0;
                    const int grow = it.rb * 128 + wg * 64;
                    if (it.type == T_F1) {
#pragma unroll
                        for (int i = 0; i < 64; i++) d[i] = bf16r(gelu_tanh(bf16r(d[i]))) * bf16r(d[64 + i]);
                    }
                    const CUtensorMap* mS = it.type == T_F1 ? &P.tS_act : (it.type == T_Q ? &P.tS_q : (it.nt < 16 ? &P.tS_k : &P.tS_v));
                    const int gcol = it.type == T_F1 ? it.nt * 128 : (it.nt & 15) * 256;
#pragma unroll
                    for (int rnd = 0; rnd < 2; rnd++) {
                        if (rnd == 1 && it.type == T_F1) break;
                        if (elect) asm volatile("cp.async.bulk.wait_group.read 0;" ::: "memory");
                        bar_sync(1 + wg, 128);
#pragma unroll
                        for (int i = 0; i < 8; i++) {
                            const float* dd = d + rnd * 64 + i * 8;
                            const int chunk = (2 * i + hi) & 7;
                            stsm_x4(sbase + (i >> 2) * 8192 + ((chunk ^ sx) << 4), pack_bf16(dd[0], dd[1]), pack_bf16(dd[2], dd[3]), pack_bf16(dd[4], dd[5]), pack_bf16(dd[6], dd[7]));
                        }
                        asm volatile("fence.proxy.async.shared::cta;" ::: "memory");
                        bar_sync(1 + wg, 128);
                        if (elect) {
                            tma_store_2d(mS, stg, gcol + rnd * 128, grow);
                            tma_store_2d(mS, stg + 8192, gcol + rnd * 128 + 64, grow);
                            asm volatile("cp.async.bulk.commit_group;" ::: "memory");
                        }
                    }
                    if (elect) { asm volatile("cp.async.bulk.wait_group 0;" ::: "memory"); asm volatile("fence.proxy.async.global;" ::: "memory"); __threadfence(); }
                }
                bar_sync(3, 256);
                if (ct == 0) {
                    if (it.type == T_KV) { st_release(&g_kvflag[it.rb * 64 + it.nt * 2], e1); st_release(&g_kvflag[it.rb * 64 + it.nt * 2 + 1], e1); }
                    else if (it.type == T_Q) { st_release(&g_st.qflag[it.rb * 32 + it.nt * 2], e1); st_release(&g_st.qflag[it.rb * 32 + it.nt * 2 + 1], e1); }
                    else red_add_release(&g_st.c_act[it.rb * 32], 1);
                }
            } else if (it.type == T_WO || it.type == T_F2) {
                float d[64];
#pragma unroll
                for (int i = 0; i < 64; i++) d[i] = 0.f;
                const int nkb = it.type == T_WO ? 64 / WO_SPLIT : 27 / F2_SPLIT;
                const int nsplit = it.type == T_WO ? WO_SPLIT : F2_SPLIT;
                for (int kb = 0; kb < nkb; kb++) {
                    mbar_wait(b_full + 8 * stage, sph);
                    const uint32_t st = sb + stage * STAGE_BYTES;
                    const uint64_t da = make_desc(st + wg * 8192, 16, 1024), db = make_desc(st + 16384, 8192, 1024);
                    wgmma_fence();
#pragma unroll
                    for (int k = 0; k < 4; k++) wgmma_n128(d, da + k * 2, db + k * 128, 1);
                    wgmma_commit();
                    wgmma_wait<1>();
                    if (kb > 0 && (ct & 127) == 0) mbar_arrive(b_empty + 8 * ((stage + STAGES - 1) % STAGES));
                    if (++stage == STAGES) { stage = 0; sph ^= 1; }
                }
                wgmma_wait<0>();
                if ((ct & 127) == 0) mbar_arrive(b_empty + 8 * ((stage + STAGES - 1) % STAGES));
                float* slab = g_slab + (size_t)rowb * 640 + it.nt * 128 + 2 * t;
#pragma unroll
                for (int i = 0; i < 16; i++) {
                    asm volatile("red.relaxed.gpu.global.add.v2.f32 [%0], {%1,%2};" :: "l"(slab + 8 * i), "f"(d[4 * i]), "f"(d[4 * i + 1]) : "memory");
                    asm volatile("red.relaxed.gpu.global.add.v2.f32 [%0], {%1,%2};" :: "l"(slab + 8 * 640 + 8 * i), "f"(d[4 * i + 2]), "f"(d[4 * i + 3]) : "memory");
                }
                bar_sync(3, 256);
                if (ct == 0) {
                    __threadfence();
                    uint32_t* cnt = (it.type == T_WO ? g_st.c_wo : g_st.c_f2) + it.rb * 32 + it.nt;
                    uint32_t old = atom_add_acqrel(cnt, 1);
                    *lastflag = (old + 1 == e1 * nsplit);
                }
                bar_sync(3, 256);
                if (*lastflag) {
                    const bool wo = it.type == T_WO;
                    const float* gate = g_mod + (wo ? 2 : 5) * 640;
                    const bf16* res = wo ? x : g_x1;
                    bf16* dst = wo ? g_x1 : out;
                    const int c = it.nt * 128 + (ct & 31) * 4;
                    const float4 gt = ldcg_f4(gate + c);
#pragma unroll 1
                    for (int i0 = 0; i0 < 16; i0 += 8) {
                        float4 a[8]; uint2 rv[8];
#pragma unroll
                        for (int i = 0; i < 8; i++) {
                            const size_t off = (size_t)(it.rb * 128 + (i0 + i) * 8 + cw) * 640 + c;
                            a[i] = ldcg_f4(g_slab + off);
                            asm volatile("ld.global.cg.v2.u32 {%0,%1}, [%2];" : "=r"(rv[i].x), "=r"(rv[i].y) : "l"(res + off) : "memory");
                        }
#pragma unroll
                        for (int i = 0; i < 8; i++) {
                            const size_t off = (size_t)(it.rb * 128 + (i0 + i) * 8 + cw) * 640 + c;
                            float y0 = __uint_as_float(rv[i].x << 16) + bf16r(gt.x * bf16r(a[i].x));
                            float y1 = __uint_as_float(rv[i].x & 0xffff0000u) + bf16r(gt.y * bf16r(a[i].y));
                            float y2 = __uint_as_float(rv[i].y << 16) + bf16r(gt.z * bf16r(a[i].z));
                            float y3 = __uint_as_float(rv[i].y & 0xffff0000u) + bf16r(gt.w * bf16r(a[i].w));
                            *(uint2*)(dst + off) = make_uint2(pack_bf16(y0, y1), pack_bf16(y2, y3));
                            *(float4*)(g_slab + off) = make_float4(0.f, 0.f, 0.f, 0.f);
                        }
                    }
                    if (wo) {
                        bar_sync(3, 256);
                        if (ct == 0) { __threadfence(); red_add_release(&g_st.c_x1[it.rb * 32], 1); }
                    }
                }
                bar_sync(3, 256);
            } else if (it.type == T_AT) {
                attn_task(it.rb * 4 + (cw >> 1), it.nt, cw & 1, lane);
                bar_sync(3, 256);
                if (ct == 0) red_add_release(&g_st.c_o[it.rb * 32 + (it.nt / (32 / WO_SPLIT)) * 8], 1);
            } else if (it.type == T_L1 || it.type == T_L2) {
                const size_t row = (size_t)it.rb * 128 + it.nt * 32 + cw * 4;
                const bool l1 = it.type == T_L1;
                ln_rows((l1 ? x : g_x1) + row * 640, (l1 ? g_h : g_h2) + row * 640, g_mod + (l1 ? 0 : 3 * 640), g_mod + (l1 ? 640 : 4 * 640), lane, 4);
                bar_sync(3, 256);
                if (ct == 0) red_add_release((it.type == T_L1 ? g_st.f_h : g_st.f_h2) + it.rb * 32, 1);
            } else if (it.type == T_MOD) {
                const int kg = ct >> 3, c8 = ct & 7;
                float acc[8] = {0, 0, 0, 0, 0, 0, 0, 0};
                const bf16* wp = w_mod + (size_t)kg * 20 * 3840 + it.nt * 64 + c8 * 8;
#pragma unroll 1
                for (int i0 = 0; i0 < 20; i0 += 10) {
                    uint4 w[10]; float sl[10];
#pragma unroll
                    for (int i = 0; i < 10; i++) { w[i] = __ldg((const uint4*)(wp + (size_t)(i0 + i) * 3840)); sl[i] = __bfloat162float(cvec[kg * 20 + i0 + i]); }
#pragma unroll
                    for (int i = 0; i < 10; i++) {
                        const float s = bf16r(__fdividef(sl[i], 1.0f + __expf(-sl[i])));
                        acc[0] += s * __uint_as_float(w[i].x << 16); acc[1] += s * __uint_as_float(w[i].x & 0xffff0000u);
                        acc[2] += s * __uint_as_float(w[i].y << 16); acc[3] += s * __uint_as_float(w[i].y & 0xffff0000u);
                        acc[4] += s * __uint_as_float(w[i].z << 16); acc[5] += s * __uint_as_float(w[i].z & 0xffff0000u);
                        acc[6] += s * __uint_as_float(w[i].w << 16); acc[7] += s * __uint_as_float(w[i].w & 0xffff0000u);
                    }
                }
                float* scr = (float*)(smem + OFF_SCR);
#pragma unroll
                for (int i = 0; i < 8; i++) scr[kg * 64 + c8 * 8 + i] = acc[i];
                bar_sync(3, 256);
                if (ct < 64) {
                    float sum = 0;
#pragma unroll 8
                    for (int i = 0; i < 32; i++) sum += scr[i * 64 + ct];
                    g_mod[it.nt * 64 + ct] = bf16r(sum);
                }
                bar_sync(3, 256);
                if (ct == 0) { if (it.nt < 20) red_add_release(&g_st.c_mod_a, 1); red_add_release(&g_st.c_mod_all, 1); }
            }
        }
        if (ct == 0) {
            uint32_t old = atom_add_acqrel(&g_st.done, 1);
            if (old + 1 == e1 * (uint32_t)nctas) st_release(&g_epoch, e1);
        }
    }
}

typedef CUresult (*PFN_encodeTiled)(CUtensorMap*, CUtensorMapDataType, cuuint32_t, void*, const cuuint64_t*, const cuuint64_t*, const cuuint32_t*, const cuuint32_t*, CUtensorMapInterleave, CUtensorMapSwizzle, CUtensorMapL2promotion, CUtensorMapFloatOOBfill);

static void make_map(PFN_encodeTiled fn, CUtensorMap* m, const void* ptr, uint64_t inner, uint64_t outer, uint32_t box_inner, uint32_t box_outer) {
    cuuint64_t dims[2] = {inner, outer};
    cuuint64_t strides[1] = {inner * 2};
    cuuint32_t box[2] = {box_inner, box_outer};
    cuuint32_t es[2] = {1, 1};
    fn(m, CU_TENSOR_MAP_DATA_TYPE_BFLOAT16, 2, (void*)ptr, dims, strides, box, es, CU_TENSOR_MAP_INTERLEAVE_NONE, CU_TENSOR_MAP_SWIZZLE_128B, CU_TENSOR_MAP_L2_PROMOTION_L2_256B, CU_TENSOR_MAP_FLOAT_OOB_FILL_NONE);
}

static int g_dbg_mode = 0;

extern "C" void kernel_launch(void* const* d_in, const int* in_sizes, int n_in, void* d_out, int out_size) {
    const bf16* x = (const bf16*)d_in[0];
    const bf16* mem0 = (const bf16*)d_in[1];
    const bf16* Wq = (const bf16*)d_in[2];
    const bf16* Wk = (const bf16*)d_in[3];
    const bf16* Wv = (const bf16*)d_in[4];
    const bf16* Wo = (const bf16*)d_in[5];
    const bf16* Wg = (const bf16*)d_in[8];
    const bf16* Wu = (const bf16*)d_in[9];
    const bf16* Wd = (const bf16*)d_in[10];
    const bf16* cvec = (const bf16*)d_in[11];
    const bf16* wmod = (const bf16*)d_in[12];
    static PFN_encodeTiled fn = nullptr;
    static int nsm = 0;
    if (!fn) {
        cudaDriverEntryPointQueryResult qr;
        cudaGetDriverEntryPoint("cuTensorMapEncodeTiled", (void**)&fn, cudaEnableDefault, &qr);
        cudaFuncSetAttribute(r_kernel, cudaFuncAttributeMaxDynamicSharedMemorySize, rk::SMEM_BYTES);
        cudaFuncSetAttribute(r_kernel, cudaFuncAttributeNonPortableClusterSizeAllowed, 1);
        cudaFuncSetAttribute(g_kernel, cudaFuncAttributeMaxDynamicSharedMemorySize, gk::SMEM_BYTES);
        cudaDeviceGetAttribute(&nsm, cudaDevAttrMultiProcessorCount, 0);
    }
    void *ph, *po, *ph2, *pact, *pq, *pk, *pv;
    cudaGetSymbolAddress(&pq, g_q); cudaGetSymbolAddress(&pk, g_k); cudaGetSymbolAddress(&pv, g_v);
    cudaGetSymbolAddress(&ph, g_h); cudaGetSymbolAddress(&po, g_o); cudaGetSymbolAddress(&ph2, g_h2); cudaGetSymbolAddress(&pact, g_act);
    GParams P;
    make_map(fn, &P.tA_h, ph, 640, 2048, 64, 128);
    make_map(fn, &P.tA_o, po, 4096, 2048, 64, 128);
    make_map(fn, &P.tA_h2, ph2, 640, 2048, 64, 128);
    make_map(fn, &P.tA_act, pact, 1728, 2048, 64, 128);
    make_map(fn, &P.tB_q, Wq, 4096, 640, 64, 64);
    make_map(fn, &P.tB_k, Wk, 4096, 640, 64, 64);
    make_map(fn, &P.tB_v, Wv, 4096, 640, 64, 64);
    make_map(fn, &P.tB_o, Wo, 640, 4096, 64, 64);
    make_map(fn, &P.tB_g, Wg, 1728, 640, 64, 64);
    make_map(fn, &P.tB_u, Wu, 1728, 640, 64, 64);
    make_map(fn, &P.tB_d, Wd, 640, 1728, 64, 64);
    make_map(fn, &P.tS_q, pq, 4096, 2048, 64, 64);
    make_map(fn, &P.tS_k, pk, 4096, 2048, 64, 64);
    make_map(fn, &P.tS_v, pv, 4096, 2048, 64, 64);
    make_map(fn, &P.tS_act, pact, 1728, 2048, 64, 64);
    cudaStream_t st = cudaStreamPerThread;
    if (g_dbg_mode != 1) {
        cudaLaunchConfig_t cfg = {};
        cfg.gridDim = dim3(64); cfg.blockDim = dim3(256); cfg.dynamicSmemBytes = rk::SMEM_BYTES; cfg.stream = st;
        cudaLaunchAttribute at[1]; at[0].id = cudaLaunchAttributeClusterDimension; at[0].val.clusterDim.x = 16; at[0].val.clusterDim.y = 1; at[0].val.clusterDim.z = 1;
        cfg.attrs = at; cfg.numAttrs = 1;
        CUtensorMap tk, tv;
        make_map(fn, &tk, pk, 4096, 2048, 64, 32);
        make_map(fn, &tv, pv, 4096, 2048, 64, 32);
        cudaLaunchKernelEx(&cfg, r_kernel, tk, tv, mem0, Wq, Wk, Wv, Wo, 1);
    }
    {
        cudaLaunchConfig_t cfg = {};
        cfg.gridDim = dim3(nsm); cfg.blockDim = dim3(384); cfg.dynamicSmemBytes = gk::SMEM_BYTES; cfg.stream = st;
        cudaLaunchAttribute at[1]; at[0].id = cudaLaunchAttributeProgrammaticStreamSerialization; at[0].val.programmaticStreamSerializationAllowed = 1;
        cfg.attrs = at; cfg.numAttrs = g_dbg_mode == 1 ? 0 : 1;
        cudaLaunchKernelEx(&cfg, g_kernel, P, x, cvec, wmod, (bf16*)d_out, nsm, g_dbg_mode == 1 ? 0 : 1);
    }
}
```

```cpp
#include <cuda_runtime.h>
#include <cuda_bf16.h>
#include <cuda.h>
#include <stdint.h>

typedef __nv_bfloat16 bf16;

__device__ __forceinline__ uint32_t smem_u32(const void* p) { return (uint32_t)__cvta_generic_to_shared(p); }
__device__ __forceinline__ uint32_t mapa_u32(uint32_t a, uint32_t r) { uint32_t o; asm volatile("mapa.shared::cluster.u32 %0, %1, %2;" : "=r"(o) : "r"(a), "r"(r)); return o; }
__device__ __forceinline__ void mbar_init(uint32_t bar, uint32_t cnt) { asm volatile("mbarrier.init.shared::cta.b64 [%0], %1;" :: "r"(bar), "r"(cnt) : "memory"); }
__device__ __forceinline__ void mbar_expect_tx(uint32_t bar, uint32_t bytes) { asm volatile("mbarrier.arrive.expect_tx.shared::cta.b64 _, [%0], %1;" :: "r"(bar), "r"(bytes) : "memory"); }
__device__ __forceinline__ void mbar_arrive(uint32_t bar) { asm volatile("mbarrier.arrive.shared::cta.b64 _, [%0];" :: "r"(bar) : "memory"); }
#define SPIN_LIMIT 4000000
__device__ __forceinline__ void mbar_wait(uint32_t bar, uint32_t ph) {
    uint32_t ok = 0; int lim = 0;
    while (true) {
        asm volatile("{ .reg .pred p; mbarrier.try_wait.parity.shared::cta.b64 p, [%1], %2; selp.u32 %0, 1, 0, p; }" : "=r"(ok) : "r"(bar), "r"(ph) : "memory");
        if (ok) break;
        if (++lim > SPIN_LIMIT) break;
    }
}
__device__ __forceinline__ void mbar_wait_cluster(uint32_t bar, uint32_t ph) {
    uint32_t ok = 0; int lim = 0;
    while (true) {
        asm volatile("{ .reg .pred p; mbarrier.try_wait.parity.acquire.cluster.shared::cta.b64 p, [%1], %2; selp.u32 %0, 1, 0, p; }" : "=r"(ok) : "r"(bar), "r"(ph) : "memory");
        if (ok) break;
        if (++lim > SPIN_LIMIT) break;
    }
}
__device__ __forceinline__ void st_async_v4(uint32_t addr, uint32_t a, uint32_t b, uint32_t c, uint32_t d, uint32_t bar) {
    asm volatile("st.async.weak.shared::cluster.mbarrier::complete_tx::bytes.v4.b32 [%0], {%1,%2,%3,%4}, [%5];" :: "r"(addr), "r"(a), "r"(b), "r"(c), "r"(d), "r"(bar) : "memory");
}
__device__ __forceinline__ void ldsm_x4(uint32_t* r, uint32_t addr) {
    asm volatile("ldmatrix.sync.aligned.m8n8.x4.shared.b16 {%0,%1,%2,%3}, [%4];" : "=r"(r[0]), "=r"(r[1]), "=r"(r[2]), "=r"(r[3]) : "r"(addr) : "memory");
}
__device__ __forceinline__ void ldsm_x4_t(uint32_t* r, uint32_t addr) {
    asm volatile("ldmatrix.sync.aligned.m8n8.x4.trans.shared.b16 {%0,%1,%2,%3}, [%4];" : "=r"(r[0]), "=r"(r[1]), "=r"(r[2]), "=r"(r[3]) : "r"(addr) : "memory");
}
__device__ __forceinline__ void mma16816(float* d, const uint32_t* a, uint32_t b0, uint32_t b1) {
    asm volatile("mma.sync.aligned.m16n8k16.row.col.f32.bf16.bf16.f32 {%0,%1,%2,%3}, {%4,%5,%6,%7}, {%8,%9}, {%0,%1,%2,%3};"
        : "+f"(d[0]), "+f"(d[1]), "+f"(d[2]), "+f"(d[3]) : "r"(a[0]), "r"(a[1]), "r"(a[2]), "r"(a[3]), "r"(b0), "r"(b1));
}
__device__ __forceinline__ uint32_t pack_bf16(float lo, float hi) {
    uint32_t r; asm("cvt.rn.bf16x2.f32 %0, %1, %2;" : "=r"(r) : "f"(hi), "f"(lo)); return r;
}
__device__ __forceinline__ float bf16r(float x) { return __bfloat162float(__float2bfloat16_rn(x)); }
__device__ __forceinline__ uint4 lds128(uint32_t a) { uint4 v; asm volatile("ld.shared.v4.u32 {%0,%1,%2,%3}, [%4];" : "=r"(v.x), "=r"(v.y), "=r"(v.z), "=r"(v.w) : "r"(a) : "memory"); return v; }
__device__ __forceinline__ void sts128(uint32_t a, uint4 v) { asm volatile("st.shared.v4.u32 [%0], {%1,%2,%3,%4};" :: "r"(a), "r"(v.x), "r"(v.y), "r"(v.z), "r"(v.w) : "memory"); }
__device__ __forceinline__ void sts32(uint32_t a, uint32_t v) { asm volatile("st.shared.u32 [%0], %1;" :: "r"(a), "r"(v) : "memory"); }
__device__ __forceinline__ void sts64(uint32_t a, uint32_t x, uint32_t y) { asm volatile("st.shared.v2.u32 [%0], {%1,%2};" :: "r"(a), "r"(x), "r"(y) : "memory"); }
__device__ __forceinline__ void sts16(uint32_t a, uint16_t v) { asm volatile("st.shared.u16 [%0], %1;" :: "r"(a), "h"(v) : "memory"); }
__device__ __forceinline__ uint2 lds64(uint32_t a) { uint2 v; asm volatile("ld.shared.v2.u32 {%0,%1}, [%2];" : "=r"(v.x), "=r"(v.y) : "r"(a) : "memory"); return v; }
__device__ __forceinline__ void cp_async16(uint32_t dst, const void* src) { asm volatile("cp.async.cg.shared.global [%0], [%1], 16;" :: "r"(dst), "l"(src) : "memory"); }
__device__ __forceinline__ void cp_async_wait_all() { asm volatile("cp.async.wait_all;" ::: "memory"); }
__device__ __forceinline__ void bar_sync(int id, int n) { asm volatile("bar.sync %0, %1;" :: "r"(id), "r"(n) : "memory"); }
__device__ __forceinline__ uint4 ld_relaxed_v4(const void* p) {
    uint4 v; asm volatile("ld.relaxed.gpu.global.v4.u32 {%0,%1,%2,%3}, [%4];" : "=r"(v.x), "=r"(v.y), "=r"(v.z), "=r"(v.w) : "l"(p) : "memory"); return v;
}
__device__ __forceinline__ void st_relaxed_v4(void* p, uint4 v) {
    asm volatile("st.relaxed.gpu.global.v4.u32 [%0], {%1,%2,%3,%4};" :: "l"(p), "r"(v.x), "r"(v.y), "r"(v.z), "r"(v.w) : "memory");
}
__device__ __forceinline__ uint32_t ld_acquire(const uint32_t* p) { uint32_t v; asm volatile("ld.acquire.gpu.global.u32 %0, [%1];" : "=r"(v) : "l"(p) : "memory"); return v; }
__device__ __forceinline__ uint32_t ld_relaxed(const uint32_t* p) { uint32_t v; asm volatile("ld.relaxed.gpu.global.u32 %0, [%1];" : "=r"(v) : "l"(p) : "memory"); return v; }
__device__ __forceinline__ void st_release(uint32_t* p, uint32_t v) { asm volatile("st.release.gpu.global.u32 [%0], %1;" :: "l"(p), "r"(v) : "memory"); }
__device__ __forceinline__ void cluster_sync_all() {
    asm volatile("barrier.cluster.arrive.release.aligned;" ::: "memory");
    asm volatile("barrier.cluster.wait.acquire.aligned;" ::: "memory");
}

__device__ bf16 g_k[2048 * 4096];
__device__ bf16 g_v[2048 * 4096];
__device__ bf16 g_km[64 * 8 * 4096];
__device__ bf16 g_vm[64 * 8 * 4096];
__device__ uint4 g_gx[2][4][16][80];
__device__ uint32_t g_rprog[64 * 32];
__device__ uint32_t g_kvflag[16 * 64];
__device__ uint32_t g_epoch;

namespace rk {
constexpr int MEM_STRIDE = 1296;
constexpr int T_STRIDE = 272;
constexpr int OFF_W = 0;
constexpr int OFF_KX = 163840;
constexpr int OFF_VX = OFF_KX + 8192;
constexpr int OFF_MEM = OFF_VX + 8192;
constexpr int OFF_Q = OFF_MEM + 10240;
constexpr int OFF_KM = OFF_Q + 8 * T_STRIDE;
constexpr int OFF_VM = OFF_KM + 8 * T_STRIDE;
constexpr int OFF_O = OFF_VM + 8 * T_STRIDE;
constexpr int OFF_SC = OFF_O + 8 * T_STRIDE;
constexpr int OFF_RED = OFF_SC + 8 * 56 * 4;
constexpr int OFF_RS = OFF_RED + 6144;
constexpr int OFF_ST = OFF_RS + 8 * 80 * 16;
constexpr int OFF_BAR = OFF_ST + 640;
constexpr int OFF_TL = OFF_BAR + 128;
constexpr int SMEM_BYTES = OFF_TL + 512;

__device__ __forceinline__ void load_frag(uint32_t* a, const bf16* __restrict__ W, int ld, int ka, int kb, int cb, int g, int t) {
    const uint32_t* p = (const uint32_t*)(W + (size_t)(ka + 2 * t) * ld + cb + 2 * g);
    const uint32_t* q = (const uint32_t*)(W + (size_t)(kb + 2 * t) * ld + cb + 2 * g);
    int ldw = ld / 2;
    uint32_t w0 = __ldg(p), w1 = __ldg(p + ldw), w2 = __ldg(q), w3 = __ldg(q + ldw);
    a[0] = __byte_perm(w0, w1, 0x5410); a[1] = __byte_perm(w0, w1, 0x7632);
    a[2] = __byte_perm(w2, w3, 0x5410); a[3] = __byte_perm(w2, w3, 0x7632);
}
__device__ __forceinline__ int chunk_src(int d, int kh, int n) { return (d - 8 * kh - n / 5) & 15; }
__device__ __forceinline__ int chunk_col(int d, int kh, int n) { const int s = chunk_src(d, kh, n); return 320 * (s & 1) + 40 * (s >> 1) + 8 * (n % 5); }
}

#define TL(i)
#define TG(i)

__device__ __forceinline__ void tma_load_2d(uint32_t dst, const CUtensorMap* map, int c0, int c1, uint32_t bar) {
    asm volatile("cp.async.bulk.tensor.2d.shared::cluster.global.mbarrier::complete_tx::bytes [%0], [%1, {%3, %4}], [%2];"
        :: "r"(dst), "l"(map), "r"(bar), "r"(c0), "r"(c1) : "memory");
}
__device__ __forceinline__ uint32_t movmatrix_t(uint32_t a) { uint32_t d; asm volatile("movmatrix.sync.aligned.m8n8.trans.b16 %0, %1;" : "=r"(d) : "r"(a)); return d; }
__device__ __forceinline__ void stg128(void* p, uint4 v) { asm volatile("st.global.v4.u32 [%0], {%1,%2,%3,%4};" :: "l"(p), "r"(v.x), "r"(v.y), "r"(v.z), "r"(v.w) : "memory"); }

__global__ void __launch_bounds__(256, 1)
r_kernel(const __grid_constant__ CUtensorMap tmK, const __grid_constant__ CUtensorMap tmV, const bf16* __restrict__ mem0, const bf16* __restrict__ Wq, const bf16* __restrict__ Wk, const bf16* __restrict__ Wv, const bf16* __restrict__ Wo, int wait_kv)
{
    using namespace rk;
    extern __shared__ __align__(1024) uint8_t smem[];
    const uint32_t sb = smem_u32(smem);
    const int tid = threadIdx.x, warp = tid >> 5, lane = tid & 31, g = lane >> 2, t = lane & 3;
    uint32_t rank, cid;
    asm volatile("mov.u32 %0, %%cluster_ctarank;" : "=r"(rank));
    asm volatile("mov.u32 %0, %%clusterid.x;" : "=r"(cid));
    const int hh = rank >> 1, j = rank & 1, h = cid * 8 + hh;
    const int kh = warp & 1, mb = warp >> 1;
    const uint32_t b_mem = sb + OFF_BAR, b_qkv = b_mem + 64, b_rs = b_mem + 72, b_kv = b_mem + 80;

    asm volatile("griddepcontrol.launch_dependents;");
    const uint32_t epoch = ld_relaxed(&g_epoch);

    if (tid == 0) {
        for (int i = 0; i < 8; i++) mbar_init(b_mem + 8 * i, 1);
        mbar_init(b_qkv, 9); mbar_init(b_rs, 1); mbar_init(b_kv, 1);
        asm volatile("fence.mbarrier_init.release.cluster;" ::: "memory");
    }
    const uint32_t wsm = sb + OFF_W + (warp < 4 ? warp * 22528 : 4 * 22528 + (warp - 4) * 18432) + lane * 16;
    uint32_t wq[20][4], wk[20][4];
    {
        const int cb = h * 128 + 64 * j + 16 * mb;
#pragma unroll
        for (int i = 0; i < 20; i++) load_frag(wq[i], Wq, 4096, chunk_col(rank, kh, 2 * i), chunk_col(rank, kh, 2 * i + 1), cb, g, t);
#pragma unroll
        for (int i = 0; i < 20; i++) load_frag(wk[i], Wk, 4096, chunk_col(rank, kh, 2 * i), chunk_col(rank, kh, 2 * i + 1), cb, g, t);
#pragma unroll 4
        for (int i = 0; i < 20; i++) { uint32_t a[4]; load_frag(a, Wv, 4096, chunk_col(rank, kh, 2 * i), chunk_col(rank, kh, 2 * i + 1), cb, g, t); sts128(wsm + i * 512, make_uint4(a[0], a[1], a[2], a[3])); }
        const bf16* Woh = Wo + (size_t)h * 128 * 640;
        const int c3 = 320 * j + 16 * warp;
        const int n3 = warp < 4 ? 24 : 16;
#pragma unroll 4
        for (int i = 0; i < n3; i++) { uint32_t a[4]; load_frag(a, Woh, 640, (i & 7) * 16, (i & 7) * 16 + 8, c3 + 128 * (i >> 3), g, t); sts128(wsm + (20 + i) * 512, make_uint4(a[0], a[1], a[2], a[3])); }
    }
    for (int i = tid; i < 640; i += 256) {
        int row = i / 80, c = i % 80;
        uint4 v = __ldg((const uint4*)(mem0 + row * 640 + c * 8));
        const int jj = c / 40, h5 = (c % 40) / 5;
        sts128(sb + OFF_MEM + (((int)rank - (2 * h5 + jj)) & 15) * 640 + row * 80 + (c % 5) * 16, v);
    }
    auto prefetch_kv = [&](int s) {
        if ((wait_kv & 1) && (s & 3) == 0) {
            const uint32_t* fk = &g_kvflag[(s >> 2) * 64 + h];
            int lim = 0;
            while (ld_acquire(fk) != epoch + 1) { if (++lim > SPIN_LIMIT) break; }
            while (ld_acquire(fk + 32) != epoch + 1) { if (++lim > SPIN_LIMIT) break; }
            asm volatile("fence.proxy.async.global;" ::: "memory");
        }
        mbar_expect_tx(b_kv, 16384);
        tma_load_2d(sb + OFF_KX, &tmK, h * 128, s * 32, b_kv);
        tma_load_2d(sb + OFF_KX + 4096, &tmK, h * 128 + 64, s * 32, b_kv);
        tma_load_2d(sb + OFF_VX, &tmV, h * 128, s * 32, b_kv);
        tma_load_2d(sb + OFF_VX + 4096, &tmV, h * 128 + 64, s * 32, b_kv);
    };
    __syncthreads();
    if (tid == 128) prefetch_kv(0);
    __syncthreads();
    cluster_sync_all();

    const float scale = 0.08838834764831845f;
#define LAUNDER() int tid_ = threadIdx.x; asm volatile("" : "+r"(tid_)); const int warp = tid_ >> 5, lane = tid_ & 31, g = lane >> 2, t = lane & 3; (void)g; (void)t; (void)warp;
#define WSM() (sb + OFF_W + (warp < 4 ? warp * 22528 : 4 * 22528 + (warp - 4) * 18432) + lane * 16)

#pragma unroll 1
    for (int s = 0; s < 64; s++) {
        const uint32_t ph = s & 1;
        {
            LAUNDER();
            TL(0);
            const int kh = warp & 1, mb = warp >> 1;
            const uint32_t wsm = WSM();
            const uint32_t mb0 = sb + OFF_MEM + kh * 5120 + (lane & 7) * 80 + (lane >> 3) * 16;
            const uint32_t mb1 = mb0 + ((lane >> 3) >= 1 ? 560 : 0), mb2 = mb0 + ((lane >> 3) >= 2 ? 560 : 0), mb3 = mb0 + ((lane >> 3) >= 3 ? 560 : 0);
            auto baddr = [&](int it) {
                const int r5 = (4 * it) % 5, c = ((4 * it) / 5) * 640 + r5 * 16;
                return (r5 <= 1 ? mb0 : (r5 == 4 ? mb1 : (r5 == 3 ? mb2 : mb3))) + c;
            };
            uint4 va[6];
            va[0] = lds128(wsm); va[1] = lds128(wsm + 512); va[2] = lds128(wsm + 1024); va[3] = lds128(wsm + 1536);
            if (s > 0) { mbar_wait(b_mem, ph ^ 1); mbar_wait(b_mem + 8, ph ^ 1); }
            TL(1); TG(15);
            float aq0[4] = {0, 0, 0, 0}, aq1[4] = {0, 0, 0, 0}, ak0[4] = {0, 0, 0, 0}, ak1[4] = {0, 0, 0, 0}, av0[4] = {0, 0, 0, 0}, av1[4] = {0, 0, 0, 0};
            uint32_t b[3][4];
            ldsm_x4(b[0], baddr(0)); ldsm_x4(b[1], baddr(1));
            if (tid_ == 0) {
                mbar_expect_tx(b_qkv, 3072);
                if (s < 63) mbar_expect_tx(b_rs, 10240);
            }
#pragma unroll
            for (int i = 0; i < 10; i++) {
                if (i + 2 < 10) {
                    const int it = i + 2, sl = (4 * it + 3) / 5, slp = (4 * (it - 1) + 3) / 5;
                    if (sl != slp && s > 0) mbar_wait(b_mem + 8 * sl, ph ^ 1);
                    ldsm_x4(b[(i + 2) % 3], baddr(i + 2));
                    va[(2 * i + 4) % 6] = lds128(wsm + (2 * i + 4) * 512); va[(2 * i + 5) % 6] = lds128(wsm + (2 * i + 5) * 512);
                }
                const uint32_t* bb = b[i % 3];
                mma16816(aq0, wq[2 * i], bb[0], bb[1]); mma16816(ak0, wk[2 * i], bb[0], bb[1]); mma16816(av0, (uint32_t*)&va[(2 * i) % 6], bb[0], bb[1]);
                mma16816(aq1, wq[2 * i + 1], bb[2], bb[3]); mma16816(ak1, wk[2 * i + 1], bb[2], bb[3]); mma16816(av1, (uint32_t*)&va[(2 * i + 1) % 6], bb[2], bb[3]);
            }
            float snd[4], fin[4];
#pragma unroll
            for (int i = 0; i < 4; i++) { float q = aq0[i] + aq1[i], k = ak0[i] + ak1[i]; snd[i] = kh ? q : k; fin[i] = kh ? k : q; av0[i] += av1[i]; }
            sts128(sb + OFF_RED + tid_ * 16, make_uint4(__float_as_uint(snd[0]), __float_as_uint(snd[1]), __float_as_uint(snd[2]), __float_as_uint(snd[3])));
            sts64(sb + OFF_RED + 4096 + tid_ * 8, __float_as_uint(kh ? av0[0] : av0[1]), __float_as_uint(kh ? av0[2] : av0[3]));
            bar_sync(1 + mb, 64);
            uint4 r = lds128(sb + OFF_RED + (tid_ ^ 32) * 16);
            uint2 r2 = lds64(sb + OFF_RED + 4096 + (tid_ ^ 32) * 8);
            fin[0] += __uint_as_float(r.x); fin[1] += __uint_as_float(r.y); fin[2] += __uint_as_float(r.z); fin[3] += __uint_as_float(r.w);
            float f0 = (kh ? av0[1] : av0[0]) + __uint_as_float(r2.x), f1 = (kh ? av0[3] : av0[2]) + __uint_as_float(r2.y);
            TL(2);
            const uint32_t cofs = (64 * j + 16 * mb) * 2;
            const uint32_t buf = sb + (kh ? OFF_KM : OFF_Q) + cofs;
            sts32(buf + (2 * t) * T_STRIDE + g * 4, pack_bf16(fin[0], fin[2]));
            sts32(buf + (2 * t + 1) * T_STRIDE + g * 4, pack_bf16(fin[1], fin[3]));
            sts32(sb + OFF_VM + cofs + (2 * t + kh) * T_STRIDE + g * 4, pack_bf16(f0, f1));
            __syncwarp();
            if (lane < 24) {
                const uint32_t peer_off = mapa_u32(sb, rank ^ 1) - sb;
                const int row = lane < 16 ? (lane >> 1) : 2 * ((lane - 16) >> 1) + kh;
                const uint32_t a = (lane < 16 ? buf : sb + OFF_VM + cofs) + row * T_STRIDE + (lane & 1) * 16;
                uint4 v = lds128(a);
                st_async_v4(a + peer_off, v.x, v.y, v.z, v.w, b_qkv + peer_off);
                if ((kh || lane >= 16) && !(wait_kv & 8)) {
                    bf16* dst = (lane < 16 ? g_km : g_vm) + ((uint32_t)(s * 8 + row) * 4096u + h * 128 + 64 * j + 16 * mb + (lane & 1) * 8);
                    stg128(dst, v);
                }
            }
            if (lane == 0) mbar_arrive(b_qkv);
            TL(3);
        }
        if (s == 63) {
            __syncthreads();
            if (threadIdx.x == 0) st_release(&g_rprog[blockIdx.x * 32], epoch * 64 + 64);
            break;
        }
        uint4 wa[8];
        {
            LAUNDER();
            const uint32_t wsm = WSM();
            if (!(wait_kv & 2) || s == 0) mbar_wait(b_kv, ph);
            if (warp >= 4 && warp < 7) {
                const int kw = warp - 4;
                uint32_t ka[8][4];
                if (kw < 2) {
                    const uint32_t kaddr = sb + OFF_KX + (16 * kw + (lane & 15)) * 128;
#pragma unroll
                    for (int i = 0; i < 8; i++) ldsm_x4(ka[i], kaddr + (i >> 2) * 4096 + ((((2 * i + (lane >> 4)) & 7) ^ (lane & 7)) << 4));
                    mbar_wait(b_qkv, ph);
                } else {
                    mbar_wait(b_qkv, ph);
                    const uint32_t kaddr = sb + OFF_KM + (lane & 7) * T_STRIDE + (lane >> 4) * 16;
#pragma unroll
                    for (int i = 0; i < 8; i++) ldsm_x4(ka[i], kaddr + i * 32);
                }
                TL(5);
                const uint32_t qa = sb + OFF_Q + (lane & 7) * T_STRIDE + (lane >> 3) * 16;
                uint32_t qb[4][4];
#pragma unroll
                for (int i = 0; i < 4; i++) ldsm_x4(qb[i], qa + i * 64);
                float s0[4] = {0, 0, 0, 0}, s1[4] = {0, 0, 0, 0}, s2[4] = {0, 0, 0, 0}, s3[4] = {0, 0, 0, 0};
                mma16816(s0, ka[0], qb[0][0], qb[0][1]); mma16816(s1, ka[1], qb[0][2], qb[0][3]);
                mma16816(s2, ka[2], qb[1][0], qb[1][1]); mma16816(s3, ka[3], qb[1][2], qb[1][3]);
                mma16816(s0, ka[4], qb[2][0], qb[2][1]); mma16816(s1, ka[5], qb[2][2], qb[2][3]);
                mma16816(s2, ka[6], qb[3][0], qb[3][1]); mma16816(s3, ka[7], qb[3][2], qb[3][3]);
                const uint32_t sc = sb + OFF_SC + (16 * kw + g) * 4 + (2 * t) * 224;
                sts32(sc, __float_as_uint(bf16r(bf16r((s0[0] + s1[0]) + (s2[0] + s3[0])) * scale)));
                sts32(sc + 224, __float_as_uint(bf16r(bf16r((s0[1] + s1[1]) + (s2[1] + s3[1])) * scale)));
                if (kw < 2) {
                    sts32(sc + 32, __float_as_uint(bf16r(bf16r((s0[2] + s1[2]) + (s2[2] + s3[2])) * scale)));
                    sts32(sc + 32 + 224, __float_as_uint(bf16r(bf16r((s0[3] + s1[3]) + (s2[3] + s3[3])) * scale)));
                }
                asm volatile("bar.arrive 6, 224;" ::: "memory");
                TL(4);
#pragma unroll
                for (int i = 0; i < 8; i++) wa[i] = lds128(wsm + (20 + i) * 512);
            } else {
#pragma unroll
                for (int i = 0; i < 8; i++) wa[i] = lds128(wsm + (20 + i) * 512);
                if (warp < 4) {
                    mbar_wait(b_qkv, ph);
                    uint32_t a0[2][4], a1[2][4], a2[2][4];
#pragma unroll
                    for (int u = 0; u < 2; u++) {
                        const int et = warp + 4 * u;
                        const uint32_t vx = sb + OFF_VX + u * 4096 + ((lane >> 4) * 8 + (lane & 7)) * 128 + ((((2 * warp + ((lane >> 3) & 1)) & 7) ^ (lane & 7)) << 4);
                        ldsm_x4_t(a0[u], vx); ldsm_x4_t(a1[u], vx + 16 * 128);
                        ldsm_x4_t(a2[u], sb + OFF_VM + (lane & 7) * T_STRIDE + (16 * et + ((lane >> 3) & 1) * 8) * 2);
                    }
                    bar_sync(6, 224);
                    TL(6);
                    float x[10];
#pragma unroll
                    for (int i = 0; i < 5; i++) { uint2 v = lds64(sb + OFF_SC + g * 224 + (8 * i + 2 * t) * 4); x[2 * i] = __uint_as_float(v.x); x[2 * i + 1] = __uint_as_float(v.y); }
                    float m = fmaxf(fmaxf(fmaxf(x[0], x[1]), fmaxf(x[2], x[3])), fmaxf(fmaxf(x[4], x[5]), fmaxf(x[6], x[7])));
                    m = fmaxf(m, fmaxf(x[8], x[9]));
                    m = fmaxf(m, __shfl_xor_sync(0xffffffff, m, 1)); m = fmaxf(m, __shfl_xor_sync(0xffffffff, m, 2));
                    float sum0 = 0, sum1 = 0;
#pragma unroll
                    for (int i = 0; i < 5; i++) { x[2 * i] = __expf(x[2 * i] - m); sum0 += x[2 * i]; x[2 * i + 1] = __expf(x[2 * i + 1] - m); sum1 += x[2 * i + 1]; }
                    float sum = sum0 + sum1;
                    sum += __shfl_xor_sync(0xffffffff, sum, 1); sum += __shfl_xor_sync(0xffffffff, sum, 2);
                    float inv = __fdividef(1.0f, sum);
                    if (inv == 123.f) TL(14);
                    TL(4);
                    uint32_t pb[5];
#pragma unroll
                    for (int i = 0; i < 5; i++) pb[i] = pack_bf16(x[2 * i] * inv, x[2 * i + 1] * inv);
#pragma unroll
                    for (int u = 0; u < 2; u++) {
                        float o0[4] = {0, 0, 0, 0}, o1[4] = {0, 0, 0, 0}, o2[4] = {0, 0, 0, 0};
                        mma16816(o0, a0[u], pb[0], pb[1]); mma16816(o1, a1[u], pb[2], pb[3]); mma16816(o2, a2[u], pb[4], 0u);
                        const uint32_t lo = movmatrix_t(pack_bf16((o0[0] + o1[0]) + o2[0], (o0[1] + o1[1]) + o2[1]));
                        const uint32_t hi = movmatrix_t(pack_bf16((o0[2] + o1[2]) + o2[2], (o0[3] + o1[3]) + o2[3]));
                        const uint32_t oa = sb + OFF_O + g * T_STRIDE + (16 * (warp + 4 * u) + 2 * t) * 2;
                        sts32(oa, lo); sts32(oa + 16, hi);
                    }
                    TL(5);
                } else {
                    if (lane < 8) mbar_expect_tx(b_mem + 8 * lane, 1280);
                }
            }
        }
        __syncthreads();
        {
            LAUNDER();
            TL(7);
            const uint32_t wsm = WSM();
            uint32_t ob[16];
            const uint32_t oa = sb + OFF_O + (lane & 7) * T_STRIDE + (lane >> 3) * 16;
#pragma unroll
            for (int i = 0; i < 4; i++) ldsm_x4(ob + 4 * i, oa + i * 64);
            const uint32_t rs_base = OFF_RS + hh * 1280 + t * 16;
            const int ntile = warp < 4 ? 3 : 2;
#pragma unroll 1
            for (int tl = 0; tl < ntile; tl++) {
                float d0[4] = {0, 0, 0, 0}, d1[4] = {0, 0, 0, 0}, d2[4] = {0, 0, 0, 0}, d3[4] = {0, 0, 0, 0};
                const bool more = tl + 1 < ntile;
                const uint32_t nx = wsm + (28 + 8 * tl) * 512;
                mma16816(d0, (uint32_t*)&wa[0], ob[0], ob[1]);   if (more) wa[0] = lds128(nx);
                mma16816(d1, (uint32_t*)&wa[1], ob[2], ob[3]);   if (more) wa[1] = lds128(nx + 512);
                mma16816(d2, (uint32_t*)&wa[2], ob[4], ob[5]);   if (more) wa[2] = lds128(nx + 1024);
                mma16816(d3, (uint32_t*)&wa[3], ob[6], ob[7]);   if (more) wa[3] = lds128(nx + 1536);
                mma16816(d0, (uint32_t*)&wa[4], ob[8], ob[9]);   if (more) wa[4] = lds128(nx + 2048);
                mma16816(d1, (uint32_t*)&wa[5], ob[10], ob[11]); if (more) wa[5] = lds128(nx + 2560);
                mma16816(d2, (uint32_t*)&wa[6], ob[12], ob[13]); if (more) wa[6] = lds128(nx + 3072);
                mma16816(d3, (uint32_t*)&wa[7], ob[14], ob[15]); if (more) wa[7] = lds128(nx + 3584);
                const int col = 16 * (warp + 8 * tl) + 2 * g; const int own = col / 40; const int cp = (col - own * 40) >> 1;
                const uint32_t dbase = mapa_u32(sb, 2 * own + j);
                st_async_v4(dbase + rs_base + cp * 64, __float_as_uint((d0[0] + d1[0]) + (d2[0] + d3[0])), __float_as_uint((d0[1] + d1[1]) + (d2[1] + d3[1])),
                            __float_as_uint((d0[2] + d1[2]) + (d2[2] + d3[2])), __float_as_uint((d0[3] + d1[3]) + (d2[3] + d3[3])), dbase + OFF_BAR + 72);
            }
            TL(8);
        }
        {
            LAUNDER();
            if (warp >= 5) {
                const int x = tid_ - 160;
                const int ot = x < 80 ? x : 79;
                const uint32_t gs = epoch * 64 + s; const uint32_t tag = (gs + 1) & 15u; const int slot = gs & 1;
                uint4* gp = &g_gx[slot][0][rank][ot];
                mbar_wait(b_rs, ph);
                TL(9); TG(12);
                uint4 u[8];
#pragma unroll
                for (int q = 0; q < 8; q++) u[q] = lds128(sb + OFF_RS + q * 1280 + ot * 16);
                float4 a;
                a.x = ((__uint_as_float(u[0].x) + __uint_as_float(u[1].x)) + (__uint_as_float(u[2].x) + __uint_as_float(u[3].x))) + ((__uint_as_float(u[4].x) + __uint_as_float(u[5].x)) + (__uint_as_float(u[6].x) + __uint_as_float(u[7].x)));
                a.y = ((__uint_as_float(u[0].y) + __uint_as_float(u[1].y)) + (__uint_as_float(u[2].y) + __uint_as_float(u[3].y))) + ((__uint_as_float(u[4].y) + __uint_as_float(u[5].y)) + (__uint_as_float(u[6].y) + __uint_as_float(u[7].y)));
                a.z = ((__uint_as_float(u[0].z) + __uint_as_float(u[1].z)) + (__uint_as_float(u[2].z) + __uint_as_float(u[3].z))) + ((__uint_as_float(u[4].z) + __uint_as_float(u[5].z)) + (__uint_as_float(u[6].z) + __uint_as_float(u[7].z)));
                a.w = ((__uint_as_float(u[0].w) + __uint_as_float(u[1].w)) + (__uint_as_float(u[2].w) + __uint_as_float(u[3].w))) + ((__uint_as_float(u[4].w) + __uint_as_float(u[5].w)) + (__uint_as_float(u[6].w) + __uint_as_float(u[7].w)));
                uint4 mine = make_uint4((__float_as_uint(a.x) & ~15u) | tag, (__float_as_uint(a.y) & ~15u) | tag, (__float_as_uint(a.z) & ~15u) | tag, (__float_as_uint(a.w) & ~15u) | tag);
                if (x < 80) st_relaxed_v4(gp + cid * 1280, mine);
                uint4 v[3];
                const uint4* rp0 = gp + (cid ^ 1) * 1280; const uint4* rp1 = gp + (cid ^ 2) * 1280; const uint4* rp2 = gp + (cid ^ 3) * 1280;
                int lim = 0;
                while (true) {
                    v[0] = ld_relaxed_v4(rp0); v[1] = ld_relaxed_v4(rp1); v[2] = ld_relaxed_v4(rp2);
                    uint32_t bad = 0;
#pragma unroll
                    for (int c = 0; c < 3; c++) bad |= (v[c].x ^ tag) | (v[c].y ^ tag) | (v[c].z ^ tag) | (v[c].w ^ tag);
                    if ((bad & 15u) == 0) break;
                    if (++lim > SPIN_LIMIT) break;
                }
                float f0 = (__uint_as_float(mine.x) + __uint_as_float(v[0].x)) + (__uint_as_float(v[1].x) + __uint_as_float(v[2].x));
                float f1 = (__uint_as_float(mine.y) + __uint_as_float(v[0].y)) + (__uint_as_float(v[1].y) + __uint_as_float(v[2].y));
                float f2 = (__uint_as_float(mine.z) + __uint_as_float(v[0].z)) + (__uint_as_float(v[1].z) + __uint_as_float(v[2].z));
                float f3 = (__uint_as_float(mine.w) + __uint_as_float(v[0].w)) + (__uint_as_float(v[1].w) + __uint_as_float(v[2].w));
                const int cp = ot >> 2, tt = ot & 3;
                sts32(sb + OFF_ST + (2 * tt) * 80 + cp * 4, pack_bf16(f0, f2));
                sts32(sb + OFF_ST + (2 * tt + 1) * 80 + cp * 4, pack_bf16(f1, f3));
                TL(10); TG(13);
                bar_sync(5, 128);
                if (x < 80) {
                    const int c = x % 40, d0 = x / 40;
                    uint4 w = lds128(sb + OFF_ST + c * 16);
                    const uint32_t off = OFF_MEM + d0 * 5120 + c * 16;
#pragma unroll
                    for (int i = 0; i < 8; i++) {
                        const uint32_t rb = mapa_u32(sb, (d0 * 8 + i + rank) & 15);
                        st_async_v4(rb + off + i * 640, w.x, w.y, w.z, w.w, rb + OFF_BAR + 8 * i);
                    }
                }
            } else if (warp == 4) {
                if (lane == 0 && (s & 3) == 3 && !(wait_kv & 4)) st_release(&g_rprog[blockIdx.x * 32], epoch * 64 + s + 1);
                __syncwarp();
            } else if (warp == 3) {
                bar_sync(5, 128);
                if (lane == 0 && s < 62 && !(wait_kv & 2)) prefetch_kv(s + 1);
                __syncwarp();
            }
            TL(11);
        }
    }
    cluster_sync_all();
}

__device__ float g_mod[3840];
__device__ bf16 g_h[2048 * 640];
__device__ bf16 g_q[2048 * 4096];
__device__ bf16 g_o[2048 * 4096];
__device__ bf16 g_x1[2048 * 640];
__device__ bf16 g_h2[2048 * 640];
__device__ bf16 g_act[2048 * 1728];
__device__ float g_slab[2048 * 640];
struct GState {
    uint32_t ticket, done, c_mod_a, c_mod_all;
    uint32_t pad[28];
    uint32_t f_h[16 * 32];
    uint32_t qflag[16 * 32];
    uint32_t c_o[16 * 32];
    uint32_t c_wo[16 * 32];
    uint32_t f_h2[16 * 32];
    uint32_t c_act[16 * 32];
    uint32_t c_f2[16 * 32];
};
__device__ GState g_st;

namespace gk {
constexpr int STAGES = 4;
constexpr int STAGE_BYTES = 49152;
constexpr int OFF_SCR = STAGES * STAGE_BYTES;
constexpr int OFF_BAR = OFF_SCR + 32768;
constexpr int SMEM_BYTES = OFF_BAR + 256 + 2048;
constexpr int WO_SPLIT = 8, F2_SPLIT = 3;
constexpr int N_MOD = 60, N_L1 = 256, N_KV = 32, N_Q = 16;
constexpr int N_AT = 32, N_WO = 5 * WO_SPLIT, N_L2 = 16, N_F1 = 14, N_F2 = 5 * F2_SPLIT, N_FIN = 16;
constexpr int KV_LEAD = 3;
constexpr int WAVE = N_KV + N_Q + N_AT + N_WO + N_L2 + N_F1 + N_F2 + N_FIN;
constexpr int I_L1 = N_MOD, I_W = I_L1 + N_L1;
constexpr int W0 = KV_LEAD;
constexpr int N_ITEMS = I_W + (21 + W0) * WAVE;
enum { T_MOD, T_L1, T_KV, T_Q, T_AT, T_WO, T_L2, T_F1, T_F2, T_FIN, T_SKIP, T_END };
struct Item { int type, rb, nt, ks; };
__host__ __device__ __forceinline__ Item decode(int t) {
    Item it; it.rb = 0; it.nt = 0; it.ks = 0;
    if (t >= N_ITEMS) { it.type = T_END; return it; }
    if (t < I_L1) { it.type = T_MOD; it.nt = t; return it; }
    if (t < I_W) { it.type = T_L1; it.rb = (t - I_L1) >> 4; it.nt = (t - I_L1) & 15; return it; }
    t -= I_W;
    int w = t / WAVE; t -= w * WAVE; w -= W0;
    if (t < N_KV) { it.type = T_KV; it.rb = w + KV_LEAD; it.nt = t; }
    else if ((t -= N_KV) < N_FIN) { it.type = T_FIN; it.rb = w - 5; it.nt = t; }
    else if ((t -= N_FIN) < N_F2) { it.type = T_F2; it.rb = w - 4; it.ks = t / 5; it.nt = t % 5; }
    else if ((t -= N_F2) < N_F1) { it.type = T_F1; it.rb = w - 3; it.nt = t; }
    else if ((t -= N_F1) < N_L2) { it.type = T_L2; it.rb = w - 2; it.nt = t; }
    else if ((t -= N_L2) < N_WO) { it.type = T_WO; it.rb = w - 1; it.ks = t / 5; it.nt = t % 5; }
    else if ((t -= N_WO) < N_Q) { it.type = T_Q; it.rb = w + 1; it.nt = t; }
    else { t -= N_Q; it.type = T_AT; it.rb = w; it.nt = t; }
    if (it.rb < 0 || it.rb > 15) it.type = T_SKIP;
    return it;
}
}

struct GParams {
    CUtensorMap tA_h, tA_o, tA_h2, tA_act, tB_q, tB_k, tB_v, tB_o, tB_g, tB_u, tB_d, tS_q, tS_k, tS_v, tS_act, tS_o, tL_q, tL_k, tL_v, tL_km, tL_vm;
};

__device__ __forceinline__ void wait_ge(const uint32_t* p, uint32_t target) {
    int lim = 0;
    while ((int32_t)(ld_acquire(p) - target) < 0) { __nanosleep(64); if (++lim > SPIN_LIMIT) break; }
}
__device__ __forceinline__ uint32_t atom_add_acqrel(uint32_t* p, uint32_t v) {
    uint32_t o; asm volatile("atom.acq_rel.gpu.global.add.u32 %0, [%1], %2;" : "=r"(o) : "l"(p), "r"(v) : "memory"); return o;
}
__device__ __forceinline__ void red_add_relaxed(uint32_t* p, uint32_t v) { asm volatile("red.relaxed.gpu.global.add.u32 [%0], %1;" :: "l"(p), "r"(v) : "memory"); }
__device__ __forceinline__ void st_relaxed_u32(uint32_t* p, uint32_t v) { asm volatile("st.relaxed.gpu.global.u32 [%0], %1;" :: "l"(p), "r"(v) : "memory"); }
__device__ __forceinline__ void red_add_release(uint32_t* p, uint32_t v) { asm volatile("red.release.gpu.global.add.u32 [%0], %1;" :: "l"(p), "r"(v) : "memory"); }

__device__ __forceinline__ void wgmma_fence() { asm volatile("wgmma.fence.sync.aligned;" ::: "memory"); }
__device__ __forceinline__ void wgmma_commit() { asm volatile("wgmma.commit_group.sync.aligned;" ::: "memory"); }
template<int N> __device__ __forceinline__ void wgmma_wait() { asm volatile("wgmma.wait_group.sync.aligned %0;" :: "n"(N) : "memory"); }

#define ACC8(b) "+f"(d[b]), "+f"(d[b+1]), "+f"(d[b+2]), "+f"(d[b+3]), "+f"(d[b+4]), "+f"(d[b+5]), "+f"(d[b+6]), "+f"(d[b+7])
#define ACC32(b) ACC8(b), ACC8(b+8), ACC8(b+16), ACC8(b+24)
__device__ __forceinline__ void wgmma_n128(float* d, uint64_t da, uint64_t db, int scale_d) {
    asm volatile("{ .reg .pred p; setp.ne.b32 p, %66, 0;\n"
        "wgmma.mma_async.sync.aligned.m64n128k16.f32.bf16.bf16 {%0,%1,%2,%3,%4,%5,%6,%7,%8,%9,%10,%11,%12,%13,%14,%15,%16,%17,%18,%19,%20,%21,%22,%23,%24,%25,%26,%27,%28,%29,%30,%31,"
        "%32,%33,%34,%35,%36,%37,%38,%39,%40,%41,%42,%43,%44,%45,%46,%47,%48,%49,%50,%51,%52,%53,%54,%55,%56,%57,%58,%59,%60,%61,%62,%63}, %64, %65, p, 1, 1, 0, 1; }"
        : ACC32(0), ACC32(32) : "l"(da), "l"(db), "r"(scale_d));
}
__device__ __forceinline__ void wgmma_n256(float* d, uint64_t da, uint64_t db, int scale_d) {
    asm volatile("{ .reg .pred p; setp.ne.b32 p, %130, 0;\n"
        "wgmma.mma_async.sync.aligned.m64n256k16.f32.bf16.bf16 {%0,%1,%2,%3,%4,%5,%6,%7,%8,%9,%10,%11,%12,%13,%14,%15,%16,%17,%18,%19,%20,%21,%22,%23,%24,%25,%26,%27,%28,%29,%30,%31,"
        "%32,%33,%34,%35,%36,%37,%38,%39,%40,%41,%42,%43,%44,%45,%46,%47,%48,%49,%50,%51,%52,%53,%54,%55,%56,%57,%58,%59,%60,%61,%62,%63,"
        "%64,%65,%66,%67,%68,%69,%70,%71,%72,%73,%74,%75,%76,%77,%78,%79,%80,%81,%82,%83,%84,%85,%86,%87,%88,%89,%90,%91,%92,%93,%94,%95,"
        "%96,%97,%98,%99,%100,%101,%102,%103,%104,%105,%106,%107,%108,%109,%110,%111,%112,%113,%114,%115,%116,%117,%118,%119,%120,%121,%122,%123,%124,%125,%126,%127}, %128, %129, p, 1, 1, 0, 1; }"
        : ACC32(0), ACC32(32), ACC32(64), ACC32(96) : "l"(da), "l"(db), "r"(scale_d));
}
__device__ __forceinline__ uint64_t make_desc(uint32_t addr, uint32_t lbo, uint32_t sbo) {
    return (uint64_t)((addr & 0x3FFFF) >> 4) | ((uint64_t)(lbo >> 4) << 16) | ((uint64_t)(sbo >> 4) << 32) | ((uint64_t)1 << 62);
}

__device__ __forceinline__ float div_fix(float a, float b, float rb) { float q = a * rb; float r = fmaf(-q, b, a); return fmaf(r, rb, q); }
__device__ __forceinline__ void row_item(int mode, uint32_t sx, uint32_t sa, uint32_t sp, uint32_t bar_empty, float* __restrict__ acc, bf16* __restrict__ yout, bf16* __restrict__ out, int lane) {
    float x[20];
#pragma unroll
    for (int i = 0; i < 5; i++) {
        const uint2 v = lds64(sx + i * 256 + lane * 8);
        x[4 * i] = __uint_as_float(v.x << 16); x[4 * i + 1] = __uint_as_float(v.x & 0xffff0000u);
        x[4 * i + 2] = __uint_as_float(v.y << 16); x[4 * i + 3] = __uint_as_float(v.y & 0xffff0000u);
    }
    if (mode) {
#pragma unroll
        for (int i = 0; i < 5; i++) {
            const uint4 a = lds128(sa + i * 512 + lane * 16), gt = lds128(sp + i * 512 + lane * 16);
            x[4 * i] = bf16r(x[4 * i] + bf16r(__uint_as_float(gt.x) * bf16r(__uint_as_float(a.x)))); x[4 * i + 1] = bf16r(x[4 * i + 1] + bf16r(__uint_as_float(gt.y) * bf16r(__uint_as_float(a.y))));
            x[4 * i + 2] = bf16r(x[4 * i + 2] + bf16r(__uint_as_float(gt.z) * bf16r(__uint_as_float(a.z)))); x[4 * i + 3] = bf16r(x[4 * i + 3] + bf16r(__uint_as_float(gt.w) * bf16r(__uint_as_float(a.w))));
            *(uint2*)(yout + i * 128 + lane * 4) = make_uint2(pack_bf16(x[4 * i], x[4 * i + 1]), pack_bf16(x[4 * i + 2], x[4 * i + 3]));
            *(float4*)(acc + i * 128 + lane * 4) = make_float4(0.f, 0.f, 0.f, 0.f);
        }
        sp += 2560;
    }
    if (mode != 2) {
        float s = 0;
#pragma unroll
        for (int i = 0; i < 20; i++) s += x[i];
#pragma unroll
        for (int o = 16; o; o >>= 1) s += __shfl_xor_sync(0xffffffff, s, o);
        const float mean = s * (1.0f / 640.0f);
        float q = 0;
#pragma unroll
        for (int i = 0; i < 20; i++) { float d = x[i] - mean; q += d * d; }
#pragma unroll
        for (int o = 16; o; o >>= 1) q += __shfl_xor_sync(0xffffffff, q, o);
        const float m16 = bf16r(mean);
        const float sd = bf16r(sqrtf(bf16r(bf16r(q * (1.0f / 640.0f)) + 1e-5f)));
        const float rs = __frcp_rn(sd);
#pragma unroll
        for (int i = 0; i < 5; i++) {
            const uint4 sh = lds128(sp + i * 512 + lane * 16), sc = lds128(sp + 2560 + i * 512 + lane * 16);
            float y0 = bf16r(bf16r(div_fix(bf16r(x[4 * i] - m16), sd, rs)) * bf16r(1.0f + __uint_as_float(sc.x))) + __uint_as_float(sh.x);
            float y1 = bf16r(bf16r(div_fix(bf16r(x[4 * i + 1] - m16), sd, rs)) * bf16r(1.0f + __uint_as_float(sc.y))) + __uint_as_float(sh.y);
            float y2 = bf16r(bf16r(div_fix(bf16r(x[4 * i + 2] - m16), sd, rs)) * bf16r(1.0f + __uint_as_float(sc.z))) + __uint_as_float(sh.z);
            float y3 = bf16r(bf16r(div_fix(bf16r(x[4 * i + 3] - m16), sd, rs)) * bf16r(1.0f + __uint_as_float(sc.w))) + __uint_as_float(sh.w);
            *(uint2*)(out + i * 128 + lane * 4) = make_uint2(pack_bf16(y0, y1), pack_bf16(y2, y3));
        }
    }
    __syncwarp();
    if (lane == 0) mbar_arrive(bar_empty);
}

__device__ __forceinline__ float gelu_tanh(float x) {
    float u2 = x * fmaf(x * x, 2.0f * 0.7978845608028654f * 0.044715f * 1.4426950408889634f, 2.0f * 0.7978845608028654f * 1.4426950408889634f);
    float e; asm("ex2.approx.ftz.f32 %0, %1;" : "=f"(e) : "f"(-u2));
    return __fdividef(x, 1.0f + e);
}
__device__ __forceinline__ uint4 ldg128(const void* p) { uint4 v; asm volatile("ld.global.v4.u32 {%0,%1,%2,%3}, [%4];" : "=r"(v.x), "=r"(v.y), "=r"(v.z), "=r"(v.w) : "l"(p) : "memory"); return v; }
__device__ __forceinline__ float4 ldcg_f4(const float* p) { float4 v; asm volatile("ld.global.cg.v4.f32 {%0,%1,%2,%3}, [%4];" : "=f"(v.x), "=f"(v.y), "=f"(v.z), "=f"(v.w) : "l"(p) : "memory"); return v; }
__device__ __forceinline__ uint4 ldcg128(const void* p) { uint4 v; asm volatile("ld.global.cg.v4.u32 {%0,%1,%2,%3}, [%4];" : "=r"(v.x), "=r"(v.y), "=r"(v.z), "=r"(v.w) : "l"(p) : "memory"); return v; }

__device__ __forceinline__ void attn_scores(uint32_t sq, uint32_t sk, uint32_t skm, int sg, int mt, int lane, uint32_t (&p)[6][2]) {
    const int g = lane >> 2, t = lane & 3, l7 = lane & 7;
    float s[5][4];
#pragma unroll
    for (int kt = 0; kt < 5; kt++) s[kt][0] = s[kt][1] = s[kt][2] = s[kt][3] = 0.f;
    const uint32_t qrow = sq + (sg * 32 + mt * 16 + (lane & 15)) * 128;
    const uint32_t krow = sk + (sg * 32 + l7) * 128, kmrow = skm + (sg * 8 + l7) * 128;
#pragma unroll
    for (int c = 0; c < 4; c++) {
        uint32_t a0[4], a1[4];
        ldsm_x4(a0, qrow + (c >> 1) * 16384 + ((((4 * c + (lane >> 4)) & 7) ^ l7) << 4));
        ldsm_x4(a1, qrow + (c >> 1) * 16384 + ((((4 * c + 2 + (lane >> 4)) & 7) ^ l7) << 4));
        const uint32_t sw = (((4 * c + (lane >> 3)) & 7) ^ l7) << 4;
#pragma unroll
        for (int kt = 0; kt < 5; kt++) {
            uint32_t b[4];
            ldsm_x4(b, kt == 0 ? kmrow + (c >> 1) * 4096 + sw : krow + (kt - 1) * 1024 + (c >> 1) * 16384 + sw);
            mma16816(s[kt], a0, b[0], b[1]); mma16816(s[kt], a1, b[2], b[3]);
        }
    }
    const float scale = 0.08838834764831845f;
    const int r0 = mt * 16 + g, r1 = r0 + 8;
    float m0 = -INFINITY, m1 = -INFINITY;
#pragma unroll
    for (int kt = 0; kt < 5; kt++) {
#pragma unroll
        for (int i = 0; i < 4; i++) {
            float v = bf16r(bf16r(s[kt][i]) * scale);
            if (kt > 0) { int key = (kt - 1) * 8 + 2 * t + (i & 1); if (key > (i < 2 ? r0 : r1)) v = -1.0e9f; }
            s[kt][i] = v;
            if (i < 2) m0 = fmaxf(m0, v); else m1 = fmaxf(m1, v);
        }
    }
    m0 = fmaxf(m0, __shfl_xor_sync(0xffffffff, m0, 1)); m0 = fmaxf(m0, __shfl_xor_sync(0xffffffff, m0, 2));
    m1 = fmaxf(m1, __shfl_xor_sync(0xffffffff, m1, 1)); m1 = fmaxf(m1, __shfl_xor_sync(0xffffffff, m1, 2));
    float l0 = 0, l1 = 0;
#pragma unroll
    for (int kt = 0; kt < 5; kt++) {
        s[kt][0] = __expf(s[kt][0] - m0); s[kt][1] = __expf(s[kt][1] - m0); l0 += s[kt][0] + s[kt][1];
        s[kt][2] = __expf(s[kt][2] - m1); s[kt][3] = __expf(s[kt][3] - m1); l1 += s[kt][2] + s[kt][3];
    }
    l0 += __shfl_xor_sync(0xffffffff, l0, 1); l0 += __shfl_xor_sync(0xffffffff, l0, 2);
    l1 += __shfl_xor_sync(0xffffffff, l1, 1); l1 += __shfl_xor_sync(0xffffffff, l1, 2);
    const float i0 = __fdividef(1.0f, l0), i1 = __fdividef(1.0f, l1);
#pragma unroll
    for (int kt = 0; kt < 5; kt++) { p[kt][0] = pack_bf16(s[kt][0] * i0, s[kt][1] * i0); p[kt][1] = pack_bf16(s[kt][2] * i1, s[kt][3] * i1); }
    p[5][0] = p[5][1] = 0;
}
__device__ __forceinline__ void attn_pv(uint32_t sv, uint32_t svm, int sg, int lane, const uint32_t (&p)[6][2], float* d) {
    const int l7 = lane & 7, hi = (lane >> 3) & 1, ec = lane >> 4;
    const uint32_t r0 = hi ? sv + (sg * 32 + l7) * 128 : svm + (sg * 8 + l7) * 128;
    const uint32_t sub0 = hi ? 16384 : 4096;
    const uint32_t r1 = sv + (sg * 32 + 8 + hi * 8 + l7) * 128;
    const uint32_t r2 = sv + (sg * 32 + 24 + l7) * 128;
#pragma unroll
    for (int i = 0; i < 8; i++) {
        const uint32_t sw = (((2 * i + ec) & 7) ^ l7) << 4;
        uint32_t b0[4], b1[4], b2[4];
        ldsm_x4_t(b0, r0 + (i >> 2) * sub0 + sw); ldsm_x4_t(b1, r1 + (i >> 2) * 16384 + sw); ldsm_x4_t(b2, r2 + (i >> 2) * 16384 + sw);
        float* o0 = d + 8 * i; float* o1 = o0 + 4;
        o0[0] = o0[1] = o0[2] = o0[3] = o1[0] = o1[1] = o1[2] = o1[3] = 0.f;
        { uint32_t a[4] = {p[0][0], p[0][1], p[1][0], p[1][1]}; mma16816(o0, a, b0[0], b0[1]); mma16816(o1, a, b0[2], b0[3]); }
        { uint32_t a[4] = {p[2][0], p[2][1], p[3][0], p[3][1]}; mma16816(o0, a, b1[0], b1[1]); mma16816(o1, a, b1[2], b1[3]); }
        { uint32_t a[4] = {p[4][0], p[4][1], p[5][0], p[5][1]}; mma16816(o0, a, b2[0], b2[1]); mma16816(o1, a, b2[2], b2[3]); }
    }
}
__device__ __forceinline__ void bulk_load(uint32_t dst, const void* src, uint32_t bytes, uint32_t bar) {
    asm volatile("cp.async.bulk.shared::cluster.global.mbarrier::complete_tx::bytes [%0], [%1], %2, [%3];" :: "r"(dst), "l"(src), "r"(bytes), "r"(bar) : "memory");
}

__device__ __forceinline__ void stsm_x4(uint32_t addr, uint32_t a, uint32_t b, uint32_t c, uint32_t d) {
    asm volatile("stmatrix.sync.aligned.m8n8.x4.shared.b16 [%0], {%1,%2,%3,%4};" :: "r"(addr), "r"(a), "r"(b), "r"(c), "r"(d) : "memory");
}
__device__ __forceinline__ void tma_store_2d(const CUtensorMap* map, uint32_t src, int c0, int c1) {
    asm volatile("cp.async.bulk.tensor.2d.global.shared::cta.bulk_group [%0, {%2, %3}], [%1];" :: "l"(map), "r"(src), "r"(c0), "r"(c1) : "memory");
}

__global__ void __launch_bounds__(384, 1)
g_kernel(const __grid_constant__ GParams P, const bf16* __restrict__ x, const bf16* __restrict__ cvec, const bf16* __restrict__ w_mod, bf16* __restrict__ out, int nctas, int wait_r)
{
    using namespace gk;
    extern __shared__ __align__(1024) uint8_t smem[];
    const uint32_t sb = smem_u32(smem);
    const int tid = threadIdx.x, warp = tid >> 5, lane = tid & 31;
    const uint32_t b_full = sb + OFF_BAR, b_empty = b_full + 8 * STAGES, b_wfull = b_empty + 8 * STAGES, b_wempty = b_wfull + 16;
    const uint32_t b_cdone = b_wempty + 16, b_sfree = b_cdone + 16;
    volatile int* wslot = (volatile int*)(smem + OFF_BAR + 192);
    const uint32_t epoch = ld_relaxed(&g_epoch);
    const uint32_t e1 = epoch + 1;
    if (tid == 0) {
        for (int i = 0; i < STAGES; i++) { mbar_init(b_full + 8 * i, 1); mbar_init(b_empty + 8 * i, 8); }
        for (int i = 0; i < 2; i++) { mbar_init(b_wfull + 8 * i, 1); mbar_init(b_wempty + 8 * i, 9); mbar_init(b_cdone + 8 * i, 4); mbar_init(b_sfree + 8 * i, 1); }
        asm volatile("fence.mbarrier_init.release.cluster;" ::: "memory");
    }
    __syncthreads();

    if (warp < 4) {
        asm volatile("setmaxnreg.dec.sync.aligned.u32 40;");
        if (warp == 0 && lane == 0) {
            uint32_t stage = 0, sph = 1, wi = 0, wph = 1;
            const uint32_t tbase = epoch * (uint32_t)(N_ITEMS + nctas);
            while (true) {
                int tk = (int)(atomicAdd(&g_st.ticket, 1u) - tbase);
                Item it = decode(tk);
                if (it.type == T_SKIP) continue;
                switch (it.type) {
                    case T_L1: wait_ge(&g_st.c_mod_a, e1 * 20); break;
                    case T_KV: case T_Q: wait_ge(&g_st.f_h[it.rb * 32], e1 * 16); break;
                    case T_AT:
                        wait_ge(&g_st.qflag[it.rb * 32 + it.nt], e1);
                        wait_ge(&g_kvflag[it.rb * 64 + it.nt], e1); wait_ge(&g_kvflag[it.rb * 64 + 32 + it.nt], e1);
                        if (wait_r) { wait_ge(&g_rprog[(2 * it.nt) * 32], epoch * 64 + 4 * it.rb + 4); wait_ge(&g_rprog[(2 * it.nt + 1) * 32], epoch * 64 + 4 * it.rb + 4); }
                        break;
                    case T_WO: wait_ge(&g_st.c_o[it.rb * 32 + it.ks * 4], e1 * (32 / WO_SPLIT)); break;
                    case T_L2: wait_ge(&g_st.c_wo[it.rb * 32], e1 * N_WO); wait_ge(&g_st.c_mod_all, e1 * 60); break;
                    case T_F1: wait_ge(&g_st.f_h2[it.rb * 32], e1 * 16); break;
                    case T_F2: wait_ge(&g_st.c_act[it.rb * 32], e1 * 14); break;
                    case T_FIN: wait_ge(&g_st.c_f2[it.rb * 32], e1 * N_F2); break;
                    default: break;
                }
                asm volatile("fence.proxy.async.global;" ::: "memory");
                mbar_wait(b_wempty + 8 * wi, wph);
                wslot[wi] = tk;
                mbar_arrive(b_wfull + 8 * wi);
                if (++wi == 2) { wi = 0; wph ^= 1; }
                if (it.type == T_END) break;
                int nkb = 0, kb0 = 0;
                const CUtensorMap *mA = nullptr, *mB0 = nullptr, *mB1 = nullptr; int n0 = 0, n1 = 0, nbox = 4;
                switch (it.type) {
                    case T_KV: nkb = 10; mA = &P.tA_h; mB0 = mB1 = (it.nt < 16) ? &P.tB_k : &P.tB_v; n0 = (it.nt & 15) * 256; n1 = n0 + 128; break;
                    case T_Q: nkb = 10; mA = &P.tA_h; mB0 = mB1 = &P.tB_q; n0 = it.nt * 256; n1 = n0 + 128; break;
                    case T_F1: nkb = 10; mA = &P.tA_h2; mB0 = &P.tB_g; mB1 = &P.tB_u; n0 = n1 = it.nt * 128; break;
                    case T_WO: nkb = 64 / WO_SPLIT; kb0 = it.ks * nkb; mA = &P.tA_o; mB0 = &P.tB_o; n0 = it.nt * 128; nbox = 2; break;
                    case T_F2: nkb = 27 / F2_SPLIT; kb0 = it.ks * nkb; mA = &P.tA_act; mB0 = &P.tB_d; n0 = it.nt * 128; nbox = 2; break;
                    default: break;
                }
                if (it.type == T_AT) {
#pragma unroll 1
                    for (int i = 0; i < 3; i++) {
                        mbar_wait(b_empty + 8 * stage, sph);
                        const uint32_t st = sb + stage * STAGE_BYTES, bar = b_full + 8 * stage;
                        mbar_expect_tx(bar, i ? 40960 : 32768);
                        const CUtensorMap* m = i == 0 ? &P.tL_q : (i == 1 ? &P.tL_k : &P.tL_v);
                        tma_load_2d(st + 16384, m, it.nt * 128, it.rb * 128, bar);
                        tma_load_2d(st + 32768, m, it.nt * 128 + 64, it.rb * 128, bar);
                        if (i) {
                            const CUtensorMap* mm = i == 1 ? &P.tL_km : &P.tL_vm;
                            tma_load_2d(st, mm, it.nt * 128, it.rb * 32, bar);
                            tma_load_2d(st + 4096, mm, it.nt * 128 + 64, it.rb * 32, bar);
                        }
                        if (++stage == STAGES) { stage = 0; sph ^= 1; }
                    }
                } else if (it.type == T_L1 || it.type == T_L2 || it.type == T_FIN) {
                    const int mode = it.type == T_L1 ? 0 : (it.type == T_L2 ? 1 : 2);
                    const uint32_t pbytes = mode == 0 ? 5120 : (mode == 1 ? 7680 : 2560);
                    const float* psrc = g_mod + (mode == 0 ? 0 : (mode == 1 ? 2 * 640 : 5 * 640));
                    {
                        mbar_wait(b_empty + 8 * stage, sph);
                        const uint32_t st = sb + stage * STAGE_BYTES, bar = b_full + 8 * stage;
                        const size_t ro = ((size_t)it.rb * 128 + it.nt * 8) * 640;
                        mbar_expect_tx(bar, 10240 + (mode ? 20480 : 0) + pbytes);
                        bulk_load(st, (mode == 2 ? g_x1 : x) + ro, 10240, bar);
                        if (mode) bulk_load(st + 10240, g_slab + ro, 20480, bar);
                        bulk_load(st + 30720, psrc, pbytes, bar);
                        if (++stage == STAGES) { stage = 0; sph ^= 1; }
                    }
                }
                for (int kb = 0; kb < nkb; kb++) {
                    mbar_wait(b_empty + 8 * stage, sph);
                    const uint32_t st = sb + stage * STAGE_BYTES, bar = b_full + 8 * stage;
                    mbar_expect_tx(bar, 16384 + nbox * 8192);
                    const int k = (kb0 + kb) * 64;
                    tma_load_2d(st, mA, k, it.rb * 128, bar);
                    tma_load_2d(st + 16384, mB0, n0, k, bar);
                    tma_load_2d(st + 16384 + 8192, mB0, n0 + 64, k, bar);
                    if (nbox == 4) {
                        tma_load_2d(st + 16384 + 16384, mB1, n1, k, bar);
                        tma_load_2d(st + 16384 + 24576, mB1, n1 + 64, k, bar);
                    }
                    if (++stage == STAGES) { stage = 0; sph ^= 1; }
                }
            }
        } else if (warp == 1 && lane == 0) {
            uint32_t wi = 0, wph = 0, cph = 0;
            while (true) {
                mbar_wait(b_wfull + 8 * wi, wph);
                const int tk = wslot[wi];
                mbar_arrive(b_wempty + 8 * wi);
                if (++wi == 2) { wi = 0; wph ^= 1; }
                const Item it = decode(tk);
                if (it.type == T_END) break;
                const bool tma = it.type == T_KV || it.type == T_Q || it.type == T_F1 || it.type == T_AT;
                const int rounds = (it.type == T_KV || it.type == T_Q) ? 2 : 1;
                const CUtensorMap* mS = it.type == T_F1 ? &P.tS_act : (it.type == T_AT ? &P.tS_o : (it.type == T_Q ? &P.tS_q : (it.nt < 16 ? &P.tS_k : &P.tS_v)));
                const int gcol = rounds == 1 ? it.nt * 128 : (it.nt & 15) * 256;
                for (int rnd = 0; rnd < rounds; rnd++) {
                    for (int wg = 0; wg < 2; wg++) {
                        mbar_wait(b_cdone + 8 * wg, cph);
                        if (tma) {
                            const uint32_t stg = sb + OFF_SCR + wg * 16384;
                            tma_store_2d(mS, stg, gcol + rnd * 128, it.rb * 128 + wg * 64);
                            tma_store_2d(mS, stg + 8192, gcol + rnd * 128 + 64, it.rb * 128 + wg * 64);
                            asm volatile("cp.async.bulk.commit_group;" ::: "memory");
                        }
                    }
                    cph ^= 1;
                    if (tma) {
                        asm volatile("cp.async.bulk.wait_group.read 0;" ::: "memory");
                        mbar_arrive(b_sfree); mbar_arrive(b_sfree + 8);
                    }
                }
                if (tma) { asm volatile("cp.async.bulk.wait_group 0;" ::: "memory"); asm volatile("fence.proxy.async.global;" ::: "memory"); }
                asm volatile("fence.acq_rel.gpu;" ::: "memory");
                uint32_t* cnt = nullptr;
                switch (it.type) {
                    case T_KV: st_relaxed_u32(&g_kvflag[it.rb * 64 + it.nt * 2], e1); st_relaxed_u32(&g_kvflag[it.rb * 64 + it.nt * 2 + 1], e1); break;
                    case T_Q: st_relaxed_u32(&g_st.qflag[it.rb * 32 + it.nt * 2], e1); st_relaxed_u32(&g_st.qflag[it.rb * 32 + it.nt * 2 + 1], e1); break;
                    case T_MOD: if (it.nt < 20) red_add_relaxed(&g_st.c_mod_a, 1); cnt = &g_st.c_mod_all; break;
                    case T_L1: cnt = &g_st.f_h[it.rb * 32]; break;
                    case T_AT: cnt = &g_st.c_o[it.rb * 32 + (it.nt / (32 / WO_SPLIT)) * 4]; break;
                    case T_WO: cnt = &g_st.c_wo[it.rb * 32]; break;
                    case T_L2: cnt = &g_st.f_h2[it.rb * 32]; break;
                    case T_F1: cnt = &g_st.c_act[it.rb * 32]; break;
                    case T_F2: cnt = &g_st.c_f2[it.rb * 32]; break;
                    default: break;
                }
                if (cnt) red_add_relaxed(cnt, 1);
            }
            uint32_t old = atom_add_acqrel(&g_st.done, 1);
            if (old + 1 == e1 * (uint32_t)nctas) st_release(&g_epoch, e1);
        }
    } else {
        asm volatile("setmaxnreg.inc.sync.aligned.u32 232;");
        const int ct = tid - 128, cw = warp - 4, wg = cw >> 2;
        const int g = lane >> 2, t = lane & 3;
        uint32_t stage = 0, sph = 0, wi = 0, wph = 0, fph = 1;
        while (true) {
            mbar_wait(b_wfull + 8 * wi, wph);
            const int tk = wslot[wi];
            __syncwarp();
            if (lane == 0) mbar_arrive(b_wempty + 8 * wi);
            if (++wi == 2) { wi = 0; wph ^= 1; }
            const Item it = decode(tk);
            if (it.type == T_END) break;
            if (it.type == T_KV || it.type == T_Q || it.type == T_F1) {
                float d[128];
#pragma unroll
                for (int i = 0; i < 128; i++) d[i] = 0.f;
                for (int kb = 0; kb < 10; kb++) {
                    mbar_wait(b_full + 8 * stage, sph);
                    const uint32_t st = sb + stage * STAGE_BYTES;
                    const uint64_t da = make_desc(st + wg * 8192, 16, 1024), db = make_desc(st + 16384, 8192, 1024);
                    wgmma_fence();
#pragma unroll
                    for (int k = 0; k < 4; k++) wgmma_n256(d, da + k * 2, db + k * 128, 1);
                    wgmma_commit();
                    wgmma_wait<1>();
                    if (kb > 0 && lane == 0) mbar_arrive(b_empty + 8 * ((stage + STAGES - 1) % STAGES));
                    if (++stage == STAGES) { stage = 0; sph ^= 1; }
                }
                wgmma_wait<0>();
                if (lane == 0) mbar_arrive(b_empty + 8 * ((stage + STAGES - 1) % STAGES));
                const uint32_t sbase = sb + OFF_SCR + wg * 16384 + ((cw & 3) * 16 + ((lane >> 3) & 1) * 8 + (lane & 7)) * 128;
                const int sx = lane & 7, hi = lane >> 4;
                if (it.type == T_F1) {
#pragma unroll
                    for (int i = 0; i < 64; i++) d[i] = bf16r(gelu_tanh(bf16r(d[i]))) * bf16r(d[64 + i]);
                }
#pragma unroll
                for (int rnd = 0; rnd < 2; rnd++) {
                    if (rnd == 1 && it.type == T_F1) break;
                    mbar_wait(b_sfree + 8 * wg, fph); fph ^= 1;
#pragma unroll
                    for (int i = 0; i < 8; i++) {
                        const float* dd = d + rnd * 64 + i * 8;
                        const int chunk = (2 * i + hi) & 7;
                        stsm_x4(sbase + (i >> 2) * 8192 + ((chunk ^ sx) << 4), pack_bf16(dd[0], dd[1]), pack_bf16(dd[2], dd[3]), pack_bf16(dd[4], dd[5]), pack_bf16(dd[6], dd[7]));
                    }
                    asm volatile("fence.proxy.async.shared::cta;" ::: "memory");
                    __syncwarp();
                    if (lane == 0) mbar_arrive(b_cdone + 8 * wg);
                }
                continue;
            } else if (it.type == T_WO || it.type == T_F2) {
                float d[64];
#pragma unroll
                for (int i = 0; i < 64; i++) d[i] = 0.f;
                const int nkb = it.type == T_WO ? 64 / WO_SPLIT : 27 / F2_SPLIT;
                for (int kb = 0; kb < nkb; kb++) {
                    mbar_wait(b_full + 8 * stage, sph);
                    const uint32_t st = sb + stage * STAGE_BYTES;
                    const uint64_t da = make_desc(st + wg * 8192, 16, 1024), db = make_desc(st + 16384, 8192, 1024);
                    wgmma_fence();
#pragma unroll
                    for (int k = 0; k < 4; k++) wgmma_n128(d, da + k * 2, db + k * 128, 1);
                    wgmma_commit();
                    wgmma_wait<1>();
                    if (kb > 0 && lane == 0) mbar_arrive(b_empty + 8 * ((stage + STAGES - 1) % STAGES));
                    if (++stage == STAGES) { stage = 0; sph ^= 1; }
                }
                wgmma_wait<0>();
                if (lane == 0) mbar_arrive(b_empty + 8 * ((stage + STAGES - 1) % STAGES));
                float* slab = g_slab + (size_t)(it.rb * 128 + wg * 64 + (cw & 3) * 16 + g) * 640 + it.nt * 128 + 2 * t;
#pragma unroll
                for (int i = 0; i < 16; i++) {
                    asm volatile("red.relaxed.gpu.global.add.v2.f32 [%0], {%1,%2};" :: "l"(slab + 8 * i), "f"(d[4 * i]), "f"(d[4 * i + 1]) : "memory");
                    asm volatile("red.relaxed.gpu.global.add.v2.f32 [%0], {%1,%2};" :: "l"(slab + 8 * 640 + 8 * i), "f"(d[4 * i + 2]), "f"(d[4 * i + 3]) : "memory");
                }
            } else if (it.type == T_AT) {
                uint32_t p[6][2];
                float d[64];
                const uint32_t s0 = stage, s1 = (stage + 1) % STAGES, s2 = (stage + 2) % STAGES;
                mbar_wait(b_full + 8 * s0, sph);
                mbar_wait(b_full + 8 * s1, s1 < s0 ? sph ^ 1 : sph);
                attn_scores(sb + s0 * STAGE_BYTES + 16384, sb + s1 * STAGE_BYTES + 16384, sb + s1 * STAGE_BYTES, cw >> 1, cw & 1, lane, p);
                __syncwarp();
                if (lane == 0) { mbar_arrive(b_empty + 8 * s0); mbar_arrive(b_empty + 8 * s1); }
                mbar_wait(b_full + 8 * s2, s2 < s0 ? sph ^ 1 : sph);
                attn_pv(sb + s2 * STAGE_BYTES + 16384, sb + s2 * STAGE_BYTES, cw >> 1, lane, p, d);
                __syncwarp();
                if (lane == 0) mbar_arrive(b_empty + 8 * s2);
                stage += 3; if (stage >= STAGES) { stage -= STAGES; sph ^= 1; }
                const uint32_t sbase = sb + OFF_SCR + wg * 16384 + ((cw & 3) * 16 + ((lane >> 3) & 1) * 8 + (lane & 7)) * 128;
                mbar_wait(b_sfree + 8 * wg, fph); fph ^= 1;
#pragma unroll
                for (int i = 0; i < 8; i++) {
                    const float* dd = d + i * 8;
                    const int chunk = (2 * i + (lane >> 4)) & 7;
                    stsm_x4(sbase + (i >> 2) * 8192 + ((chunk ^ (lane & 7)) << 4), pack_bf16(dd[0], dd[1]), pack_bf16(dd[2], dd[3]), pack_bf16(dd[4], dd[5]), pack_bf16(dd[6], dd[7]));
                }
                asm volatile("fence.proxy.async.shared::cta;" ::: "memory");
            } else if (it.type == T_L1 || it.type == T_L2 || it.type == T_FIN) {
                const int mode = it.type == T_L1 ? 0 : (it.type == T_L2 ? 1 : 2);
                {
                    const size_t ro = ((size_t)it.rb * 128 + it.nt * 8 + cw) * 640;
                    const uint32_t st = sb + stage * STAGE_BYTES;
                    mbar_wait(b_full + 8 * stage, sph);
                    row_item(mode, st + cw * 1280, st + 10240 + cw * 2560, st + 30720, b_empty + 8 * stage, g_slab + ro, (mode == 2 ? out : g_x1) + ro, (mode ? g_h2 : g_h) + ro, lane);
                    if (++stage == STAGES) { stage = 0; sph ^= 1; }
                }
            } else if (it.type == T_MOD) {
                const int kg = ct >> 3, c8 = ct & 7;
                float acc[8] = {0, 0, 0, 0, 0, 0, 0, 0};
                const bf16* wp = w_mod + (size_t)kg * 20 * 3840 + it.nt * 64 + c8 * 8;
#pragma unroll 1
                for (int i0 = 0; i0 < 20; i0 += 10) {
                    uint4 w[10]; float sl[10];
#pragma unroll
                    for (int i = 0; i < 10; i++) { w[i] = __ldg((const uint4*)(wp + (size_t)(i0 + i) * 3840)); sl[i] = __bfloat162float(cvec[kg * 20 + i0 + i]); }
#pragma unroll
                    for (int i = 0; i < 10; i++) {
                        const float s = bf16r(__fdividef(sl[i], 1.0f + __expf(-sl[i])));
                        acc[0] += s * __uint_as_float(w[i].x << 16); acc[1] += s * __uint_as_float(w[i].x & 0xffff0000u);
                        acc[2] += s * __uint_as_float(w[i].y << 16); acc[3] += s * __uint_as_float(w[i].y & 0xffff0000u);
                        acc[4] += s * __uint_as_float(w[i].z << 16); acc[5] += s * __uint_as_float(w[i].z & 0xffff0000u);
                        acc[6] += s * __uint_as_float(w[i].w << 16); acc[7] += s * __uint_as_float(w[i].w & 0xffff0000u);
                    }
                }
#pragma unroll
                for (int i = 0; i < 8; i++) { acc[i] += __shfl_xor_sync(0xffffffff, acc[i], 8); acc[i] += __shfl_xor_sync(0xffffffff, acc[i], 16); }
                float* scr = (float*)(smem + OFF_BAR + 256);
                bar_sync(3, 256);
                if (lane < 8) {
#pragma unroll
                    for (int i = 0; i < 8; i++) scr[cw * 64 + lane * 8 + i] = acc[i];
                }
                bar_sync(3, 256);
                if (ct < 64) {
                    float sum = 0;
#pragma unroll
                    for (int i = 0; i < 8; i++) sum += scr[i * 64 + ct];
                    g_mod[it.nt * 64 + ct] = bf16r(sum);
                }
            }
            __syncwarp();
            if (lane == 0) mbar_arrive(b_cdone + 8 * wg);
        }
    }
}

typedef CUresult (*PFN_encodeTiled)(CUtensorMap*, CUtensorMapDataType, cuuint32_t, void*, const cuuint64_t*, const cuuint64_t*, const cuuint32_t*, const cuuint32_t*, CUtensorMapInterleave, CUtensorMapSwizzle, CUtensorMapL2promotion, CUtensorMapFloatOOBfill);

static void make_map(PFN_encodeTiled fn, CUtensorMap* m, const void* ptr, uint64_t inner, uint64_t outer, uint32_t box_inner, uint32_t box_outer) {
    cuuint64_t dims[2] = {inner, outer};
    cuuint64_t strides[1] = {inner * 2};
    cuuint32_t box[2] = {box_inner, box_outer};
    cuuint32_t es[2] = {1, 1};
    fn(m, CU_TENSOR_MAP_DATA_TYPE_BFLOAT16, 2, (void*)ptr, dims, strides, box, es, CU_TENSOR_MAP_INTERLEAVE_NONE, CU_TENSOR_MAP_SWIZZLE_128B, CU_TENSOR_MAP_L2_PROMOTION_L2_256B, CU_TENSOR_MAP_FLOAT_OOB_FILL_NONE);
}

static int g_dbg_mode = 0;

extern "C" void kernel_launch(void* const* d_in, const int* in_sizes, int n_in, void* d_out, int out_size) {
    const bf16* x = (const bf16*)d_in[0];
    const bf16* mem0 = (const bf16*)d_in[1];
    const bf16* Wq = (const bf16*)d_in[2];
    const bf16* Wk = (const bf16*)d_in[3];
    const bf16* Wv = (const bf16*)d_in[4];
    const bf16* Wo = (const bf16*)d_in[5];
    const bf16* Wg = (const bf16*)d_in[8];
    const bf16* Wu = (const bf16*)d_in[9];
    const bf16* Wd = (const bf16*)d_in[10];
    const bf16* cvec = (const bf16*)d_in[11];
    const bf16* wmod = (const bf16*)d_in[12];
    static PFN_encodeTiled fn = nullptr;
    static int nsm = 0;
    if (!fn) {
        cudaDriverEntryPointQueryResult qr;
        cudaGetDriverEntryPoint("cuTensorMapEncodeTiled", (void**)&fn, cudaEnableDefault, &qr);
        cudaFuncSetAttribute(r_kernel, cudaFuncAttributeMaxDynamicSharedMemorySize, rk::SMEM_BYTES);
        cudaFuncSetAttribute(r_kernel, cudaFuncAttributeNonPortableClusterSizeAllowed, 1);
        cudaFuncSetAttribute(g_kernel, cudaFuncAttributeMaxDynamicSharedMemorySize, gk::SMEM_BYTES);
        cudaDeviceGetAttribute(&nsm, cudaDevAttrMultiProcessorCount, 0);
    }
    void *ph, *po, *ph2, *pact, *pq, *pk, *pv;
    cudaGetSymbolAddress(&pq, g_q); cudaGetSymbolAddress(&pk, g_k); cudaGetSymbolAddress(&pv, g_v);
    cudaGetSymbolAddress(&ph, g_h); cudaGetSymbolAddress(&po, g_o); cudaGetSymbolAddress(&ph2, g_h2); cudaGetSymbolAddress(&pact, g_act);
    GParams P;
    make_map(fn, &P.tA_h, ph, 640, 2048, 64, 128);
    make_map(fn, &P.tA_o, po, 4096, 2048, 64, 128);
    make_map(fn, &P.tA_h2, ph2, 640, 2048, 64, 128);
    make_map(fn, &P.tA_act, pact, 1728, 2048, 64, 128);
    make_map(fn, &P.tB_q, Wq, 4096, 640, 64, 64);
    make_map(fn, &P.tB_k, Wk, 4096, 640, 64, 64);
    make_map(fn, &P.tB_v, Wv, 4096, 640, 64, 64);
    make_map(fn, &P.tB_o, Wo, 640, 4096, 64, 64);
    make_map(fn, &P.tB_g, Wg, 1728, 640, 64, 64);
    make_map(fn, &P.tB_u, Wu, 1728, 640, 64, 64);
    make_map(fn, &P.tB_d, Wd, 640, 1728, 64, 64);
    make_map(fn, &P.tS_q, pq, 4096, 2048, 64, 64);
    make_map(fn, &P.tS_k, pk, 4096, 2048, 64, 64);
    make_map(fn, &P.tS_v, pv, 4096, 2048, 64, 64);
    make_map(fn, &P.tS_act, pact, 1728, 2048, 64, 64);
    void *pkm, *pvm; cudaGetSymbolAddress(&pkm, g_km); cudaGetSymbolAddress(&pvm, g_vm);
    make_map(fn, &P.tS_o, po, 4096, 2048, 64, 64);
    make_map(fn, &P.tL_q, pq, 4096, 2048, 64, 128);
    make_map(fn, &P.tL_k, pk, 4096, 2048, 64, 128);
    make_map(fn, &P.tL_v, pv, 4096, 2048, 64, 128);
    make_map(fn, &P.tL_km, pkm, 4096, 512, 64, 32);
    make_map(fn, &P.tL_vm, pvm, 4096, 512, 64, 32);
    cudaStream_t st = cudaStreamPerThread;
    if (g_dbg_mode != 1) {
        cudaLaunchConfig_t cfg = {};
        cfg.gridDim = dim3(64); cfg.blockDim = dim3(256); cfg.dynamicSmemBytes = rk::SMEM_BYTES; cfg.stream = st;
        cudaLaunchAttribute at[1]; at[0].id = cudaLaunchAttributeClusterDimension; at[0].val.clusterDim.x = 16; at[0].val.clusterDim.y = 1; at[0].val.clusterDim.z = 1;
        cfg.attrs = at; cfg.numAttrs = 1;
        CUtensorMap tk, tv;
        make_map(fn, &tk, pk, 4096, 2048, 64, 32);
        make_map(fn, &tv, pv, 4096, 2048, 64, 32);
        cudaLaunchKernelEx(&cfg, r_kernel, tk, tv, mem0, Wq, Wk, Wv, Wo, 1);
    }
    {
        cudaLaunchConfig_t cfg = {};
        cfg.gridDim = dim3(nsm); cfg.blockDim = dim3(384); cfg.dynamicSmemBytes = gk::SMEM_BYTES; cfg.stream = st;
        cudaLaunchAttribute at[1]; at[0].id = cudaLaunchAttributeProgrammaticStreamSerialization; at[0].val.programmaticStreamSerializationAllowed = 1;
        cfg.attrs = at; cfg.numAttrs = g_dbg_mode == 1 ? 0 : 1;
        cudaLaunchKernelEx(&cfg, g_kernel, P, x, cvec, wmod, (bf16*)d_out, nsm, g_dbg_mode == 1 ? 0 : 1);
    }
}
```

```cpp
#include <cuda_runtime.h>
#include <cuda_bf16.h>
#include <cuda.h>
#include <stdint.h>

typedef __nv_bfloat16 bf16;

__device__ __forceinline__ uint32_t smem_u32(const void* p) { return (uint32_t)__cvta_generic_to_shared(p); }
__device__ __forceinline__ uint32_t mapa_u32(uint32_t a, uint32_t r) { uint32_t o; asm volatile("mapa.shared::cluster.u32 %0, %1, %2;" : "=r"(o) : "r"(a), "r"(r)); return o; }
__device__ __forceinline__ void mbar_init(uint32_t bar, uint32_t cnt) { asm volatile("mbarrier.init.shared::cta.b64 [%0], %1;" :: "r"(bar), "r"(cnt) : "memory"); }
__device__ __forceinline__ void mbar_expect_tx(uint32_t bar, uint32_t bytes) { asm volatile("mbarrier.arrive.expect_tx.shared::cta.b64 _, [%0], %1;" :: "r"(bar), "r"(bytes) : "memory"); }
__device__ __forceinline__ void mbar_arrive(uint32_t bar) { asm volatile("mbarrier.arrive.shared::cta.b64 _, [%0];" :: "r"(bar) : "memory"); }
#define SPIN_LIMIT 400000
__device__ __forceinline__ void mbar_wait(uint32_t bar, uint32_t ph) {
    uint32_t ok = 0; int lim = 0;
    while (true) {
        asm volatile("{ .reg .pred p; mbarrier.try_wait.parity.shared::cta.b64 p, [%1], %2; selp.u32 %0, 1, 0, p; }" : "=r"(ok) : "r"(bar), "r"(ph) : "memory");
        if (ok) break;
        if (++lim > SPIN_LIMIT) break;
    }
}
__device__ __forceinline__ void mbar_wait_cluster(uint32_t bar, uint32_t ph) {
    uint32_t ok = 0; int lim = 0;
    while (true) {
        asm volatile("{ .reg .pred p; mbarrier.try_wait.parity.acquire.cluster.shared::cta.b64 p, [%1], %2; selp.u32 %0, 1, 0, p; }" : "=r"(ok) : "r"(bar), "r"(ph) : "memory");
        if (ok) break;
        if (++lim > SPIN_LIMIT) break;
    }
}
__device__ __forceinline__ void st_async_v4(uint32_t addr, uint32_t a, uint32_t b, uint32_t c, uint32_t d, uint32_t bar) {
    asm volatile("st.async.weak.shared::cluster.mbarrier::complete_tx::bytes.v4.b32 [%0], {%1,%2,%3,%4}, [%5];" :: "r"(addr), "r"(a), "r"(b), "r"(c), "r"(d), "r"(bar) : "memory");
}
__device__ __forceinline__ void ldsm_x4(uint32_t* r, uint32_t addr) {
    asm volatile("ldmatrix.sync.aligned.m8n8.x4.shared.b16 {%0,%1,%2,%3}, [%4];" : "=r"(r[0]), "=r"(r[1]), "=r"(r[2]), "=r"(r[3]) : "r"(addr) : "memory");
}
__device__ __forceinline__ void ldsm_x4_t(uint32_t* r, uint32_t addr) {
    asm volatile("ldmatrix.sync.aligned.m8n8.x4.trans.shared.b16 {%0,%1,%2,%3}, [%4];" : "=r"(r[0]), "=r"(r[1]), "=r"(r[2]), "=r"(r[3]) : "r"(addr) : "memory");
}
__device__ __forceinline__ void mma16816(float* d, const uint32_t* a, uint32_t b0, uint32_t b1) {
    asm volatile("mma.sync.aligned.m16n8k16.row.col.f32.bf16.bf16.f32 {%0,%1,%2,%3}, {%4,%5,%6,%7}, {%8,%9}, {%0,%1,%2,%3};"
        : "+f"(d[0]), "+f"(d[1]), "+f"(d[2]), "+f"(d[3]) : "r"(a[0]), "r"(a[1]), "r"(a[2]), "r"(a[3]), "r"(b0), "r"(b1));
}
__device__ __forceinline__ uint32_t pack_bf16(float lo, float hi) {
    uint32_t r; asm("cvt.rn.bf16x2.f32 %0, %1, %2;" : "=r"(r) : "f"(hi), "f"(lo)); return r;
}
__device__ __forceinline__ float bf16r(float x) { return __bfloat162float(__float2bfloat16_rn(x)); }
__device__ __forceinline__ uint4 lds128(uint32_t a) { uint4 v; asm volatile("ld.shared.v4.u32 {%0,%1,%2,%3}, [%4];" : "=r"(v.x), "=r"(v.y), "=r"(v.z), "=r"(v.w) : "r"(a) : "memory"); return v; }
__device__ __forceinline__ void sts128(uint32_t a, uint4 v) { asm volatile("st.shared.v4.u32 [%0], {%1,%2,%3,%4};" :: "r"(a), "r"(v.x), "r"(v.y), "r"(v.z), "r"(v.w) : "memory"); }
__device__ __forceinline__ void sts32(uint32_t a, uint32_t v) { asm volatile("st.shared.u32 [%0], %1;" :: "r"(a), "r"(v) : "memory"); }
__device__ __forceinline__ void sts64(uint32_t a, uint32_t x, uint32_t y) { asm volatile("st.shared.v2.u32 [%0], {%1,%2};" :: "r"(a), "r"(x), "r"(y) : "memory"); }
__device__ __forceinline__ void sts16(uint32_t a, uint16_t v) { asm volatile("st.shared.u16 [%0], %1;" :: "r"(a), "h"(v) : "memory"); }
__device__ __forceinline__ uint2 lds64(uint32_t a) { uint2 v; asm volatile("ld.shared.v2.u32 {%0,%1}, [%2];" : "=r"(v.x), "=r"(v.y) : "r"(a) : "memory"); return v; }
__device__ __forceinline__ void cp_async16(uint32_t dst, const void* src) { asm volatile("cp.async.cg.shared.global [%0], [%1], 16;" :: "r"(dst), "l"(src) : "memory"); }
__device__ __forceinline__ void cp_async_wait_all() { asm volatile("cp.async.wait_all;" ::: "memory"); }
__device__ __forceinline__ void bar_sync(int id, int n) { asm volatile("bar.sync %0, %1;" :: "r"(id), "r"(n) : "memory"); }
__device__ __forceinline__ uint4 ld_relaxed_v4(const void* p) {
    uint4 v; asm volatile("ld.relaxed.gpu.global.v4.u32 {%0,%1,%2,%3}, [%4];" : "=r"(v.x), "=r"(v.y), "=r"(v.z), "=r"(v.w) : "l"(p) : "memory"); return v;
}
__device__ __forceinline__ void st_relaxed_v4(void* p, uint4 v) {
    asm volatile("st.relaxed.gpu.global.v4.u32 [%0], {%1,%2,%3,%4};" :: "l"(p), "r"(v.x), "r"(v.y), "r"(v.z), "r"(v.w) : "memory");
}
__device__ __forceinline__ uint32_t ld_acquire(const uint32_t* p) { uint32_t v; asm volatile("ld.acquire.gpu.global.u32 %0, [%1];" : "=r"(v) : "l"(p) : "memory"); return v; }
__device__ __forceinline__ uint32_t ld_relaxed(const uint32_t* p) { uint32_t v; asm volatile("ld.relaxed.gpu.global.u32 %0, [%1];" : "=r"(v) : "l"(p) : "memory"); return v; }
__device__ __forceinline__ void st_release(uint32_t* p, uint32_t v) { asm volatile("st.release.gpu.global.u32 [%0], %1;" :: "l"(p), "r"(v) : "memory"); }
__device__ __forceinline__ void cluster_sync_all() {
    asm volatile("barrier.cluster.arrive.release.aligned;" ::: "memory");
    asm volatile("barrier.cluster.wait.acquire.aligned;" ::: "memory");
}

__device__ bf16 g_k[2048 * 4096];
__device__ bf16 g_v[2048 * 4096];
__device__ bf16 g_km[64 * 8 * 4096];
__device__ bf16 g_vm[64 * 8 * 4096];
__device__ uint4 g_gx[2][4][16][80];
__device__ uint32_t g_kvflag[16 * 64];
__device__ uint32_t g_epoch;
struct GState {
    uint32_t done, c_mod_a, c_mod_all, lq_claim;
    uint32_t pad0[28];
    unsigned long long hq_pub;
    uint32_t pad1[30];
    uint32_t hq_items, hq_claim, hq_hint;
    uint32_t pad2[29];
    uint32_t hq_ent[128];
    uint32_t f_h[16 * 32];
    uint32_t d_at[16 * 32];
    uint32_t c_at[16 * 32];
    uint32_t c_wo[16 * 32];
    uint32_t f_h2[16 * 32];
    uint32_t c_act[16 * 32];
    uint32_t c_f2[16 * 32];
};
__device__ GState g_st;
namespace gk {
enum { T_MOD, T_L1, T_KV, T_Q, T_AT, T_WO, T_L2, T_F1, T_F2, T_FIN, T_SKIP, T_END };
#define FINE_RB 14
__host__ __device__ __forceinline__ bool fine(int rb) { return rb >= FINE_RB; }
#define WO_COARSE 8
__host__ __device__ __forceinline__ int wo_split(int rb) { return fine(rb) ? 16 : WO_COARSE; }
__host__ __device__ __forceinline__ int f2_split(int rb) { return fine(rb) ? 9 : 3; }
__host__ __device__ __forceinline__ int n_nt(int rb) { return fine(rb) ? 5 : 3; }
__host__ __device__ __forceinline__ int n_f1(int rb) { return fine(rb) ? 27 : 14; }
__host__ __device__ __forceinline__ int group_size(int ty, int rb) {
    switch (ty) {
        case T_AT: return 32;
        case T_WO: return n_nt(rb) * wo_split(rb);
        case T_F1: return n_f1(rb);
        case T_F2: return n_nt(rb) * f2_split(rb);
        default: return 16;
    }
}
}
__device__ __forceinline__ uint32_t atom_add_acqrel(uint32_t* p, uint32_t v) {
    uint32_t o; asm volatile("atom.acq_rel.gpu.global.add.u32 %0, [%1], %2;" : "=r"(o) : "l"(p), "r"(v) : "memory"); return o;
}
__device__ __forceinline__ void publish_group(int ty, int rb, uint32_t e1) {
    const uint32_t n = gk::group_size(ty, rb);
    const unsigned long long old = atomicAdd(&g_st.hq_pub, (1ull << 32) | n);
    const uint32_t e = (uint32_t)(old >> 32), base = (uint32_t)old;
    st_release(&g_st.hq_ent[e], (uint32_t)ty | ((uint32_t)rb << 4) | (base << 8) | ((e1 & 255u) << 24));
    atomicAdd(&g_st.hq_items, n);
}
#define RT(i)

namespace rk {
constexpr int MEM_STRIDE = 1296;
constexpr int T_STRIDE = 272;
constexpr int OFF_W = 0;
constexpr int OFF_KX = 163840;
constexpr int OFF_VX = OFF_KX + 8192;
constexpr int OFF_MEM = OFF_VX + 8192;
constexpr int OFF_Q = OFF_MEM + 10240;
constexpr int OFF_KM = OFF_Q + 8 * T_STRIDE;
constexpr int OFF_VM = OFF_KM + 8 * T_STRIDE;
constexpr int OFF_O = OFF_VM + 8 * T_STRIDE;
constexpr int OFF_SC = OFF_O + 8 * T_STRIDE;
constexpr int OFF_RED = OFF_SC + 8 * 56 * 4;
constexpr int OFF_RS = OFF_RED + 6144;
constexpr int OFF_ST = OFF_RS + 8 * 80 * 16;
constexpr int OFF_BAR = OFF_ST + 640;
constexpr int OFF_TL = OFF_BAR + 128;
constexpr int SMEM_BYTES = OFF_TL + 512;

__device__ __forceinline__ uint32_t ldg_nc(const void* p) { uint32_t v; asm volatile("ld.global.nc.u32 %0, [%1];" : "=r"(v) : "l"(p)); return v; }
__device__ __forceinline__ void load_raw(uint32_t* a, const bf16* __restrict__ W, int ld, int ka, int kb, int cb, int g, int t) {
    const bf16* p = W + (uint32_t)((ka + 2 * t) * ld + cb + 2 * g);
    const bf16* q = W + (uint32_t)((kb + 2 * t) * ld + cb + 2 * g);
    a[0] = ldg_nc(p); a[1] = ldg_nc(p + ld); a[2] = ldg_nc(q); a[3] = ldg_nc(q + ld);
}
__device__ __forceinline__ void fix_frag(uint32_t* a) {
    const uint32_t w0 = a[0], w1 = a[1], w2 = a[2], w3 = a[3];
    a[0] = __byte_perm(w0, w1, 0x5410); a[1] = __byte_perm(w0, w1, 0x7632);
    a[2] = __byte_perm(w2, w3, 0x5410); a[3] = __byte_perm(w2, w3, 0x7632);
}
__device__ __forceinline__ int chunk_src(int d, int kh, int n) { return (d - 8 * kh - n / 5) & 15; }
__device__ __forceinline__ int chunk_col(int d, int kh, int n) { const int s = chunk_src(d, kh, n); return 320 * (s & 1) + 40 * (s >> 1) + 8 * (n % 5); }
}

#define RSTEP 20
#define TL(i)
#define TG(i)

__device__ __forceinline__ void tma_load_2d(uint32_t dst, const CUtensorMap* map, int c0, int c1, uint32_t bar) {
    asm volatile("cp.async.bulk.tensor.2d.shared::cluster.global.mbarrier::complete_tx::bytes [%0], [%1, {%3, %4}], [%2];"
        :: "r"(dst), "l"(map), "r"(bar), "r"(c0), "r"(c1) : "memory");
}
__device__ __forceinline__ uint32_t movmatrix_t(uint32_t a) { uint32_t d; asm volatile("movmatrix.sync.aligned.m8n8.trans.b16 %0, %1;" : "=r"(d) : "r"(a)); return d; }
__device__ __forceinline__ void stg128(void* p, uint4 v) { asm volatile("st.global.v4.u32 [%0], {%1,%2,%3,%4};" :: "l"(p), "r"(v.x), "r"(v.y), "r"(v.z), "r"(v.w) : "memory"); }

__global__ void __launch_bounds__(256, 1)
r_kernel(const __grid_constant__ CUtensorMap tmK, const __grid_constant__ CUtensorMap tmV, const bf16* __restrict__ mem0, const bf16* __restrict__ Wq, const bf16* __restrict__ Wk, const bf16* __restrict__ Wv, const bf16* __restrict__ Wo, int wait_kv)
{
    using namespace rk;
    extern __shared__ __align__(1024) uint8_t smem[];
    const uint32_t sb = smem_u32(smem);
    const int tid = threadIdx.x, warp = tid >> 5, lane = tid & 31, g = lane >> 2, t = lane & 3;
    uint32_t rank, cid;
    asm volatile("mov.u32 %0, %%cluster_ctarank;" : "=r"(rank));
    asm volatile("mov.u32 %0, %%clusterid.x;" : "=r"(cid));
    const int hh = rank >> 1, j = rank & 1, h = cid * 8 + hh;
    const int kh = warp & 1, mb = warp >> 1;
    const uint32_t b_mem = sb + OFF_BAR, b_qkv = b_mem + 64, b_rs = b_mem + 72, b_kv = b_mem + 80;

    RT(64);
    asm volatile("griddepcontrol.launch_dependents;");
    const uint32_t epoch = ld_relaxed(&g_epoch);

    if (tid == 0) {
        for (int i = 0; i < 8; i++) mbar_init(b_mem + 8 * i, 1);
        mbar_init(b_qkv, 9); mbar_init(b_rs, 1); mbar_init(b_kv, 1);
        asm volatile("fence.mbarrier_init.release.cluster;" ::: "memory");
    }
    const uint32_t wsm = sb + OFF_W + (warp < 4 ? warp * 22528 : 4 * 22528 + (warp - 4) * 18432) + lane * 16;
    {
        const size_t co = (size_t)h * 128 + 64 * j;
        for (int i = tid; i < 640; i += 256) {
            asm volatile("prefetch.global.L2 [%0];" :: "l"(Wv + (size_t)i * 4096 + co));
            asm volatile("prefetch.global.L2 [%0];" :: "l"(Wo + ((size_t)h * 128 + i / 5) * 640 + 320 * j + (i % 5) * 64));
            asm volatile("prefetch.global.L2 [%0];" :: "l"(Wq + (size_t)i * 4096 + co));
            asm volatile("prefetch.global.L2 [%0];" :: "l"(Wk + (size_t)i * 4096 + co));
        }
    }
    uint32_t wq[20][4], wk[20][4];
    {
        const int cb = h * 128 + 64 * j + 16 * mb;
#pragma unroll
        for (int i = 0; i < 20; i++) load_raw(wq[i], Wv, 4096, chunk_col(rank, kh, 2 * i), chunk_col(rank, kh, 2 * i + 1), cb, g, t);
        const bf16* Woh = Wo + (size_t)h * 128 * 640;
        const int c3 = 320 * j + 16 * warp;
#pragma unroll
        for (int i = 0; i < 16; i++) load_raw(wk[i], Woh, 640, (i & 7) * 16, (i & 7) * 16 + 8, c3 + 128 * (i >> 3), g, t);
#pragma unroll
        for (int i = 0; i < 20; i++) { fix_frag(wq[i]); sts128(wsm + i * 512, make_uint4(wq[i][0], wq[i][1], wq[i][2], wq[i][3])); }
        if (warp < 4) {
#pragma unroll
            for (int i = 0; i < 8; i++) load_raw(wq[i], Woh, 640, i * 16, i * 16 + 8, c3 + 256, g, t);
        }
#pragma unroll
        for (int i = 0; i < 16; i++) { fix_frag(wk[i]); sts128(wsm + (20 + i) * 512, make_uint4(wk[i][0], wk[i][1], wk[i][2], wk[i][3])); }
#pragma unroll
        for (int i = 0; i < 20; i++) load_raw(wk[i], Wk, 4096, chunk_col(rank, kh, 2 * i), chunk_col(rank, kh, 2 * i + 1), cb, g, t);
        if (warp < 4) {
#pragma unroll
            for (int i = 0; i < 8; i++) { fix_frag(wq[i]); sts128(wsm + (36 + i) * 512, make_uint4(wq[i][0], wq[i][1], wq[i][2], wq[i][3])); }
        }
#pragma unroll
        for (int i = 0; i < 20; i++) load_raw(wq[i], Wq, 4096, chunk_col(rank, kh, 2 * i), chunk_col(rank, kh, 2 * i + 1), cb, g, t);
#pragma unroll
        for (int i = 0; i < 20; i++) { fix_frag(wk[i]); fix_frag(wq[i]); }
    }
    for (int i = tid; i < 640; i += 256) {
        int row = i / 80, c = i % 80;
        uint4 v = __ldg((const uint4*)(mem0 + row * 640 + c * 8));
        const int jj = c / 40, h5 = (c % 40) / 5;
        sts128(sb + OFF_MEM + (((int)rank - (2 * h5 + jj)) & 15) * 640 + row * 80 + (c % 5) * 16, v);
    }
    auto prefetch_kv = [&](int s) {
        if ((wait_kv & 1) && (s & 3) == 0) {
            const uint32_t* fk = &g_kvflag[(s >> 2) * 64 + h];
            int lim = 0;
            while (ld_acquire(fk) != epoch + 1) { if (++lim > SPIN_LIMIT) break; }
            while (ld_acquire(fk + 32) != epoch + 1) { if (++lim > SPIN_LIMIT) break; }
            asm volatile("fence.proxy.async.global;" ::: "memory");
        }
        mbar_expect_tx(b_kv, 16384);
        tma_load_2d(sb + OFF_KX, &tmK, h * 128, s * 32, b_kv);
        tma_load_2d(sb + OFF_KX + 4096, &tmK, h * 128 + 64, s * 32, b_kv);
        tma_load_2d(sb + OFF_VX, &tmV, h * 128, s * 32, b_kv);
        tma_load_2d(sb + OFF_VX + 4096, &tmV, h * 128 + 64, s * 32, b_kv);
    };
    __syncthreads();
    RT(65);
    __syncthreads();
    cluster_sync_all();

    const float scale = 0.08838834764831845f;
#define LAUNDER() int tid_ = threadIdx.x; asm volatile("" : "+r"(tid_)); const int warp = tid_ >> 5, lane = tid_ & 31, g = lane >> 2, t = lane & 3; (void)g; (void)t; (void)warp;
#define WSM() (sb + OFF_W + (warp < 4 ? warp * 22528 : 4 * 22528 + (warp - 4) * 18432) + lane * 16)

#pragma unroll 1
    for (int s = 0; s < 64; s++) {
        const uint32_t ph = s & 1;
        RT(s);
        {
            LAUNDER();
            TL(0);
            const int kh = warp & 1, mb = warp >> 1;
            const uint32_t wsm = WSM();
            const uint32_t mb0 = sb + OFF_MEM + kh * 5120 + (lane & 7) * 80 + (lane >> 3) * 16;
            const uint32_t mb1 = mb0 + ((lane >> 3) >= 1 ? 560 : 0), mb2 = mb0 + ((lane >> 3) >= 2 ? 560 : 0), mb3 = mb0 + ((lane >> 3) >= 3 ? 560 : 0);
            auto baddr = [&](int it) {
                const int r5 = (4 * it) % 5, c = ((4 * it) / 5) * 640 + r5 * 16;
                return (r5 <= 1 ? mb0 : (r5 == 4 ? mb1 : (r5 == 3 ? mb2 : mb3))) + c;
            };
            uint4 va[6];
            va[0] = lds128(wsm); va[1] = lds128(wsm + 512); va[2] = lds128(wsm + 1024); va[3] = lds128(wsm + 1536);
            if (s > 0) { mbar_wait(b_mem, ph ^ 1); mbar_wait(b_mem + 8, ph ^ 1); }
            TL(1); TG(15);
            float aq0[4] = {0, 0, 0, 0}, aq1[4] = {0, 0, 0, 0}, ak0[4] = {0, 0, 0, 0}, ak1[4] = {0, 0, 0, 0}, av0[4] = {0, 0, 0, 0}, av1[4] = {0, 0, 0, 0};
            uint32_t b[3][4];
            ldsm_x4(b[0], baddr(0)); ldsm_x4(b[1], baddr(1));
            if (tid_ == 0) {
                mbar_expect_tx(b_qkv, 3072);
                if (s < 63) mbar_expect_tx(b_rs, 10240);
            }
#pragma unroll
            for (int i = 0; i < 10; i++) {
                if (i + 2 < 10) {
                    const int it = i + 2, sl = (4 * it + 3) / 5, slp = (4 * (it - 1) + 3) / 5;
                    if (sl != slp && s > 0) mbar_wait(b_mem + 8 * sl, ph ^ 1);
                    ldsm_x4(b[(i + 2) % 3], baddr(i + 2));
                    va[(2 * i + 4) % 6] = lds128(wsm + (2 * i + 4) * 512); va[(2 * i + 5) % 6] = lds128(wsm + (2 * i + 5) * 512);
                }
                const uint32_t* bb = b[i % 3];
                mma16816(aq0, wq[2 * i], bb[0], bb[1]); mma16816(ak0, wk[2 * i], bb[0], bb[1]); mma16816(av0, (uint32_t*)&va[(2 * i) % 6], bb[0], bb[1]);
                mma16816(aq1, wq[2 * i + 1], bb[2], bb[3]); mma16816(ak1, wk[2 * i + 1], bb[2], bb[3]); mma16816(av1, (uint32_t*)&va[(2 * i + 1) % 6], bb[2], bb[3]);
            }
            float snd[4], fin[4];
#pragma unroll
            for (int i = 0; i < 4; i++) { float q = aq0[i] + aq1[i], k = ak0[i] + ak1[i]; snd[i] = kh ? q : k; fin[i] = kh ? k : q; av0[i] += av1[i]; }
            sts128(sb + OFF_RED + tid_ * 16, make_uint4(__float_as_uint(snd[0]), __float_as_uint(snd[1]), __float_as_uint(snd[2]), __float_as_uint(snd[3])));
            sts64(sb + OFF_RED + 4096 + tid_ * 8, __float_as_uint(kh ? av0[0] : av0[1]), __float_as_uint(kh ? av0[2] : av0[3]));
            bar_sync(1 + mb, 64);
            uint4 r = lds128(sb + OFF_RED + (tid_ ^ 32) * 16);
            uint2 r2 = lds64(sb + OFF_RED + 4096 + (tid_ ^ 32) * 8);
            fin[0] += __uint_as_float(r.x); fin[1] += __uint_as_float(r.y); fin[2] += __uint_as_float(r.z); fin[3] += __uint_as_float(r.w);
            float f0 = (kh ? av0[1] : av0[0]) + __uint_as_float(r2.x), f1 = (kh ? av0[3] : av0[2]) + __uint_as_float(r2.y);
            TL(2);
            const uint32_t cofs = (64 * j + 16 * mb) * 2;
            const uint32_t buf = sb + (kh ? OFF_KM : OFF_Q) + cofs;
            sts32(buf + (2 * t) * T_STRIDE + g * 4, pack_bf16(fin[0], fin[2]));
            sts32(buf + (2 * t + 1) * T_STRIDE + g * 4, pack_bf16(fin[1], fin[3]));
            sts32(sb + OFF_VM + cofs + (2 * t + kh) * T_STRIDE + g * 4, pack_bf16(f0, f1));
            __syncwarp();
            if (lane < 24) {
                const uint32_t peer_off = mapa_u32(sb, rank ^ 1) - sb;
                const int row = lane < 16 ? (lane >> 1) : 2 * ((lane - 16) >> 1) + kh;
                const uint32_t a = (lane < 16 ? buf : sb + OFF_VM + cofs) + row * T_STRIDE + (lane & 1) * 16;
                uint4 v = lds128(a);
                st_async_v4(a + peer_off, v.x, v.y, v.z, v.w, b_qkv + peer_off);
                if ((kh || lane >= 16) && !(wait_kv & 8)) {
                    bf16* dst = (lane < 16 ? g_km : g_vm) + ((uint32_t)(s * 8 + row) * 4096u + h * 128 + 64 * j + 16 * mb + (lane & 1) * 8);
                    stg128(dst, v);
                }
            }
            if (lane == 0) mbar_arrive(b_qkv);
            if (s == 0 && tid_ == 224) prefetch_kv(0);
            TL(3);
        }
        if (s == 63) {
            __syncthreads();
            if (threadIdx.x == 0 && (wait_kv & 1)) { if (atom_add_acqrel(&g_st.d_at[15 * 32], 1) + 1 == (epoch + 1) * 112) publish_group(gk::T_AT, 15, epoch + 1); }
            break;
        }
        uint4 wa[8];
        {
            LAUNDER();
            const uint32_t wsm = WSM();
            if (!(wait_kv & 2) || s == 0) mbar_wait(b_kv, ph);
            if (warp >= 4 && warp < 7) {
                const int kw = warp - 4;
                uint32_t ka[8][4];
                if (kw < 2) {
                    const uint32_t kaddr = sb + OFF_KX + (16 * kw + (lane & 15)) * 128;
#pragma unroll
                    for (int i = 0; i < 8; i++) ldsm_x4(ka[i], kaddr + (i >> 2) * 4096 + ((((2 * i + (lane >> 4)) & 7) ^ (lane & 7)) << 4));
                    mbar_wait(b_qkv, ph);
                } else {
                    mbar_wait(b_qkv, ph);
                    const uint32_t kaddr = sb + OFF_KM + (lane & 7) * T_STRIDE + (lane >> 4) * 16;
#pragma unroll
                    for (int i = 0; i < 8; i++) ldsm_x4(ka[i], kaddr + i * 32);
                }
                TL(5);
                const uint32_t qa = sb + OFF_Q + (lane & 7) * T_STRIDE + (lane >> 3) * 16;
                uint32_t qb[4][4];
#pragma unroll
                for (int i = 0; i < 4; i++) ldsm_x4(qb[i], qa + i * 64);
                float s0[4] = {0, 0, 0, 0}, s1[4] = {0, 0, 0, 0}, s2[4] = {0, 0, 0, 0}, s3[4] = {0, 0, 0, 0};
                mma16816(s0, ka[0], qb[0][0], qb[0][1]); mma16816(s1, ka[1], qb[0][2], qb[0][3]);
                mma16816(s2, ka[2], qb[1][0], qb[1][1]); mma16816(s3, ka[3], qb[1][2], qb[1][3]);
                mma16816(s0, ka[4], qb[2][0], qb[2][1]); mma16816(s1, ka[5], qb[2][2], qb[2][3]);
                mma16816(s2, ka[6], qb[3][0], qb[3][1]); mma16816(s3, ka[7], qb[3][2], qb[3][3]);
                const uint32_t sc = sb + OFF_SC + (16 * kw + g) * 4 + (2 * t) * 224;
                sts32(sc, __float_as_uint(bf16r(bf16r((s0[0] + s1[0]) + (s2[0] + s3[0])) * scale)));
                sts32(sc + 224, __float_as_uint(bf16r(bf16r((s0[1] + s1[1]) + (s2[1] + s3[1])) * scale)));
                if (kw < 2) {
                    sts32(sc + 32, __float_as_uint(bf16r(bf16r((s0[2] + s1[2]) + (s2[2] + s3[2])) * scale)));
                    sts32(sc + 32 + 224, __float_as_uint(bf16r(bf16r((s0[3] + s1[3]) + (s2[3] + s3[3])) * scale)));
                }
                asm volatile("bar.arrive 6, 224;" ::: "memory");
                TL(4);
#pragma unroll
                for (int i = 0; i < 8; i++) wa[i] = lds128(wsm + (20 + i) * 512);
            } else {
#pragma unroll
                for (int i = 0; i < 8; i++) wa[i] = lds128(wsm + (20 + i) * 512);
                if (warp < 4) {
                    mbar_wait(b_qkv, ph);
                    uint32_t a0[2][4], a1[2][4], a2[2][4];
#pragma unroll
                    for (int u = 0; u < 2; u++) {
                        const int et = warp + 4 * u;
                        const uint32_t vx = sb + OFF_VX + u * 4096 + ((lane >> 4) * 8 + (lane & 7)) * 128 + ((((2 * warp + ((lane >> 3) & 1)) & 7) ^ (lane & 7)) << 4);
                        ldsm_x4_t(a0[u], vx); ldsm_x4_t(a1[u], vx + 16 * 128);
                        ldsm_x4_t(a2[u], sb + OFF_VM + (lane & 7) * T_STRIDE + (16 * et + ((lane >> 3) & 1) * 8) * 2);
                    }
                    bar_sync(6, 224);
                    TL(6);
                    float x[10];
#pragma unroll
                    for (int i = 0; i < 5; i++) { uint2 v = lds64(sb + OFF_SC + g * 224 + (8 * i + 2 * t) * 4); x[2 * i] = __uint_as_float(v.x); x[2 * i + 1] = __uint_as_float(v.y); }
                    float m = fmaxf(fmaxf(fmaxf(x[0], x[1]), fmaxf(x[2], x[3])), fmaxf(fmaxf(x[4], x[5]), fmaxf(x[6], x[7])));
                    m = fmaxf(m, fmaxf(x[8], x[9]));
                    m = fmaxf(m, __shfl_xor_sync(0xffffffff, m, 1)); m = fmaxf(m, __shfl_xor_sync(0xffffffff, m, 2));
                    float sum0 = 0, sum1 = 0;
#pragma unroll
                    for (int i = 0; i < 5; i++) { x[2 * i] = __expf(x[2 * i] - m); sum0 += x[2 * i]; x[2 * i + 1] = __expf(x[2 * i + 1] - m); sum1 += x[2 * i + 1]; }
                    float sum = sum0 + sum1;
                    sum += __shfl_xor_sync(0xffffffff, sum, 1); sum += __shfl_xor_sync(0xffffffff, sum, 2);
                    float inv = __fdividef(1.0f, sum);
                    if (inv == 123.f) TL(14);
                    TL(4);
                    uint32_t pb[5];
#pragma unroll
                    for (int i = 0; i < 5; i++) pb[i] = pack_bf16(x[2 * i] * inv, x[2 * i + 1] * inv);
#pragma unroll
                    for (int u = 0; u < 2; u++) {
                        float o0[4] = {0, 0, 0, 0}, o1[4] = {0, 0, 0, 0}, o2[4] = {0, 0, 0, 0};
                        mma16816(o0, a0[u], pb[0], pb[1]); mma16816(o1, a1[u], pb[2], pb[3]); mma16816(o2, a2[u], pb[4], 0u);
                        const uint32_t lo = movmatrix_t(pack_bf16((o0[0] + o1[0]) + o2[0], (o0[1] + o1[1]) + o2[1]));
                        const uint32_t hi = movmatrix_t(pack_bf16((o0[2] + o1[2]) + o2[2], (o0[3] + o1[3]) + o2[3]));
                        const uint32_t oa = sb + OFF_O + g * T_STRIDE + (16 * (warp + 4 * u) + 2 * t) * 2;
                        sts32(oa, lo); sts32(oa + 16, hi);
                    }
                    TL(5);
                } else {
                    if (lane < 8) mbar_expect_tx(b_mem + 8 * lane, 1280);
                }
            }
        }
        __syncthreads();
        {
            LAUNDER();
            TL(7);
            const uint32_t wsm = WSM();
            uint32_t ob[16];
            const uint32_t oa = sb + OFF_O + (lane & 7) * T_STRIDE + (lane >> 3) * 16;
#pragma unroll
            for (int i = 0; i < 4; i++) ldsm_x4(ob + 4 * i, oa + i * 64);
            const uint32_t rs_base = OFF_RS + hh * 1280 + t * 16;
            const int ntile = warp < 4 ? 3 : 2;
#pragma unroll 1
            for (int tl = 0; tl < ntile; tl++) {
                float d0[4] = {0, 0, 0, 0}, d1[4] = {0, 0, 0, 0}, d2[4] = {0, 0, 0, 0}, d3[4] = {0, 0, 0, 0};
                const bool more = tl + 1 < ntile;
                const uint32_t nx = wsm + (28 + 8 * tl) * 512;
                mma16816(d0, (uint32_t*)&wa[0], ob[0], ob[1]);   if (more) wa[0] = lds128(nx);
                mma16816(d1, (uint32_t*)&wa[1], ob[2], ob[3]);   if (more) wa[1] = lds128(nx + 512);
                mma16816(d2, (uint32_t*)&wa[2], ob[4], ob[5]);   if (more) wa[2] = lds128(nx + 1024);
                mma16816(d3, (uint32_t*)&wa[3], ob[6], ob[7]);   if (more) wa[3] = lds128(nx + 1536);
                mma16816(d0, (uint32_t*)&wa[4], ob[8], ob[9]);   if (more) wa[4] = lds128(nx + 2048);
                mma16816(d1, (uint32_t*)&wa[5], ob[10], ob[11]); if (more) wa[5] = lds128(nx + 2560);
                mma16816(d2, (uint32_t*)&wa[6], ob[12], ob[13]); if (more) wa[6] = lds128(nx + 3072);
                mma16816(d3, (uint32_t*)&wa[7], ob[14], ob[15]); if (more) wa[7] = lds128(nx + 3584);
                const int col = 16 * (warp + 8 * tl) + 2 * g; const int own = col / 40; const int cp = (col - own * 40) >> 1;
                const uint32_t dbase = mapa_u32(sb, 2 * own + j);
                st_async_v4(dbase + rs_base + cp * 64, __float_as_uint((d0[0] + d1[0]) + (d2[0] + d3[0])), __float_as_uint((d0[1] + d1[1]) + (d2[1] + d3[1])),
                            __float_as_uint((d0[2] + d1[2]) + (d2[2] + d3[2])), __float_as_uint((d0[3] + d1[3]) + (d2[3] + d3[3])), dbase + OFF_BAR + 72);
            }
            TL(8);
        }
        {
            LAUNDER();
            if (warp >= 5) {
                const int x = tid_ - 160;
                const int ot = x < 80 ? x : 79;
                const uint32_t gs = epoch * 64 + s; const uint32_t tag = (gs + 1) & 15u; const int slot = gs & 1;
                uint4* gp = &g_gx[slot][0][rank][ot];
                mbar_wait(b_rs, ph);
                TL(9); TG(12);
                uint4 u[8];
#pragma unroll
                for (int q = 0; q < 8; q++) u[q] = lds128(sb + OFF_RS + q * 1280 + ot * 16);
                float4 a;
                a.x = ((__uint_as_float(u[0].x) + __uint_as_float(u[1].x)) + (__uint_as_float(u[2].x) + __uint_as_float(u[3].x))) + ((__uint_as_float(u[4].x) + __uint_as_float(u[5].x)) + (__uint_as_float(u[6].x) + __uint_as_float(u[7].x)));
                a.y = ((__uint_as_float(u[0].y) + __uint_as_float(u[1].y)) + (__uint_as_float(u[2].y) + __uint_as_float(u[3].y))) + ((__uint_as_float(u[4].y) + __uint_as_float(u[5].y)) + (__uint_as_float(u[6].y) + __uint_as_float(u[7].y)));
                a.z = ((__uint_as_float(u[0].z) + __uint_as_float(u[1].z)) + (__uint_as_float(u[2].z) + __uint_as_float(u[3].z))) + ((__uint_as_float(u[4].z) + __uint_as_float(u[5].z)) + (__uint_as_float(u[6].z) + __uint_as_float(u[7].z)));
                a.w = ((__uint_as_float(u[0].w) + __uint_as_float(u[1].w)) + (__uint_as_float(u[2].w) + __uint_as_float(u[3].w))) + ((__uint_as_float(u[4].w) + __uint_as_float(u[5].w)) + (__uint_as_float(u[6].w) + __uint_as_float(u[7].w)));
                uint4 mine = make_uint4((__float_as_uint(a.x) & ~15u) | tag, (__float_as_uint(a.y) & ~15u) | tag, (__float_as_uint(a.z) & ~15u) | tag, (__float_as_uint(a.w) & ~15u) | tag);
                if (x < 80) st_relaxed_v4(gp + cid * 1280, mine);
                uint4 v[3];
                const uint4* rp0 = gp + (cid ^ 1) * 1280; const uint4* rp1 = gp + (cid ^ 2) * 1280; const uint4* rp2 = gp + (cid ^ 3) * 1280;
                int lim = 0;
                while (true) {
                    v[0] = ld_relaxed_v4(rp0); v[1] = ld_relaxed_v4(rp1); v[2] = ld_relaxed_v4(rp2);
                    uint32_t bad = 0;
#pragma unroll
                    for (int c = 0; c < 3; c++) bad |= (v[c].x ^ tag) | (v[c].y ^ tag) | (v[c].z ^ tag) | (v[c].w ^ tag);
                    if ((bad & 15u) == 0) break;
                    if (++lim > SPIN_LIMIT) break;
                }
                float f0 = (__uint_as_float(mine.x) + __uint_as_float(v[0].x)) + (__uint_as_float(v[1].x) + __uint_as_float(v[2].x));
                float f1 = (__uint_as_float(mine.y) + __uint_as_float(v[0].y)) + (__uint_as_float(v[1].y) + __uint_as_float(v[2].y));
                float f2 = (__uint_as_float(mine.z) + __uint_as_float(v[0].z)) + (__uint_as_float(v[1].z) + __uint_as_float(v[2].z));
                float f3 = (__uint_as_float(mine.w) + __uint_as_float(v[0].w)) + (__uint_as_float(v[1].w) + __uint_as_float(v[2].w));
                const int cp = ot >> 2, tt = ot & 3;
                sts32(sb + OFF_ST + (2 * tt) * 80 + cp * 4, pack_bf16(f0, f2));
                sts32(sb + OFF_ST + (2 * tt + 1) * 80 + cp * 4, pack_bf16(f1, f3));
                TL(10); TG(13);
                bar_sync(5, 128);
                if (x < 80) {
                    const int c = x % 40, d0 = x / 40;
                    uint4 w = lds128(sb + OFF_ST + c * 16);
                    const uint32_t off = OFF_MEM + d0 * 5120 + c * 16;
#pragma unroll
                    for (int i = 0; i < 8; i++) {
                        const uint32_t rb = mapa_u32(sb, (d0 * 8 + i + rank) & 15);
                        st_async_v4(rb + off + i * 640, w.x, w.y, w.z, w.w, rb + OFF_BAR + 8 * i);
                    }
                }
            } else if (warp == 4) {
                if (lane == 0 && (s & 3) == 3 && (wait_kv & 1)) { if (atom_add_acqrel(&g_st.d_at[(s >> 2) * 32], 1) + 1 == (epoch + 1) * 112) publish_group(gk::T_AT, s >> 2, epoch + 1); }
                __syncwarp();
            } else if (warp == 3) {
                bar_sync(5, 128);
                if (lane == 0 && s < 62 && !(wait_kv & 2)) prefetch_kv(s + 1);
                __syncwarp();
            }
            TL(11);
        }
    }
    cluster_sync_all();
}

__device__ float g_mod[3840];
__device__ bf16 g_h[2048 * 640];
__device__ bf16 g_q[2048 * 4096];
__device__ bf16 g_o[2048 * 4096];
__device__ bf16 g_x1[2048 * 640];
__device__ bf16 g_h2[2048 * 640];
__device__ bf16 g_act[2048 * 1728];
__device__ float g_slab[2048 * 640];

namespace gk {
constexpr int STAGES = 4;
constexpr int STAGE_BYTES = 49152;
constexpr int OFF_SCR = STAGES * STAGE_BYTES;
constexpr int OFF_BAR = OFF_SCR + 32768;
constexpr int SMEM_BYTES = OFF_BAR + 256 + 2048;
constexpr int N_MOD = 60, N_L1 = 256, N_KV = 32, N_Q = 16;
constexpr int I_L1 = N_MOD, I_W = I_L1 + N_L1;
constexpr int N_LOW = I_W + 16 * (N_KV + N_Q);
constexpr int NFINE = 16 - FINE_RB;
constexpr int N_HIGH = 16 * (32 + 16 + 16) + (16 - NFINE) * (3 * WO_COARSE + 14 + 9) + NFINE * (80 + 27 + 45);
struct Item { int type, rb, nt, ks; };
__host__ __device__ inline Item decode_low(int t) {
    Item it; it.rb = 0; it.nt = 0; it.ks = 0;
    if (t < I_L1) { it.type = T_MOD; it.nt = t; return it; }
    if (t < I_W) { it.type = T_L1; it.rb = (t - I_L1) >> 4; it.nt = (t - I_L1) & 15; return it; }
    t -= I_W;
    if (t < 64) { it.type = T_KV; it.rb = t >> 5; it.nt = t & 31; return it; }
    t -= 64;
    if (t < 14 * 48) { const int w = t / 48; t -= w * 48; if (t < 16) { it.type = T_Q; it.rb = w; it.nt = t; } else { it.type = T_KV; it.rb = w + 2; it.nt = t - 16; } return it; }
    t -= 14 * 48;
    it.type = T_Q; it.rb = 14 + (t >> 4); it.nt = t & 15; return it;
}
__device__ __forceinline__ bool is_wide(const Item& it) {
    if (it.type == T_KV || it.type == T_Q) return true;
    if (it.type == T_F1) return !fine(it.rb);
    if (it.type == T_WO || it.type == T_F2) return !fine(it.rb) && it.nt < 2;
    return false;
}
__device__ __forceinline__ int red_col(const Item& it) { return fine(it.rb) ? it.nt * 128 : it.nt * 256; }
__device__ __forceinline__ int pack_item(const Item& it) { return it.type | (it.rb << 4) | (it.nt << 8) | (it.ks << 16); }
__device__ __forceinline__ Item unpack_item(int v) { Item it; it.type = v & 15; it.rb = (v >> 4) & 15; it.nt = (v >> 8) & 255; it.ks = (v >> 16) & 255; return it; }
}

struct GParams {
    CUtensorMap tA_h, tA_o, tA_h2, tA_act, tB_q, tB_k, tB_v, tB_o, tB_g, tB_u, tB_d, tS_q, tS_k, tS_v, tS_act, tS_o, tL_q, tL_k, tL_v, tL_km, tL_vm, tR_acc;
};

__device__ __forceinline__ void wait_ge(const uint32_t* p, uint32_t target) {
    int lim = 0;
    while ((int32_t)(ld_acquire(p) - target) < 0) { __nanosleep(64); if (++lim > SPIN_LIMIT) break; }
}
__device__ __forceinline__ void red_add_relaxed(uint32_t* p, uint32_t v) { asm volatile("red.relaxed.gpu.global.add.u32 [%0], %1;" :: "l"(p), "r"(v) : "memory"); }
__device__ __forceinline__ void st_relaxed_u32(uint32_t* p, uint32_t v) { asm volatile("st.relaxed.gpu.global.u32 [%0], %1;" :: "l"(p), "r"(v) : "memory"); }
__device__ __forceinline__ void red_add_release(uint32_t* p, uint32_t v) { asm volatile("red.release.gpu.global.add.u32 [%0], %1;" :: "l"(p), "r"(v) : "memory"); }

__device__ __forceinline__ void wgmma_fence() { asm volatile("wgmma.fence.sync.aligned;" ::: "memory"); }
__device__ __forceinline__ void wgmma_commit() { asm volatile("wgmma.commit_group.sync.aligned;" ::: "memory"); }
template<int N> __device__ __forceinline__ void wgmma_wait() { asm volatile("wgmma.wait_group.sync.aligned %0;" :: "n"(N) : "memory"); }

template<int N> __device__ __forceinline__ void fence_acc(float* d) {
#pragma unroll
    for (int i = 0; i < N; i++) asm volatile("" : "+f"(d[i]) :: "memory");
}
#define ACC8(b) "+f"(d[b]), "+f"(d[b+1]), "+f"(d[b+2]), "+f"(d[b+3]), "+f"(d[b+4]), "+f"(d[b+5]), "+f"(d[b+6]), "+f"(d[b+7])
#define ACC32(b) ACC8(b), ACC8(b+8), ACC8(b+16), ACC8(b+24)
__device__ __forceinline__ void wgmma_n128(float* d, uint64_t da, uint64_t db, int scale_d) {
    asm volatile("{ .reg .pred p; setp.ne.b32 p, %66, 0;\n"
        "wgmma.mma_async.sync.aligned.m64n128k16.f32.bf16.bf16 {%0,%1,%2,%3,%4,%5,%6,%7,%8,%9,%10,%11,%12,%13,%14,%15,%16,%17,%18,%19,%20,%21,%22,%23,%24,%25,%26,%27,%28,%29,%30,%31,"
        "%32,%33,%34,%35,%36,%37,%38,%39,%40,%41,%42,%43,%44,%45,%46,%47,%48,%49,%50,%51,%52,%53,%54,%55,%56,%57,%58,%59,%60,%61,%62,%63}, %64, %65, p, 1, 1, 0, 1; }"
        : ACC32(0), ACC32(32) : "l"(da), "l"(db), "r"(scale_d));
}
__device__ __forceinline__ void wgmma_n256(float* d, uint64_t da, uint64_t db, int scale_d) {
    asm volatile("{ .reg .pred p; setp.ne.b32 p, %130, 0;\n"
        "wgmma.mma_async.sync.aligned.m64n256k16.f32.bf16.bf16 {%0,%1,%2,%3,%4,%5,%6,%7,%8,%9,%10,%11,%12,%13,%14,%15,%16,%17,%18,%19,%20,%21,%22,%23,%24,%25,%26,%27,%28,%29,%30,%31,"
        "%32,%33,%34,%35,%36,%37,%38,%39,%40,%41,%42,%43,%44,%45,%46,%47,%48,%49,%50,%51,%52,%53,%54,%55,%56,%57,%58,%59,%60,%61,%62,%63,"
        "%64,%65,%66,%67,%68,%69,%70,%71,%72,%73,%74,%75,%76,%77,%78,%79,%80,%81,%82,%83,%84,%85,%86,%87,%88,%89,%90,%91,%92,%93,%94,%95,"
        "%96,%97,%98,%99,%100,%101,%102,%103,%104,%105,%106,%107,%108,%109,%110,%111,%112,%113,%114,%115,%116,%117,%118,%119,%120,%121,%122,%123,%124,%125,%126,%127}, %128, %129, p, 1, 1, 0, 1; }"
        : ACC32(0), ACC32(32), ACC32(64), ACC32(96) : "l"(da), "l"(db), "r"(scale_d));
}
__device__ __forceinline__ uint64_t make_desc(uint32_t addr, uint32_t lbo, uint32_t sbo) {
    return (uint64_t)((addr & 0x3FFFF) >> 4) | ((uint64_t)(lbo >> 4) << 16) | ((uint64_t)(sbo >> 4) << 32) | ((uint64_t)1 << 62);
}

__device__ __forceinline__ float div_fix(float a, float b, float rb) { float q = a * rb; float r = fmaf(-q, b, a); return fmaf(r, rb, q); }
__device__ __forceinline__ void row_item(int mode, uint32_t sx, uint32_t sa, uint32_t sp, uint32_t bar_empty, float* __restrict__ acc, bf16* __restrict__ yout, bf16* __restrict__ out, int lane) {
    float x[20];
#pragma unroll
    for (int i = 0; i < 5; i++) {
        const uint2 v = lds64(sx + i * 256 + lane * 8);
        x[4 * i] = __uint_as_float(v.x << 16); x[4 * i + 1] = __uint_as_float(v.x & 0xffff0000u);
        x[4 * i + 2] = __uint_as_float(v.y << 16); x[4 * i + 3] = __uint_as_float(v.y & 0xffff0000u);
    }
    if (mode) {
#pragma unroll
        for (int i = 0; i < 5; i++) {
            const uint4 a = lds128(sa + i * 512 + lane * 16), gt = lds128(sp + i * 512 + lane * 16);
            x[4 * i] = bf16r(x[4 * i] + bf16r(__uint_as_float(gt.x) * bf16r(__uint_as_float(a.x)))); x[4 * i + 1] = bf16r(x[4 * i + 1] + bf16r(__uint_as_float(gt.y) * bf16r(__uint_as_float(a.y))));
            x[4 * i + 2] = bf16r(x[4 * i + 2] + bf16r(__uint_as_float(gt.z) * bf16r(__uint_as_float(a.z)))); x[4 * i + 3] = bf16r(x[4 * i + 3] + bf16r(__uint_as_float(gt.w) * bf16r(__uint_as_float(a.w))));
            *(uint2*)(yout + i * 128 + lane * 4) = make_uint2(pack_bf16(x[4 * i], x[4 * i + 1]), pack_bf16(x[4 * i + 2], x[4 * i + 3]));
            *(float4*)(acc + i * 128 + lane * 4) = make_float4(0.f, 0.f, 0.f, 0.f);
        }
        sp += 2560;
    }
    if (mode != 2) {
        float s = 0;
#pragma unroll
        for (int i = 0; i < 20; i++) s += x[i];
#pragma unroll
        for (int o = 16; o; o >>= 1) s += __shfl_xor_sync(0xffffffff, s, o);
        const float mean = s * (1.0f / 640.0f);
        float q = 0;
#pragma unroll
        for (int i = 0; i < 20; i++) { float d = x[i] - mean; q += d * d; }
#pragma unroll
        for (int o = 16; o; o >>= 1) q += __shfl_xor_sync(0xffffffff, q, o);
        const float m16 = bf16r(mean);
        const float sd = bf16r(sqrtf(bf16r(bf16r(q * (1.0f / 640.0f)) + 1e-5f)));
        const float rs = __frcp_rn(sd);
#pragma unroll
        for (int i = 0; i < 5; i++) {
            const uint4 sh = lds128(sp + i * 512 + lane * 16), sc = lds128(sp + 2560 + i * 512 + lane * 16);
            float y0 = bf16r(bf16r(div_fix(bf16r(x[4 * i] - m16), sd, rs)) * bf16r(1.0f + __uint_as_float(sc.x))) + __uint_as_float(sh.x);
            float y1 = bf16r(bf16r(div_fix(bf16r(x[4 * i + 1] - m16), sd, rs)) * bf16r(1.0f + __uint_as_float(sc.y))) + __uint_as_float(sh.y);
            float y2 = bf16r(bf16r(div_fix(bf16r(x[4 * i + 2] - m16), sd, rs)) * bf16r(1.0f + __uint_as_float(sc.z))) + __uint_as_float(sh.z);
            float y3 = bf16r(bf16r(div_fix(bf16r(x[4 * i + 3] - m16), sd, rs)) * bf16r(1.0f + __uint_as_float(sc.w))) + __uint_as_float(sh.w);
            *(uint2*)(out + i * 128 + lane * 4) = make_uint2(pack_bf16(y0, y1), pack_bf16(y2, y3));
        }
    }
    __syncwarp();
    if (lane == 0) mbar_arrive(bar_empty);
}

__device__ __forceinline__ float gelu_tanh(float x) {
    float u2 = x * fmaf(x * x, 2.0f * 0.7978845608028654f * 0.044715f * 1.4426950408889634f, 2.0f * 0.7978845608028654f * 1.4426950408889634f);
    float e; asm("ex2.approx.ftz.f32 %0, %1;" : "=f"(e) : "f"(-u2));
    return __fdividef(x, 1.0f + e);
}
__device__ __forceinline__ uint4 ldg128(const void* p) { uint4 v; asm volatile("ld.global.v4.u32 {%0,%1,%2,%3}, [%4];" : "=r"(v.x), "=r"(v.y), "=r"(v.z), "=r"(v.w) : "l"(p) : "memory"); return v; }
__device__ __forceinline__ float4 ldcg_f4(const float* p) { float4 v; asm volatile("ld.global.cg.v4.f32 {%0,%1,%2,%3}, [%4];" : "=f"(v.x), "=f"(v.y), "=f"(v.z), "=f"(v.w) : "l"(p) : "memory"); return v; }
__device__ __forceinline__ uint4 ldcg128(const void* p) { uint4 v; asm volatile("ld.global.cg.v4.u32 {%0,%1,%2,%3}, [%4];" : "=r"(v.x), "=r"(v.y), "=r"(v.z), "=r"(v.w) : "l"(p) : "memory"); return v; }

__device__ __forceinline__ void attn_scores(uint32_t sq, uint32_t sk, uint32_t skm, int sg, int mt, int lane, uint32_t (&p)[6][2]) {
    const int g = lane >> 2, t = lane & 3, l7 = lane & 7;
    float s[5][4];
#pragma unroll
    for (int kt = 0; kt < 5; kt++) s[kt][0] = s[kt][1] = s[kt][2] = s[kt][3] = 0.f;
    const uint32_t qrow = sq + (sg * 32 + mt * 16 + (lane & 15)) * 128;
    const uint32_t krow = sk + (sg * 32 + l7) * 128, kmrow = skm + (sg * 8 + l7) * 128;
#pragma unroll
    for (int c = 0; c < 4; c++) {
        uint32_t a0[4], a1[4];
        ldsm_x4(a0, qrow + (c >> 1) * 16384 + ((((4 * c + (lane >> 4)) & 7) ^ l7) << 4));
        ldsm_x4(a1, qrow + (c >> 1) * 16384 + ((((4 * c + 2 + (lane >> 4)) & 7) ^ l7) << 4));
        const uint32_t sw = (((4 * c + (lane >> 3)) & 7) ^ l7) << 4;
#pragma unroll
        for (int kt = 0; kt < 5; kt++) {
            uint32_t b[4];
            ldsm_x4(b, kt == 0 ? kmrow + (c >> 1) * 4096 + sw : krow + (kt - 1) * 1024 + (c >> 1) * 16384 + sw);
            mma16816(s[kt], a0, b[0], b[1]); mma16816(s[kt], a1, b[2], b[3]);
        }
    }
    const float scale = 0.08838834764831845f;
    const int r0 = mt * 16 + g, r1 = r0 + 8;
    float m0 = -INFINITY, m1 = -INFINITY;
#pragma unroll
    for (int kt = 0; kt < 5; kt++) {
#pragma unroll
        for (int i = 0; i < 4; i++) {
            float v = bf16r(bf16r(s[kt][i]) * scale);
            if (kt > 0) { int key = (kt - 1) * 8 + 2 * t + (i & 1); if (key > (i < 2 ? r0 : r1)) v = -1.0e9f; }
            s[kt][i] = v;
            if (i < 2) m0 = fmaxf(m0, v); else m1 = fmaxf(m1, v);
        }
    }
    m0 = fmaxf(m0, __shfl_xor_sync(0xffffffff, m0, 1)); m0 = fmaxf(m0, __shfl_xor_sync(0xffffffff, m0, 2));
    m1 = fmaxf(m1, __shfl_xor_sync(0xffffffff, m1, 1)); m1 = fmaxf(m1, __shfl_xor_sync(0xffffffff, m1, 2));
    float l0 = 0, l1 = 0;
#pragma unroll
    for (int kt = 0; kt < 5; kt++) {
        s[kt][0] = __expf(s[kt][0] - m0); s[kt][1] = __expf(s[kt][1] - m0); l0 += s[kt][0] + s[kt][1];
        s[kt][2] = __expf(s[kt][2] - m1); s[kt][3] = __expf(s[kt][3] - m1); l1 += s[kt][2] + s[kt][3];
    }
    l0 += __shfl_xor_sync(0xffffffff, l0, 1); l0 += __shfl_xor_sync(0xffffffff, l0, 2);
    l1 += __shfl_xor_sync(0xffffffff, l1, 1); l1 += __shfl_xor_sync(0xffffffff, l1, 2);
    const float i0 = __fdividef(1.0f, l0), i1 = __fdividef(1.0f, l1);
#pragma unroll
    for (int kt = 0; kt < 5; kt++) { p[kt][0] = pack_bf16(s[kt][0] * i0, s[kt][1] * i0); p[kt][1] = pack_bf16(s[kt][2] * i1, s[kt][3] * i1); }
    p[5][0] = p[5][1] = 0;
}
__device__ __forceinline__ void attn_pv(uint32_t sv, uint32_t svm, int sg, int lane, const uint32_t (&p)[6][2], float* d) {
    const int l7 = lane & 7, hi = (lane >> 3) & 1, ec = lane >> 4;
    const uint32_t r0 = hi ? sv + (sg * 32 + l7) * 128 : svm + (sg * 8 + l7) * 128;
    const uint32_t sub0 = hi ? 16384 : 4096;
    const uint32_t r1 = sv + (sg * 32 + 8 + hi * 8 + l7) * 128;
    const uint32_t r2 = sv + (sg * 32 + 24 + l7) * 128;
#pragma unroll
    for (int i = 0; i < 8; i++) {
        const uint32_t sw = (((2 * i + ec) & 7) ^ l7) << 4;
        uint32_t b0[4], b1[4], b2[4];
        ldsm_x4_t(b0, r0 + (i >> 2) * sub0 + sw); ldsm_x4_t(b1, r1 + (i >> 2) * 16384 + sw); ldsm_x4_t(b2, r2 + (i >> 2) * 16384 + sw);
        float* o0 = d + 8 * i; float* o1 = o0 + 4;
        o0[0] = o0[1] = o0[2] = o0[3] = o1[0] = o1[1] = o1[2] = o1[3] = 0.f;
        { uint32_t a[4] = {p[0][0], p[0][1], p[1][0], p[1][1]}; mma16816(o0, a, b0[0], b0[1]); mma16816(o1, a, b0[2], b0[3]); }
        { uint32_t a[4] = {p[2][0], p[2][1], p[3][0], p[3][1]}; mma16816(o0, a, b1[0], b1[1]); mma16816(o1, a, b1[2], b1[3]); }
        { uint32_t a[4] = {p[4][0], p[4][1], p[5][0], p[5][1]}; mma16816(o0, a, b2[0], b2[1]); mma16816(o1, a, b2[2], b2[3]); }
    }
}
__device__ __forceinline__ void bulk_load(uint32_t dst, const void* src, uint32_t bytes, uint32_t bar) {
    asm volatile("cp.async.bulk.shared::cluster.global.mbarrier::complete_tx::bytes [%0], [%1], %2, [%3];" :: "r"(dst), "l"(src), "r"(bytes), "r"(bar) : "memory");
}

__device__ __forceinline__ void stsm_x4(uint32_t addr, uint32_t a, uint32_t b, uint32_t c, uint32_t d) {
    asm volatile("stmatrix.sync.aligned.m8n8.x4.shared.b16 [%0], {%1,%2,%3,%4};" :: "r"(addr), "r"(a), "r"(b), "r"(c), "r"(d) : "memory");
}
__device__ __forceinline__ void tma_reduce_2d(const CUtensorMap* map, uint32_t src, int c0, int c1) {
    asm volatile("cp.reduce.async.bulk.tensor.2d.global.shared::cta.add.tile.bulk_group [%0, {%2, %3}], [%1];" :: "l"(map), "r"(src), "r"(c0), "r"(c1) : "memory");
}
__device__ __forceinline__ void tma_store_2d(const CUtensorMap* map, uint32_t src, int c0, int c1) {
    asm volatile("cp.async.bulk.tensor.2d.global.shared::cta.bulk_group [%0, {%2, %3}], [%1];" :: "l"(map), "r"(src), "r"(c0), "r"(c1) : "memory");
}

__global__ void __launch_bounds__(384, 1)
g_kernel(const __grid_constant__ GParams P, const bf16* __restrict__ x, const bf16* __restrict__ cvec, const bf16* __restrict__ w_mod, bf16* __restrict__ out, int nctas, int wait_r)
{
    using namespace gk;
    extern __shared__ __align__(1024) uint8_t smem[];
    const uint32_t sb = smem_u32(smem);
    const int tid = threadIdx.x, warp = tid >> 5, lane = tid & 31;
    const uint32_t b_full = sb + OFF_BAR, b_empty = b_full + 8 * STAGES, b_wfull = b_empty + 8 * STAGES, b_wempty = b_wfull + 16;
    const uint32_t b_cdone = b_wempty + 16, b_sfree = b_cdone + 16;
    volatile int* wslot = (volatile int*)(smem + OFF_BAR + 192);
    const uint32_t epoch = ld_relaxed(&g_epoch);
    const uint32_t e1 = epoch + 1;
    if (tid == 0) {
        for (int i = 0; i < STAGES; i++) { mbar_init(b_full + 8 * i, 1); mbar_init(b_empty + 8 * i, 8); }
        for (int i = 0; i < 2; i++) { mbar_init(b_wfull + 8 * i, 1); mbar_init(b_wempty + 8 * i, 9); mbar_init(b_cdone + 8 * i, 4); mbar_init(b_sfree + 8 * i, 1); }
        asm volatile("fence.mbarrier_init.release.cluster;" ::: "memory");
    }
    __syncthreads();

    if (warp < 4) {
        asm volatile("setmaxnreg.dec.sync.aligned.u32 40;");
        if (warp == 0 && lane == 0) {
            uint32_t stage = 0, sph = 1, wi = 0, wph = 1;
            int cur = 0; uint32_t ent = 0; bool have_ent = false, low_left = true;
            int held = -1, lim = 0;
            while (true) {
                Item it; it.type = T_END; it.rb = it.nt = it.ks = 0;
                int tk = 0; (void)tk;
                while (true) {
                    if (held < 0) {
                        const uint4 pk = ld_relaxed_v4(&g_st.hq_items);
                        const uint32_t pub = pk.x, clm = pk.y;
                        if ((int)pk.z > cur) { cur = (int)pk.z; have_ent = false; }
                        if (clm >= (uint32_t)N_HIGH && !low_left) break;
                        if (clm < pub) { held = (int)atomicAdd(&g_st.hq_claim, 1u); if (held >= N_HIGH) { held = -1; if (!low_left) break; } }
                    }
                    if (held >= 0) {
                        bool found = false;
                        while (true) {
                            if (!have_ent) { ent = ld_acquire(&g_st.hq_ent[cur]); have_ent = (ent >> 24) == (e1 & 255u) && ent != 0; if (!have_ent) break; }
                            const int ty = ent & 15, rb = (ent >> 4) & 15, base = (ent >> 8) & 0xffff;
                            const int n = group_size(ty, rb);
                            if (held < base + n) {
                                const int i = held - base;
                                it.type = ty; it.rb = rb; it.nt = i;
                                if (ty == T_WO || ty == T_F2) { const int nn = n_nt(rb); it.ks = i / nn; it.nt = i - it.ks * nn; }
                                if (i == 0) atomicMax(&g_st.hq_hint, (uint32_t)cur);
                                found = true; break;
                            }
                            cur++; have_ent = false;
                        }
                        if (found) {
                            held = -1; break;
                        }
                    }
                    if (low_left) {
                        const int lt = (int)atomicAdd(&g_st.lq_claim, 1u);
                        if (lt < N_LOW) {
                            it = decode_low(lt);
                            if (it.type == T_L1) wait_ge(&g_st.c_mod_a, e1 * 20);
                            else if (it.type != T_MOD) wait_ge(&g_st.f_h[it.rb * 32], e1 * 16);
                            break;
                        }
                        low_left = false;
                        continue;
                    }
                    __nanosleep(60);
                    if (++lim > SPIN_LIMIT) { held = -1; it.type = T_END; break; }
                }
                if (it.type == T_L2) wait_ge(&g_st.c_mod_all, e1 * 60);
                asm volatile("fence.proxy.async.global;" ::: "memory");
                mbar_wait(b_wempty + 8 * wi, wph);
                wslot[wi] = pack_item(it);
                mbar_arrive(b_wfull + 8 * wi);
                if (++wi == 2) { wi = 0; wph ^= 1; }
                if (it.type == T_END) break;
                int nkb = 0, kb0 = 0;
                const CUtensorMap *mA = nullptr, *mB0 = nullptr, *mB1 = nullptr; int n0 = 0, n1 = 0, nbox = 4;
                switch (it.type) {
                    case T_KV: nkb = 10; mA = &P.tA_h; mB0 = mB1 = (it.nt < 16) ? &P.tB_k : &P.tB_v; n0 = (it.nt & 15) * 256; n1 = n0 + 128; break;
                    case T_Q: nkb = 10; mA = &P.tA_h; mB0 = mB1 = &P.tB_q; n0 = it.nt * 256; n1 = n0 + 128; break;
                    case T_F1: nkb = 10; mA = &P.tA_h2; mB0 = &P.tB_g; mB1 = &P.tB_u; if (fine(it.rb)) { n0 = n1 = it.nt * 64; nbox = 2; } else n0 = n1 = it.nt * 128; break;
                    case T_WO: nkb = 64 / wo_split(it.rb); kb0 = it.ks * nkb; mA = &P.tA_o; mB0 = mB1 = &P.tB_o; n0 = red_col(it); if (is_wide(it)) n1 = n0 + 128; else { n1 = n0 + 64; nbox = 2; } break;
                    case T_F2: nkb = 27 / f2_split(it.rb); kb0 = it.ks * nkb; mA = &P.tA_act; mB0 = mB1 = &P.tB_d; n0 = red_col(it); if (is_wide(it)) n1 = n0 + 128; else { n1 = n0 + 64; nbox = 2; } break;
                    default: break;
                }
                if (it.type == T_AT) {
#pragma unroll 1
                    for (int i = 0; i < 3; i++) {
                        mbar_wait(b_empty + 8 * stage, sph);
                        const uint32_t st = sb + stage * STAGE_BYTES, bar = b_full + 8 * stage;
                        mbar_expect_tx(bar, i ? 40960 : 32768);
                        const CUtensorMap* m = i == 0 ? &P.tL_q : (i == 1 ? &P.tL_k : &P.tL_v);
                        tma_load_2d(st + 16384, m, it.nt * 128, it.rb * 128, bar);
                        tma_load_2d(st + 32768, m, it.nt * 128 + 64, it.rb * 128, bar);
                        if (i) {
                            const CUtensorMap* mm = i == 1 ? &P.tL_km : &P.tL_vm;
                            tma_load_2d(st, mm, it.nt * 128, it.rb * 32, bar);
                            tma_load_2d(st + 4096, mm, it.nt * 128 + 64, it.rb * 32, bar);
                        }
                        if (++stage == STAGES) { stage = 0; sph ^= 1; }
                    }
                } else if (it.type == T_L1 || it.type == T_L2 || it.type == T_FIN) {
                    const int mode = it.type == T_L1 ? 0 : (it.type == T_L2 ? 1 : 2);
                    const uint32_t pbytes = mode == 0 ? 5120 : (mode == 1 ? 7680 : 2560);
                    const float* psrc = g_mod + (mode == 0 ? 0 : (mode == 1 ? 2 * 640 : 5 * 640));
                    {
                        mbar_wait(b_empty + 8 * stage, sph);
                        const uint32_t st = sb + stage * STAGE_BYTES, bar = b_full + 8 * stage;
                        const size_t ro = ((size_t)it.rb * 128 + it.nt * 8) * 640;
                        mbar_expect_tx(bar, 10240 + (mode ? 20480 : 0) + pbytes);
                        bulk_load(st, (mode == 2 ? g_x1 : x) + ro, 10240, bar);
                        if (mode) bulk_load(st + 10240, g_slab + ro, 20480, bar);
                        bulk_load(st + 30720, psrc, pbytes, bar);
                        if (++stage == STAGES) { stage = 0; sph ^= 1; }
                    }
                }
                for (int kb = 0; kb < nkb; kb++) {
                    mbar_wait(b_empty + 8 * stage, sph);
                    const uint32_t st = sb + stage * STAGE_BYTES, bar = b_full + 8 * stage;
                    mbar_expect_tx(bar, 16384 + nbox * 8192);
                    const int k = (kb0 + kb) * 64;
                    tma_load_2d(st, mA, k, it.rb * 128, bar);
                    tma_load_2d(st + 16384, mB0, n0, k, bar);
                    if (nbox == 4) {
                        tma_load_2d(st + 16384 + 8192, mB0, n0 + 64, k, bar);
                        tma_load_2d(st + 16384 + 16384, mB1, n1, k, bar);
                        tma_load_2d(st + 16384 + 24576, mB1, n1 + 64, k, bar);
                    } else {
                        tma_load_2d(st + 16384 + 8192, mB1, n1, k, bar);
                    }
                    if (++stage == STAGES) { stage = 0; sph ^= 1; }
                }
            }
        } else if (warp == 1 && lane == 0) {
            uint32_t wi = 0, wph = 0, cph = 0;
            while (true) {
                mbar_wait(b_wfull + 8 * wi, wph);
                const Item it = unpack_item(wslot[wi]);
                mbar_arrive(b_wempty + 8 * wi);
                if (++wi == 2) { wi = 0; wph ^= 1; }
                if (it.type == T_END) break;
                const bool red = it.type == T_WO || it.type == T_F2;
                const bool tma = it.type == T_KV || it.type == T_Q || it.type == T_F1 || it.type == T_AT || red;
                const bool narrow = it.type == T_F1 && fine(it.rb);
                const int rounds = red ? (is_wide(it) ? 4 : 2) : ((it.type == T_KV || it.type == T_Q) ? 2 : 1);
                const CUtensorMap* mS = it.type == T_F1 ? &P.tS_act : (it.type == T_AT ? &P.tS_o : (it.type == T_Q ? &P.tS_q : (it.nt < 16 ? &P.tS_k : &P.tS_v)));
                const int gcol = red ? red_col(it) : (narrow ? it.nt * 64 : (rounds == 1 ? it.nt * 128 : (it.nt & 15) * 256));
                for (int rnd = 0; rnd < rounds; rnd++) {
                    for (int wg = 0; wg < 2; wg++) {
                        mbar_wait(b_cdone + 8 * wg, cph);
                        const uint32_t stg = sb + OFF_SCR + wg * 16384;
                        const int grow = it.rb * 128 + wg * 64;
                        if (red) {
                            tma_reduce_2d(&P.tR_acc, stg, gcol + rnd * 64, grow);
                            tma_reduce_2d(&P.tR_acc, stg + 8192, gcol + rnd * 64 + 32, grow);
                        } else if (tma) {
                            tma_store_2d(mS, stg, gcol + rnd * 128, grow);
                            if (!narrow) tma_store_2d(mS, stg + 8192, gcol + rnd * 128 + 64, grow);
                        }
                        if (tma) asm volatile("cp.async.bulk.commit_group;" ::: "memory");
                    }
                    cph ^= 1;
                    if (tma) asm volatile("cp.async.bulk.wait_group.read 0;" ::: "memory");
                    mbar_arrive(b_sfree); mbar_arrive(b_sfree + 8);
                }
                if (tma) { asm volatile("cp.async.bulk.wait_group 0;" ::: "memory"); asm volatile("fence.proxy.async.global;" ::: "memory"); }
                asm volatile("fence.acq_rel.gpu;" ::: "memory");
                uint32_t* cnt = nullptr; uint32_t tgt = 0; int nxt = -1;
                switch (it.type) {
                    case T_KV: st_relaxed_u32(&g_kvflag[it.rb * 64 + it.nt * 2], e1); st_relaxed_u32(&g_kvflag[it.rb * 64 + it.nt * 2 + 1], e1);
                    case T_Q: cnt = &g_st.d_at[it.rb * 32]; tgt = wait_r ? 112 : 48; nxt = T_AT; break;
                    case T_MOD: if (it.nt < 20) red_add_relaxed(&g_st.c_mod_a, 1); red_add_relaxed(&g_st.c_mod_all, 1); break;
                    case T_L1: red_add_relaxed(&g_st.f_h[it.rb * 32], 1); break;
                    case T_AT: cnt = &g_st.c_at[it.rb * 32]; tgt = 32; nxt = T_WO; break;
                    case T_WO: cnt = &g_st.c_wo[it.rb * 32]; tgt = group_size(T_WO, it.rb); nxt = T_L2; break;
                    case T_L2: cnt = &g_st.f_h2[it.rb * 32]; tgt = 16; nxt = T_F1; break;
                    case T_F1: cnt = &g_st.c_act[it.rb * 32]; tgt = group_size(T_F1, it.rb); nxt = T_F2; break;
                    case T_F2: cnt = &g_st.c_f2[it.rb * 32]; tgt = group_size(T_F2, it.rb); nxt = T_FIN; break;
                    default: break;
                }
                if (cnt) { if (atom_add_acqrel(cnt, 1) + 1 == e1 * tgt) publish_group(nxt, it.rb, e1); }
            }
            uint32_t old = atom_add_acqrel(&g_st.done, 1);
            if (old + 1 == e1 * (uint32_t)nctas) {
                g_st.hq_pub = 0; g_st.hq_items = 0; g_st.hq_claim = 0; g_st.hq_hint = 0; g_st.lq_claim = 0;
                st_release(&g_epoch, e1);
            }
        }
    } else {
        asm volatile("setmaxnreg.inc.sync.aligned.u32 232;");
        const int ct = tid - 128, cw = warp - 4, wg = cw >> 2;
        const int g = lane >> 2, t = lane & 3;
        uint32_t stage = 0, sph = 0, wi = 0, wph = 0, fph = 1;
        while (true) {
            mbar_wait(b_wfull + 8 * wi, wph);
            const Item it = unpack_item(wslot[wi]);
            __syncwarp();
            if (lane == 0) mbar_arrive(b_wempty + 8 * wi);
            if (++wi == 2) { wi = 0; wph ^= 1; }
            if (it.type == T_END) break;
            const bool narrow = it.type == T_F1 && fine(it.rb);
            if (is_wide(it)) {
                const bool red = it.type == T_WO || it.type == T_F2;
                const int nkb = it.type == T_WO ? 64 / wo_split(it.rb) : (it.type == T_F2 ? 27 / f2_split(it.rb) : 10);
                float d[128];
#pragma unroll
                for (int i = 0; i < 128; i++) d[i] = 0.f;
                for (int kb = 0; kb < nkb; kb++) {
                    mbar_wait(b_full + 8 * stage, sph);
                    const uint32_t st = sb + stage * STAGE_BYTES;
                    const uint64_t da = make_desc(st + wg * 8192, 16, 1024), db = make_desc(st + 16384, 8192, 1024);
                    wgmma_fence();
#pragma unroll
                    for (int k = 0; k < 4; k++) wgmma_n256(d, da + k * 2, db + k * 128, 1);
                    wgmma_commit();
                    wgmma_wait<1>();
                    if (kb > 0 && lane == 0) mbar_arrive(b_empty + 8 * ((stage + STAGES - 1) % STAGES));
                    if (++stage == STAGES) { stage = 0; sph ^= 1; }
                }
                wgmma_wait<0>();
                fence_acc<128>(d);
                if (lane == 0) mbar_arrive(b_empty + 8 * ((stage + STAGES - 1) % STAGES));
                if (red) {
                    const uint32_t sbase = sb + OFF_SCR + wg * 16384 + ((cw & 3) * 16 + g) * 128 + (t & 1) * 8;
#pragma unroll
                    for (int rnd = 0; rnd < 4; rnd++) {
                        mbar_wait(b_sfree + 8 * wg, fph); fph ^= 1;
#pragma unroll
                        for (int i = 0; i < 8; i++) {
                            const float* dd = d + rnd * 32 + i * 4;
                            const uint32_t a = sbase + (i >> 2) * 8192 + ((((2 * i + (t >> 1)) & 7) ^ (g & 7)) << 4);
                            sts64(a, __float_as_uint(dd[0]), __float_as_uint(dd[1]));
                            sts64(a + 1024, __float_as_uint(dd[2]), __float_as_uint(dd[3]));
                        }
                        asm volatile("fence.proxy.async.shared::cta;" ::: "memory");
                        __syncwarp();
                        if (lane == 0) mbar_arrive(b_cdone + 8 * wg);
                    }
                    continue;
                }
                const uint32_t sbase = sb + OFF_SCR + wg * 16384 + ((cw & 3) * 16 + ((lane >> 3) & 1) * 8 + (lane & 7)) * 128;
                const int sx = lane & 7, hi = lane >> 4;
                if (it.type == T_F1) {
#pragma unroll
                    for (int i = 0; i < 64; i++) d[i] = bf16r(gelu_tanh(bf16r(d[i]))) * bf16r(d[64 + i]);
                }
#pragma unroll
                for (int rnd = 0; rnd < 2; rnd++) {
                    if (rnd == 1 && it.type == T_F1) break;
                    mbar_wait(b_sfree + 8 * wg, fph); fph ^= 1;
#pragma unroll
                    for (int i = 0; i < 8; i++) {
                        const float* dd = d + rnd * 64 + i * 8;
                        const int chunk = (2 * i + hi) & 7;
                        stsm_x4(sbase + (i >> 2) * 8192 + ((chunk ^ sx) << 4), pack_bf16(dd[0], dd[1]), pack_bf16(dd[2], dd[3]), pack_bf16(dd[4], dd[5]), pack_bf16(dd[6], dd[7]));
                    }
                    asm volatile("fence.proxy.async.shared::cta;" ::: "memory");
                    __syncwarp();
                    if (lane == 0) mbar_arrive(b_cdone + 8 * wg);
                }
                continue;
            } else if (narrow) {
                float d[64];
#pragma unroll
                for (int i = 0; i < 64; i++) d[i] = 0.f;
                const int nkb = 10;
                for (int kb = 0; kb < nkb; kb++) {
                    mbar_wait(b_full + 8 * stage, sph);
                    const uint32_t st = sb + stage * STAGE_BYTES;
                    const uint64_t da = make_desc(st + wg * 8192, 16, 1024), db = make_desc(st + 16384, 8192, 1024);
                    wgmma_fence();
#pragma unroll
                    for (int k = 0; k < 4; k++) wgmma_n128(d, da + k * 2, db + k * 128, 1);
                    wgmma_commit();
                    wgmma_wait<1>();
                    if (kb > 0 && lane == 0) mbar_arrive(b_empty + 8 * ((stage + STAGES - 1) % STAGES));
                    if (++stage == STAGES) { stage = 0; sph ^= 1; }
                }
                wgmma_wait<0>();
                fence_acc<64>(d);
                if (lane == 0) mbar_arrive(b_empty + 8 * ((stage + STAGES - 1) % STAGES));
                {
                    const uint32_t sbase = sb + OFF_SCR + wg * 16384 + ((cw & 3) * 16 + ((lane >> 3) & 1) * 8 + (lane & 7)) * 128;
#pragma unroll
                    for (int i = 0; i < 32; i++) d[i] = bf16r(gelu_tanh(bf16r(d[i]))) * bf16r(d[32 + i]);
                    mbar_wait(b_sfree + 8 * wg, fph); fph ^= 1;
#pragma unroll
                    for (int i = 0; i < 4; i++) {
                        const float* dd = d + i * 8;
                        const int chunk = 2 * i + (lane >> 4);
                        stsm_x4(sbase + ((chunk ^ (lane & 7)) << 4), pack_bf16(dd[0], dd[1]), pack_bf16(dd[2], dd[3]), pack_bf16(dd[4], dd[5]), pack_bf16(dd[6], dd[7]));
                    }
                    asm volatile("fence.proxy.async.shared::cta;" ::: "memory");
                }
            } else if (it.type == T_WO || it.type == T_F2) {
                float d[64];
#pragma unroll
                for (int i = 0; i < 64; i++) d[i] = 0.f;
                const int nkb = it.type == T_WO ? 64 / wo_split(it.rb) : 27 / f2_split(it.rb);
                for (int kb = 0; kb < nkb; kb++) {
                    mbar_wait(b_full + 8 * stage, sph);
                    const uint32_t st = sb + stage * STAGE_BYTES;
                    const uint64_t da = make_desc(st + wg * 8192, 16, 1024), db = make_desc(st + 16384, 8192, 1024);
                    wgmma_fence();
#pragma unroll
                    for (int k = 0; k < 4; k++) wgmma_n128(d, da + k * 2, db + k * 128, 1);
                    wgmma_commit();
                    wgmma_wait<1>();
                    if (kb > 0 && lane == 0) mbar_arrive(b_empty + 8 * ((stage + STAGES - 1) % STAGES));
                    if (++stage == STAGES) { stage = 0; sph ^= 1; }
                }
                wgmma_wait<0>();
                fence_acc<64>(d);
                if (lane == 0) mbar_arrive(b_empty + 8 * ((stage + STAGES - 1) % STAGES));
                {
                    const int r0 = (cw & 3) * 16 + g;
                    const uint32_t sbase = sb + OFF_SCR + wg * 16384 + r0 * 128 + (t & 1) * 8;
#pragma unroll
                    for (int rnd = 0; rnd < 2; rnd++) {
                        mbar_wait(b_sfree + 8 * wg, fph); fph ^= 1;
#pragma unroll
                        for (int i = 0; i < 8; i++) {
                            const float* dd = d + rnd * 32 + i * 4;
                            const uint32_t a = sbase + (i >> 2) * 8192 + ((((2 * i + (t >> 1)) & 7) ^ (g & 7)) << 4);
                            sts64(a, __float_as_uint(dd[0]), __float_as_uint(dd[1]));
                            sts64(a + 1024, __float_as_uint(dd[2]), __float_as_uint(dd[3]));
                        }
                        asm volatile("fence.proxy.async.shared::cta;" ::: "memory");
                        if (rnd == 0) { __syncwarp(); if (lane == 0) mbar_arrive(b_cdone + 8 * wg); }
                    }
                }
            } else if (it.type == T_AT) {
                uint32_t p[6][2];
                float d[64];
                const uint32_t s0 = stage, s1 = (stage + 1) % STAGES, s2 = (stage + 2) % STAGES;
                mbar_wait(b_full + 8 * s0, sph);
                mbar_wait(b_full + 8 * s1, s1 < s0 ? sph ^ 1 : sph);
                attn_scores(sb + s0 * STAGE_BYTES + 16384, sb + s1 * STAGE_BYTES + 16384, sb + s1 * STAGE_BYTES, cw >> 1, cw & 1, lane, p);
                __syncwarp();
                if (lane == 0) { mbar_arrive(b_empty + 8 * s0); mbar_arrive(b_empty + 8 * s1); }
                mbar_wait(b_full + 8 * s2, s2 < s0 ? sph ^ 1 : sph);
                attn_pv(sb + s2 * STAGE_BYTES + 16384, sb + s2 * STAGE_BYTES, cw >> 1, lane, p, d);
                __syncwarp();
                if (lane == 0) mbar_arrive(b_empty + 8 * s2);
                stage += 3; if (stage >= STAGES) { stage -= STAGES; sph ^= 1; }
                const uint32_t sbase = sb + OFF_SCR + wg * 16384 + ((cw & 3) * 16 + ((lane >> 3) & 1) * 8 + (lane & 7)) * 128;
                mbar_wait(b_sfree + 8 * wg, fph); fph ^= 1;
#pragma unroll
                for (int i = 0; i < 8; i++) {
                    const float* dd = d + i * 8;
                    const int chunk = (2 * i + (lane >> 4)) & 7;
                    stsm_x4(sbase + (i >> 2) * 8192 + ((chunk ^ (lane & 7)) << 4), pack_bf16(dd[0], dd[1]), pack_bf16(dd[2], dd[3]), pack_bf16(dd[4], dd[5]), pack_bf16(dd[6], dd[7]));
                }
                asm volatile("fence.proxy.async.shared::cta;" ::: "memory");
            } else if (it.type == T_L1 || it.type == T_L2 || it.type == T_FIN) {
                const int mode = it.type == T_L1 ? 0 : (it.type == T_L2 ? 1 : 2);
                {
                    const size_t ro = ((size_t)it.rb * 128 + it.nt * 8 + cw) * 640;
                    const uint32_t st = sb + stage * STAGE_BYTES;
                    mbar_wait(b_full + 8 * stage, sph);
                    row_item(mode, st + cw * 1280, st + 10240 + cw * 2560, st + 30720, b_empty + 8 * stage, g_slab + ro, (mode == 2 ? out : g_x1) + ro, (mode ? g_h2 : g_h) + ro, lane);
                    if (++stage == STAGES) { stage = 0; sph ^= 1; }
                }
            } else if (it.type == T_MOD) {
                const int kg = ct >> 3, c8 = ct & 7;
                float acc[8] = {0, 0, 0, 0, 0, 0, 0, 0};
                const bf16* wp = w_mod + (size_t)kg * 20 * 3840 + it.nt * 64 + c8 * 8;
                {
                    uint4 w[20]; float sl[20];
#pragma unroll
                    for (int i = 0; i < 20; i++) { w[i] = __ldg((const uint4*)(wp + (size_t)i * 3840)); sl[i] = __bfloat162float(cvec[kg * 20 + i]); }
#pragma unroll
                    for (int i = 0; i < 20; i++) {
                        const float s = bf16r(__fdividef(sl[i], 1.0f + __expf(-sl[i])));
                        acc[0] += s * __uint_as_float(w[i].x << 16); acc[1] += s * __uint_as_float(w[i].x & 0xffff0000u);
                        acc[2] += s * __uint_as_float(w[i].y << 16); acc[3] += s * __uint_as_float(w[i].y & 0xffff0000u);
                        acc[4] += s * __uint_as_float(w[i].z << 16); acc[5] += s * __uint_as_float(w[i].z & 0xffff0000u);
                        acc[6] += s * __uint_as_float(w[i].w << 16); acc[7] += s * __uint_as_float(w[i].w & 0xffff0000u);
                    }
                }
#pragma unroll
                for (int i = 0; i < 8; i++) { acc[i] += __shfl_xor_sync(0xffffffff, acc[i], 8); acc[i] += __shfl_xor_sync(0xffffffff, acc[i], 16); }
                float* scr = (float*)(smem + OFF_BAR + 256);
                bar_sync(3, 256);
                if (lane < 8) {
#pragma unroll
                    for (int i = 0; i < 8; i++) scr[cw * 64 + lane * 8 + i] = acc[i];
                }
                bar_sync(3, 256);
                if (ct < 64) {
                    float sum = 0;
#pragma unroll
                    for (int i = 0; i < 8; i++) sum += scr[i * 64 + ct];
                    g_mod[it.nt * 64 + ct] = bf16r(sum);
                }
            }
            if (it.type == T_MOD || it.type == T_L1 || it.type == T_L2 || it.type == T_FIN) { mbar_wait(b_sfree + 8 * wg, fph); fph ^= 1; }
            __syncwarp();
            if (lane == 0) mbar_arrive(b_cdone + 8 * wg);
        }
    }
}

typedef CUresult (*PFN_encodeTiled)(CUtensorMap*, CUtensorMapDataType, cuuint32_t, void*, const cuuint64_t*, const cuuint64_t*, const cuuint32_t*, const cuuint32_t*, CUtensorMapInterleave, CUtensorMapSwizzle, CUtensorMapL2promotion, CUtensorMapFloatOOBfill);

static void make_map(PFN_encodeTiled fn, CUtensorMap* m, const void* ptr, uint64_t inner, uint64_t outer, uint32_t box_inner, uint32_t box_outer, bool f32 = false) {
    cuuint64_t dims[2] = {inner, outer};
    cuuint64_t strides[1] = {inner * (f32 ? 4 : 2)};
    cuuint32_t box[2] = {box_inner, box_outer};
    cuuint32_t es[2] = {1, 1};
    fn(m, f32 ? CU_TENSOR_MAP_DATA_TYPE_FLOAT32 : CU_TENSOR_MAP_DATA_TYPE_BFLOAT16, 2, (void*)ptr, dims, strides, box, es, CU_TENSOR_MAP_INTERLEAVE_NONE, CU_TENSOR_MAP_SWIZZLE_128B, CU_TENSOR_MAP_L2_PROMOTION_L2_256B, CU_TENSOR_MAP_FLOAT_OOB_FILL_NONE);
}

static int g_dbg_mode = 0;

extern "C" void kernel_launch(void* const* d_in, const int* in_sizes, int n_in, void* d_out, int out_size) {
    const bf16* x = (const bf16*)d_in[0];
    const bf16* mem0 = (const bf16*)d_in[1];
    const bf16* Wq = (const bf16*)d_in[2];
    const bf16* Wk = (const bf16*)d_in[3];
    const bf16* Wv = (const bf16*)d_in[4];
    const bf16* Wo = (const bf16*)d_in[5];
    const bf16* Wg = (const bf16*)d_in[8];
    const bf16* Wu = (const bf16*)d_in[9];
    const bf16* Wd = (const bf16*)d_in[10];
    const bf16* cvec = (const bf16*)d_in[11];
    const bf16* wmod = (const bf16*)d_in[12];
    static PFN_encodeTiled fn = nullptr;
    static int nsm = 0;
    if (!fn) {
        cudaDriverEntryPointQueryResult qr;
        cudaGetDriverEntryPoint("cuTensorMapEncodeTiled", (void**)&fn, cudaEnableDefault, &qr);
        cudaFuncSetAttribute(r_kernel, cudaFuncAttributeMaxDynamicSharedMemorySize, rk::SMEM_BYTES);
        cudaFuncSetAttribute(r_kernel, cudaFuncAttributeNonPortableClusterSizeAllowed, 1);
        cudaFuncSetAttribute(g_kernel, cudaFuncAttributeMaxDynamicSharedMemorySize, gk::SMEM_BYTES);
        cudaDeviceGetAttribute(&nsm, cudaDevAttrMultiProcessorCount, 0);
    }
    void *ph, *po, *ph2, *pact, *pq, *pk, *pv;
    cudaGetSymbolAddress(&pq, g_q); cudaGetSymbolAddress(&pk, g_k); cudaGetSymbolAddress(&pv, g_v);
    cudaGetSymbolAddress(&ph, g_h); cudaGetSymbolAddress(&po, g_o); cudaGetSymbolAddress(&ph2, g_h2); cudaGetSymbolAddress(&pact, g_act);
    GParams P;
    make_map(fn, &P.tA_h, ph, 640, 2048, 64, 128);
    make_map(fn, &P.tA_o, po, 4096, 2048, 64, 128);
    make_map(fn, &P.tA_h2, ph2, 640, 2048, 64, 128);
    make_map(fn, &P.tA_act, pact, 1728, 2048, 64, 128);
    make_map(fn, &P.tB_q, Wq, 4096, 640, 64, 64);
    make_map(fn, &P.tB_k, Wk, 4096, 640, 64, 64);
    make_map(fn, &P.tB_v, Wv, 4096, 640, 64, 64);
    make_map(fn, &P.tB_o, Wo, 640, 4096, 64, 64);
    make_map(fn, &P.tB_g, Wg, 1728, 640, 64, 64);
    make_map(fn, &P.tB_u, Wu, 1728, 640, 64, 64);
    make_map(fn, &P.tB_d, Wd, 640, 1728, 64, 64);
    make_map(fn, &P.tS_q, pq, 4096, 2048, 64, 64);
    make_map(fn, &P.tS_k, pk, 4096, 2048, 64, 64);
    make_map(fn, &P.tS_v, pv, 4096, 2048, 64, 64);
    make_map(fn, &P.tS_act, pact, 1728, 2048, 64, 64);
    void *pkm, *pvm; cudaGetSymbolAddress(&pkm, g_km); cudaGetSymbolAddress(&pvm, g_vm);
    make_map(fn, &P.tS_o, po, 4096, 2048, 64, 64);
    make_map(fn, &P.tL_q, pq, 4096, 2048, 64, 128);
    make_map(fn, &P.tL_k, pk, 4096, 2048, 64, 128);
    make_map(fn, &P.tL_v, pv, 4096, 2048, 64, 128);
    make_map(fn, &P.tL_km, pkm, 4096, 512, 64, 32);
    make_map(fn, &P.tL_vm, pvm, 4096, 512, 64, 32);
    void* pacc; cudaGetSymbolAddress(&pacc, g_slab);
    make_map(fn, &P.tR_acc, pacc, 640, 2048, 32, 64, true);
    cudaStream_t st = cudaStreamPerThread;
    if (g_dbg_mode != 1) {
        cudaLaunchConfig_t cfg = {};
        cfg.gridDim = dim3(64); cfg.blockDim = dim3(256); cfg.dynamicSmemBytes = rk::SMEM_BYTES; cfg.stream = st;
        cudaLaunchAttribute at[1]; at[0].id = cudaLaunchAttributeClusterDimension; at[0].val.clusterDim.x = 16; at[0].val.clusterDim.y = 1; at[0].val.clusterDim.z = 1;
        cfg.attrs = at; cfg.numAttrs = 1;
        CUtensorMap tk, tv;
        make_map(fn, &tk, pk, 4096, 2048, 64, 32);
        make_map(fn, &tv, pv, 4096, 2048, 64, 32);
        cudaLaunchKernelEx(&cfg, r_kernel, tk, tv, mem0, Wq, Wk, Wv, Wo, 1);
    }
    {
        cudaLaunchConfig_t cfg = {};
        cfg.gridDim = dim3(nsm); cfg.blockDim = dim3(384); cfg.dynamicSmemBytes = gk::SMEM_BYTES; cfg.stream = st;
        cudaLaunchAttribute at[1]; at[0].id = cudaLaunchAttributeProgrammaticStreamSerialization; at[0].val.programmaticStreamSerializationAllowed = 1;
        cfg.attrs = at; cfg.numAttrs = g_dbg_mode == 1 ? 0 : 1;
        cudaLaunchKernelEx(&cfg, g_kernel, P, x, cvec, wmod, (bf16*)d_out, nsm, g_dbg_mode == 1 ? 0 : 1);
    }
}
```

```cpp
#include <cuda_runtime.h>
#include <cuda_bf16.h>
#include <cuda.h>
#include <stdint.h>

typedef __nv_bfloat16 bf16;

__device__ __forceinline__ uint32_t smem_u32(const void* p) { return (uint32_t)__cvta_generic_to_shared(p); }
__device__ __forceinline__ uint32_t mapa_u32(uint32_t a, uint32_t r) { uint32_t o; asm volatile("mapa.shared::cluster.u32 %0, %1, %2;" : "=r"(o) : "r"(a), "r"(r)); return o; }
__device__ __forceinline__ void mbar_init(uint32_t bar, uint32_t cnt) { asm volatile("mbarrier.init.shared::cta.b64 [%0], %1;" :: "r"(bar), "r"(cnt) : "memory"); }
__device__ __forceinline__ void mbar_expect_tx(uint32_t bar, uint32_t bytes) { asm volatile("mbarrier.arrive.expect_tx.shared::cta.b64 _, [%0], %1;" :: "r"(bar), "r"(bytes) : "memory"); }
__device__ __forceinline__ void mbar_arrive(uint32_t bar) { asm volatile("mbarrier.arrive.shared::cta.b64 _, [%0];" :: "r"(bar) : "memory"); }
#define SPIN_LIMIT 400000
__device__ __forceinline__ void mbar_wait(uint32_t bar, uint32_t ph) {
    uint32_t ok = 0; int lim = 0;
    while (true) {
        asm volatile("{ .reg .pred p; mbarrier.try_wait.parity.shared::cta.b64 p, [%1], %2; selp.u32 %0, 1, 0, p; }" : "=r"(ok) : "r"(bar), "r"(ph) : "memory");
        if (ok) break;
        if (++lim > SPIN_LIMIT) break;
    }
}
__device__ __forceinline__ void mbar_wait_cluster(uint32_t bar, uint32_t ph) {
    uint32_t ok = 0; int lim = 0;
    while (true) {
        asm volatile("{ .reg .pred p; mbarrier.try_wait.parity.acquire.cluster.shared::cta.b64 p, [%1], %2; selp.u32 %0, 1, 0, p; }" : "=r"(ok) : "r"(bar), "r"(ph) : "memory");
        if (ok) break;
        if (++lim > SPIN_LIMIT) break;
    }
}
__device__ __forceinline__ void st_async_v4(uint32_t addr, uint32_t a, uint32_t b, uint32_t c, uint32_t d, uint32_t bar) {
    asm volatile("st.async.weak.shared::cluster.mbarrier::complete_tx::bytes.v4.b32 [%0], {%1,%2,%3,%4}, [%5];" :: "r"(addr), "r"(a), "r"(b), "r"(c), "r"(d), "r"(bar) : "memory");
}
__device__ __forceinline__ void ldsm_x4(uint32_t* r, uint32_t addr) {
    asm volatile("ldmatrix.sync.aligned.m8n8.x4.shared.b16 {%0,%1,%2,%3}, [%4];" : "=r"(r[0]), "=r"(r[1]), "=r"(r[2]), "=r"(r[3]) : "r"(addr) : "memory");
}
__device__ __forceinline__ void ldsm_x4_t(uint32_t* r, uint32_t addr) {
    asm volatile("ldmatrix.sync.aligned.m8n8.x4.trans.shared.b16 {%0,%1,%2,%3}, [%4];" : "=r"(r[0]), "=r"(r[1]), "=r"(r[2]), "=r"(r[3]) : "r"(addr) : "memory");
}
__device__ __forceinline__ void mma16816(float* d, const uint32_t* a, uint32_t b0, uint32_t b1) {
    asm volatile("mma.sync.aligned.m16n8k16.row.col.f32.bf16.bf16.f32 {%0,%1,%2,%3}, {%4,%5,%6,%7}, {%8,%9}, {%0,%1,%2,%3};"
        : "+f"(d[0]), "+f"(d[1]), "+f"(d[2]), "+f"(d[3]) : "r"(a[0]), "r"(a[1]), "r"(a[2]), "r"(a[3]), "r"(b0), "r"(b1));
}
__device__ __forceinline__ uint32_t pack_bf16(float lo, float hi) {
    uint32_t r; asm("cvt.rn.bf16x2.f32 %0, %1, %2;" : "=r"(r) : "f"(hi), "f"(lo)); return r;
}
__device__ __forceinline__ float bf16r(float x) { return __bfloat162float(__float2bfloat16_rn(x)); }
__device__ __forceinline__ uint4 lds128(uint32_t a) { uint4 v; asm volatile("ld.shared.v4.u32 {%0,%1,%2,%3}, [%4];" : "=r"(v.x), "=r"(v.y), "=r"(v.z), "=r"(v.w) : "r"(a) : "memory"); return v; }
__device__ __forceinline__ void sts128(uint32_t a, uint4 v) { asm volatile("st.shared.v4.u32 [%0], {%1,%2,%3,%4};" :: "r"(a), "r"(v.x), "r"(v.y), "r"(v.z), "r"(v.w) : "memory"); }
__device__ __forceinline__ void sts32(uint32_t a, uint32_t v) { asm volatile("st.shared.u32 [%0], %1;" :: "r"(a), "r"(v) : "memory"); }
__device__ __forceinline__ void sts64(uint32_t a, uint32_t x, uint32_t y) { asm volatile("st.shared.v2.u32 [%0], {%1,%2};" :: "r"(a), "r"(x), "r"(y) : "memory"); }
__device__ __forceinline__ void sts16(uint32_t a, uint16_t v) { asm volatile("st.shared.u16 [%0], %1;" :: "r"(a), "h"(v) : "memory"); }
__device__ __forceinline__ uint2 lds64(uint32_t a) { uint2 v; asm volatile("ld.shared.v2.u32 {%0,%1}, [%2];" : "=r"(v.x), "=r"(v.y) : "r"(a) : "memory"); return v; }
__device__ __forceinline__ void cp_async16(uint32_t dst, const void* src) { asm volatile("cp.async.cg.shared.global [%0], [%1], 16;" :: "r"(dst), "l"(src) : "memory"); }
__device__ __forceinline__ void cp_async_wait_all() { asm volatile("cp.async.wait_all;" ::: "memory"); }
__device__ __forceinline__ void bar_sync(int id, int n) { asm volatile("bar.sync %0, %1;" :: "r"(id), "r"(n) : "memory"); }
__device__ __forceinline__ uint4 ld_relaxed_v4(const void* p) {
    uint4 v; asm volatile("ld.relaxed.gpu.global.v4.u32 {%0,%1,%2,%3}, [%4];" : "=r"(v.x), "=r"(v.y), "=r"(v.z), "=r"(v.w) : "l"(p) : "memory"); return v;
}
__device__ __forceinline__ void st_relaxed_v4(void* p, uint4 v) {
    asm volatile("st.relaxed.gpu.global.v4.u32 [%0], {%1,%2,%3,%4};" :: "l"(p), "r"(v.x), "r"(v.y), "r"(v.z), "r"(v.w) : "memory");
}
__device__ __forceinline__ uint32_t ld_acquire(const uint32_t* p) { uint32_t v; asm volatile("ld.acquire.gpu.global.u32 %0, [%1];" : "=r"(v) : "l"(p) : "memory"); return v; }
__device__ __forceinline__ uint32_t ld_relaxed(const uint32_t* p) { uint32_t v; asm volatile("ld.relaxed.gpu.global.u32 %0, [%1];" : "=r"(v) : "l"(p) : "memory"); return v; }
__device__ __forceinline__ void st_release(uint32_t* p, uint32_t v) { asm volatile("st.release.gpu.global.u32 [%0], %1;" :: "l"(p), "r"(v) : "memory"); }
__device__ __forceinline__ void cluster_sync_all() {
    asm volatile("barrier.cluster.arrive.release.aligned;" ::: "memory");
    asm volatile("barrier.cluster.wait.acquire.aligned;" ::: "memory");
}

__device__ bf16 g_k[2048 * 4096];
__device__ bf16 g_v[2048 * 4096];
__device__ bf16 g_km[64 * 8 * 4096];
__device__ bf16 g_vm[64 * 8 * 4096];
__device__ uint4 g_gx[2][4][16][80];
__device__ uint32_t g_kvflag[16 * 64];
__device__ uint32_t g_epoch;
struct GState {
    uint32_t done, c_mod_a, c_mod_all, unused0;
    uint32_t pad0[28];
    uint32_t ready[3], lq_claim, exh[4];
    uint32_t pad1[24];
    uint32_t cnt[96 * 8];
    uint32_t f_h[16 * 32];
    uint32_t d_at[16 * 32];
    uint32_t c_at[16 * 32];
    uint32_t c_wo[16 * 32];
    uint32_t f_h2[16 * 32];
    uint32_t c_act[16 * 32];
    uint32_t c_f2[16 * 32];
};
__device__ GState g_st;
namespace gk {
enum { T_MOD, T_L1, T_KV, T_Q, T_AT, T_WO, T_L2, T_F1, T_F2, T_FIN, T_SKIP, T_END };
#define FINE_RB 14
__host__ __device__ __forceinline__ bool fine(int rb) { return rb >= FINE_RB; }
#define WO_FINE 16
#define WO_COARSE 8
__host__ __device__ __forceinline__ int wo_split(int rb) { return fine(rb) ? WO_FINE : WO_COARSE; }
__host__ __device__ __forceinline__ int f2_split(int rb) { return fine(rb) ? 9 : 3; }
__host__ __device__ __forceinline__ int n_nt(int rb) { return fine(rb) ? 5 : 3; }
__host__ __device__ __forceinline__ int n_f1(int rb) { return fine(rb) ? 27 : 14; }
__host__ __device__ __forceinline__ int group_size(int ty, int rb) {
    switch (ty) {
        case T_AT: return 32;
        case T_WO: return n_nt(rb) * wo_split(rb);
        case T_F1: return n_f1(rb);
        case T_F2: return n_nt(rb) * f2_split(rb);
        default: return 16;
    }
}
}
__device__ __forceinline__ uint32_t atom_add_acqrel(uint32_t* p, uint32_t v) {
    uint32_t o; asm volatile("atom.acq_rel.gpu.global.add.u32 %0, [%1], %2;" : "=r"(o) : "l"(p), "r"(v) : "memory"); return o;
}
__device__ __forceinline__ void red_release_inc(uint32_t* p) { asm volatile("red.release.gpu.global.add.u32 [%0], 1;" :: "l"(p) : "memory"); }
__device__ __forceinline__ void publish_group(int ty, int rb, uint32_t) {
    const int gi = (ty - gk::T_AT) * 16 + rb;
    asm volatile("red.release.gpu.global.or.b32 [%0], %1;" :: "l"(&g_st.ready[gi >> 5]), "r"(1u << (gi & 31)) : "memory");
}
#define RT(i)

namespace rk {
constexpr int MEM_STRIDE = 1296;
constexpr int T_STRIDE = 272;
constexpr int OFF_W = 0;
constexpr int OFF_KX = 163840;
constexpr int OFF_VX = OFF_KX + 8192;
constexpr int OFF_MEM = OFF_VX + 8192;
constexpr int OFF_Q = OFF_MEM + 10240;
constexpr int OFF_KM = OFF_Q + 8 * T_STRIDE;
constexpr int OFF_VM = OFF_KM + 8 * T_STRIDE;
constexpr int OFF_O = OFF_VM + 8 * T_STRIDE;
constexpr int OFF_SC = OFF_O + 8 * T_STRIDE;
constexpr int OFF_RED = OFF_SC + 8 * 56 * 4;
constexpr int OFF_RS = OFF_RED + 6144;
constexpr int OFF_ST = OFF_RS + 8 * 80 * 16;
constexpr int OFF_BAR = OFF_ST + 640;
constexpr int OFF_TL = OFF_BAR + 128;
constexpr int SMEM_BYTES = OFF_TL + 512;

__device__ __forceinline__ uint32_t ldg_nc(const void* p) { uint32_t v; asm volatile("ld.global.nc.u32 %0, [%1];" : "=r"(v) : "l"(p)); return v; }
__device__ __forceinline__ void load_raw(uint32_t* a, const bf16* __restrict__ W, int ld, int ka, int kb, int cb, int g, int t) {
    const bf16* p = W + (uint32_t)((ka + 2 * t) * ld + cb + 2 * g);
    const bf16* q = W + (uint32_t)((kb + 2 * t) * ld + cb + 2 * g);
    a[0] = ldg_nc(p); a[1] = ldg_nc(p + ld); a[2] = ldg_nc(q); a[3] = ldg_nc(q + ld);
}
__device__ __forceinline__ void fix_frag(uint32_t* a) {
    const uint32_t w0 = a[0], w1 = a[1], w2 = a[2], w3 = a[3];
    a[0] = __byte_perm(w0, w1, 0x5410); a[1] = __byte_perm(w0, w1, 0x7632);
    a[2] = __byte_perm(w2, w3, 0x5410); a[3] = __byte_perm(w2, w3, 0x7632);
}
__device__ __forceinline__ int chunk_src(int d, int kh, int n) { return (d - 8 * kh - n / 5) & 15; }
__device__ __forceinline__ int chunk_col(int d, int kh, int n) { const int s = chunk_src(d, kh, n); return 320 * (s & 1) + 40 * (s >> 1) + 8 * (n % 5); }
}

#define RSTEP 20
#define TL(i)
#define TG(i)

__device__ __forceinline__ void tma_load_2d(uint32_t dst, const CUtensorMap* map, int c0, int c1, uint32_t bar) {
    asm volatile("cp.async.bulk.tensor.2d.shared::cluster.global.mbarrier::complete_tx::bytes [%0], [%1, {%3, %4}], [%2];"
        :: "r"(dst), "l"(map), "r"(bar), "r"(c0), "r"(c1) : "memory");
}
__device__ __forceinline__ uint32_t movmatrix_t(uint32_t a) { uint32_t d; asm volatile("movmatrix.sync.aligned.m8n8.trans.b16 %0, %1;" : "=r"(d) : "r"(a)); return d; }
__device__ __forceinline__ void stg128(void* p, uint4 v) { asm volatile("st.global.v4.u32 [%0], {%1,%2,%3,%4};" :: "l"(p), "r"(v.x), "r"(v.y), "r"(v.z), "r"(v.w) : "memory"); }

__global__ void __launch_bounds__(256, 1)
r_kernel(const __grid_constant__ CUtensorMap tmK, const __grid_constant__ CUtensorMap tmV, const bf16* __restrict__ mem0, const bf16* __restrict__ Wq, const bf16* __restrict__ Wk, const bf16* __restrict__ Wv, const bf16* __restrict__ Wo, int wait_kv)
{
    using namespace rk;
    extern __shared__ __align__(1024) uint8_t smem[];
    const uint32_t sb = smem_u32(smem);
    const int tid = threadIdx.x, warp = tid >> 5, lane = tid & 31, g = lane >> 2, t = lane & 3;
    uint32_t rank, cid;
    asm volatile("mov.u32 %0, %%cluster_ctarank;" : "=r"(rank));
    asm volatile("mov.u32 %0, %%clusterid.x;" : "=r"(cid));
    const int hh = rank >> 1, j = rank & 1, h = cid * 8 + hh;
    const int kh = warp & 1, mb = warp >> 1;
    const uint32_t b_mem = sb + OFF_BAR, b_qkv = b_mem + 64, b_rs = b_mem + 72, b_kv = b_mem + 80;

    RT(64);
    asm volatile("griddepcontrol.launch_dependents;");
    const uint32_t epoch = ld_relaxed(&g_epoch);

    if (tid == 0) {
        for (int i = 0; i < 8; i++) mbar_init(b_mem + 8 * i, 1);
        mbar_init(b_qkv, 9); mbar_init(b_rs, 1); mbar_init(b_kv, 1);
        asm volatile("fence.mbarrier_init.release.cluster;" ::: "memory");
    }
    const uint32_t wsm = sb + OFF_W + (warp < 4 ? warp * 22528 : 4 * 22528 + (warp - 4) * 18432) + lane * 16;
    {
        const size_t co = (size_t)h * 128 + 64 * j;
        for (int i = tid; i < 640; i += 256) {
            asm volatile("prefetch.global.L2 [%0];" :: "l"(Wv + (size_t)i * 4096 + co));
            asm volatile("prefetch.global.L2 [%0];" :: "l"(Wo + ((size_t)h * 128 + i / 5) * 640 + 320 * j + (i % 5) * 64));
            asm volatile("prefetch.global.L2 [%0];" :: "l"(Wq + (size_t)i * 4096 + co));
            asm volatile("prefetch.global.L2 [%0];" :: "l"(Wk + (size_t)i * 4096 + co));
        }
    }
    uint32_t wq[20][4], wk[20][4];
    {
        const int cb = h * 128 + 64 * j + 16 * mb;
#pragma unroll
        for (int i = 0; i < 20; i++) load_raw(wq[i], Wv, 4096, chunk_col(rank, kh, 2 * i), chunk_col(rank, kh, 2 * i + 1), cb, g, t);
        const bf16* Woh = Wo + (size_t)h * 128 * 640;
        const int c3 = 320 * j + 16 * warp;
#pragma unroll
        for (int i = 0; i < 16; i++) load_raw(wk[i], Woh, 640, (i & 7) * 16, (i & 7) * 16 + 8, c3 + 128 * (i >> 3), g, t);
#pragma unroll
        for (int i = 0; i < 20; i++) { fix_frag(wq[i]); sts128(wsm + i * 512, make_uint4(wq[i][0], wq[i][1], wq[i][2], wq[i][3])); }
        if (warp < 4) {
#pragma unroll
            for (int i = 0; i < 8; i++) load_raw(wq[i], Woh, 640, i * 16, i * 16 + 8, c3 + 256, g, t);
        }
#pragma unroll
        for (int i = 0; i < 16; i++) { fix_frag(wk[i]); sts128(wsm + (20 + i) * 512, make_uint4(wk[i][0], wk[i][1], wk[i][2], wk[i][3])); }
#pragma unroll
        for (int i = 0; i < 20; i++) load_raw(wk[i], Wk, 4096, chunk_col(rank, kh, 2 * i), chunk_col(rank, kh, 2 * i + 1), cb, g, t);
        if (warp < 4) {
#pragma unroll
            for (int i = 0; i < 8; i++) { fix_frag(wq[i]); sts128(wsm + (36 + i) * 512, make_uint4(wq[i][0], wq[i][1], wq[i][2], wq[i][3])); }
        }
#pragma unroll
        for (int i = 0; i < 20; i++) load_raw(wq[i], Wq, 4096, chunk_col(rank, kh, 2 * i), chunk_col(rank, kh, 2 * i + 1), cb, g, t);
#pragma unroll
        for (int i = 0; i < 20; i++) { fix_frag(wk[i]); fix_frag(wq[i]); }
    }
    for (int i = tid; i < 640; i += 256) {
        int row = i / 80, c = i % 80;
        uint4 v = __ldg((const uint4*)(mem0 + row * 640 + c * 8));
        const int jj = c / 40, h5 = (c % 40) / 5;
        sts128(sb + OFF_MEM + (((int)rank - (2 * h5 + jj)) & 15) * 640 + row * 80 + (c % 5) * 16, v);
    }
    auto prefetch_kv = [&](int s) {
        if ((wait_kv & 1) && (s & 3) == 0) {
            const uint32_t* fk = &g_kvflag[(s >> 2) * 64 + h];
            int lim = 0;
            while (ld_acquire(fk) != epoch + 1) { if (++lim > SPIN_LIMIT) break; }
            while (ld_acquire(fk + 32) != epoch + 1) { if (++lim > SPIN_LIMIT) break; }
            asm volatile("fence.proxy.async.global;" ::: "memory");
        }
        mbar_expect_tx(b_kv, 16384);
        tma_load_2d(sb + OFF_KX, &tmK, h * 128, s * 32, b_kv);
        tma_load_2d(sb + OFF_KX + 4096, &tmK, h * 128 + 64, s * 32, b_kv);
        tma_load_2d(sb + OFF_VX, &tmV, h * 128, s * 32, b_kv);
        tma_load_2d(sb + OFF_VX + 4096, &tmV, h * 128 + 64, s * 32, b_kv);
    };
    __syncthreads();
    RT(65);
    __syncthreads();
    cluster_sync_all();

    const float scale = 0.08838834764831845f;
#define LAUNDER() int tid_ = threadIdx.x; asm volatile("" : "+r"(tid_)); const int warp = tid_ >> 5, lane = tid_ & 31, g = lane >> 2, t = lane & 3; (void)g; (void)t; (void)warp;
#define WSM() (sb + OFF_W + (warp < 4 ? warp * 22528 : 4 * 22528 + (warp - 4) * 18432) + lane * 16)

#pragma unroll 1
    for (int s = 0; s < 64; s++) {
        const uint32_t ph = s & 1;
        RT(s);
        {
            LAUNDER();
            TL(0);
            const int kh = warp & 1, mb = warp >> 1;
            const uint32_t wsm = WSM();
            const uint32_t mb0 = sb + OFF_MEM + kh * 5120 + (lane & 7) * 80 + (lane >> 3) * 16;
            const uint32_t mb1 = mb0 + ((lane >> 3) >= 1 ? 560 : 0), mb2 = mb0 + ((lane >> 3) >= 2 ? 560 : 0), mb3 = mb0 + ((lane >> 3) >= 3 ? 560 : 0);
            auto baddr = [&](int it) {
                const int r5 = (4 * it) % 5, c = ((4 * it) / 5) * 640 + r5 * 16;
                return (r5 <= 1 ? mb0 : (r5 == 4 ? mb1 : (r5 == 3 ? mb2 : mb3))) + c;
            };
            uint4 va[6];
            va[0] = lds128(wsm); va[1] = lds128(wsm + 512); va[2] = lds128(wsm + 1024); va[3] = lds128(wsm + 1536);
            if (s > 0) { mbar_wait(b_mem, ph ^ 1); mbar_wait(b_mem + 8, ph ^ 1); }
            TL(1); TG(15);
            float aq0[4] = {0, 0, 0, 0}, aq1[4] = {0, 0, 0, 0}, ak0[4] = {0, 0, 0, 0}, ak1[4] = {0, 0, 0, 0}, av0[4] = {0, 0, 0, 0}, av1[4] = {0, 0, 0, 0};
            uint32_t b[3][4];
            ldsm_x4(b[0], baddr(0)); ldsm_x4(b[1], baddr(1));
            if (tid_ == 0) {
                mbar_expect_tx(b_qkv, 3072);
                if (s < 63) mbar_expect_tx(b_rs, 10240);
            }
#pragma unroll
            for (int i = 0; i < 10; i++) {
                if (i + 2 < 10) {
                    const int it = i + 2, sl = (4 * it + 3) / 5, slp = (4 * (it - 1) + 3) / 5;
                    if (sl != slp && s > 0) mbar_wait(b_mem + 8 * sl, ph ^ 1);
                    ldsm_x4(b[(i + 2) % 3], baddr(i + 2));
                    va[(2 * i + 4) % 6] = lds128(wsm + (2 * i + 4) * 512); va[(2 * i + 5) % 6] = lds128(wsm + (2 * i + 5) * 512);
                }
                const uint32_t* bb = b[i % 3];
                mma16816(aq0, wq[2 * i], bb[0], bb[1]); mma16816(ak0, wk[2 * i], bb[0], bb[1]); mma16816(av0, (uint32_t*)&va[(2 * i) % 6], bb[0], bb[1]);
                mma16816(aq1, wq[2 * i + 1], bb[2], bb[3]); mma16816(ak1, wk[2 * i + 1], bb[2], bb[3]); mma16816(av1, (uint32_t*)&va[(2 * i + 1) % 6], bb[2], bb[3]);
            }
            float snd[4], fin[4];
#pragma unroll
            for (int i = 0; i < 4; i++) { float q = aq0[i] + aq1[i], k = ak0[i] + ak1[i]; snd[i] = kh ? q : k; fin[i] = kh ? k : q; av0[i] += av1[i]; }
            sts128(sb + OFF_RED + tid_ * 16, make_uint4(__float_as_uint(snd[0]), __float_as_uint(snd[1]), __float_as_uint(snd[2]), __float_as_uint(snd[3])));
            sts64(sb + OFF_RED + 4096 + tid_ * 8, __float_as_uint(kh ? av0[0] : av0[1]), __float_as_uint(kh ? av0[2] : av0[3]));
            bar_sync(1 + mb, 64);
            uint4 r = lds128(sb + OFF_RED + (tid_ ^ 32) * 16);
            uint2 r2 = lds64(sb + OFF_RED + 4096 + (tid_ ^ 32) * 8);
            fin[0] += __uint_as_float(r.x); fin[1] += __uint_as_float(r.y); fin[2] += __uint_as_float(r.z); fin[3] += __uint_as_float(r.w);
            float f0 = (kh ? av0[1] : av0[0]) + __uint_as_float(r2.x), f1 = (kh ? av0[3] : av0[2]) + __uint_as_float(r2.y);
            TL(2);
            const uint32_t cofs = (64 * j + 16 * mb) * 2;
            const uint32_t buf = sb + (kh ? OFF_KM : OFF_Q) + cofs;
            sts32(buf + (2 * t) * T_STRIDE + g * 4, pack_bf16(fin[0], fin[2]));
            sts32(buf + (2 * t + 1) * T_STRIDE + g * 4, pack_bf16(fin[1], fin[3]));
            sts32(sb + OFF_VM + cofs + (2 * t + kh) * T_STRIDE + g * 4, pack_bf16(f0, f1));
            __syncwarp();
            if (lane < 24) {
                const uint32_t peer_off = mapa_u32(sb, rank ^ 1) - sb;
                const int row = lane < 16 ? (lane >> 1) : 2 * ((lane - 16) >> 1) + kh;
                const uint32_t a = (lane < 16 ? buf : sb + OFF_VM + cofs) + row * T_STRIDE + (lane & 1) * 16;
                uint4 v = lds128(a);
                st_async_v4(a + peer_off, v.x, v.y, v.z, v.w, b_qkv + peer_off);
                if ((kh || lane >= 16) && !(wait_kv & 8)) {
                    bf16* dst = (lane < 16 ? g_km : g_vm) + ((uint32_t)(s * 8 + row) * 4096u + h * 128 + 64 * j + 16 * mb + (lane & 1) * 8);
                    stg128(dst, v);
                }
            }
            if (lane == 0) mbar_arrive(b_qkv);
            if (s == 0 && tid_ == 224) prefetch_kv(0);
            TL(3);
        }
        if (s == 63) {
            __syncthreads();
            if (threadIdx.x == 0 && (wait_kv & 1)) red_release_inc(&g_st.d_at[15 * 32]);
            break;
        }
        uint4 wa[8];
        {
            LAUNDER();
            const uint32_t wsm = WSM();
            if (!(wait_kv & 2) || s == 0) mbar_wait(b_kv, ph);
            if (warp >= 4 && warp < 7) {
                const int kw = warp - 4;
                uint32_t ka[8][4];
                if (kw < 2) {
                    const uint32_t kaddr = sb + OFF_KX + (16 * kw + (lane & 15)) * 128;
#pragma unroll
                    for (int i = 0; i < 8; i++) ldsm_x4(ka[i], kaddr + (i >> 2) * 4096 + ((((2 * i + (lane >> 4)) & 7) ^ (lane & 7)) << 4));
                    mbar_wait(b_qkv, ph);
                } else {
                    mbar_wait(b_qkv, ph);
                    const uint32_t kaddr = sb + OFF_KM + (lane & 7) * T_STRIDE + (lane >> 4) * 16;
#pragma unroll
                    for (int i = 0; i < 8; i++) ldsm_x4(ka[i], kaddr + i * 32);
                }
                TL(5);
                const uint32_t qa = sb + OFF_Q + (lane & 7) * T_STRIDE + (lane >> 3) * 16;
                uint32_t qb[4][4];
#pragma unroll
                for (int i = 0; i < 4; i++) ldsm_x4(qb[i], qa + i * 64);
                float s0[4] = {0, 0, 0, 0}, s1[4] = {0, 0, 0, 0}, s2[4] = {0, 0, 0, 0}, s3[4] = {0, 0, 0, 0};
                mma16816(s0, ka[0], qb[0][0], qb[0][1]); mma16816(s1, ka[1], qb[0][2], qb[0][3]);
                mma16816(s2, ka[2], qb[1][0], qb[1][1]); mma16816(s3, ka[3], qb[1][2], qb[1][3]);
                mma16816(s0, ka[4], qb[2][0], qb[2][1]); mma16816(s1, ka[5], qb[2][2], qb[2][3]);
                mma16816(s2, ka[6], qb[3][0], qb[3][1]); mma16816(s3, ka[7], qb[3][2], qb[3][3]);
                const uint32_t sc = sb + OFF_SC + (16 * kw + g) * 4 + (2 * t) * 224;
                sts32(sc, __float_as_uint(bf16r(bf16r((s0[0] + s1[0]) + (s2[0] + s3[0])) * scale)));
                sts32(sc + 224, __float_as_uint(bf16r(bf16r((s0[1] + s1[1]) + (s2[1] + s3[1])) * scale)));
                if (kw < 2) {
                    sts32(sc + 32, __float_as_uint(bf16r(bf16r((s0[2] + s1[2]) + (s2[2] + s3[2])) * scale)));
                    sts32(sc + 32 + 224, __float_as_uint(bf16r(bf16r((s0[3] + s1[3]) + (s2[3] + s3[3])) * scale)));
                }
                asm volatile("bar.arrive 6, 224;" ::: "memory");
                TL(4);
#pragma unroll
                for (int i = 0; i < 8; i++) wa[i] = lds128(wsm + (20 + i) * 512);
            } else {
#pragma unroll
                for (int i = 0; i < 8; i++) wa[i] = lds128(wsm + (20 + i) * 512);
                if (warp < 4) {
                    mbar_wait(b_qkv, ph);
                    uint32_t a0[2][4], a1[2][4], a2[2][4];
#pragma unroll
                    for (int u = 0; u < 2; u++) {
                        const int et = warp + 4 * u;
                        const uint32_t vx = sb + OFF_VX + u * 4096 + ((lane >> 4) * 8 + (lane & 7)) * 128 + ((((2 * warp + ((lane >> 3) & 1)) & 7) ^ (lane & 7)) << 4);
                        ldsm_x4_t(a0[u], vx); ldsm_x4_t(a1[u], vx + 16 * 128);
                        ldsm_x4_t(a2[u], sb + OFF_VM + (lane & 7) * T_STRIDE + (16 * et + ((lane >> 3) & 1) * 8) * 2);
                    }
                    bar_sync(6, 224);
                    TL(6);
                    float x[10];
#pragma unroll
                    for (int i = 0; i < 5; i++) { uint2 v = lds64(sb + OFF_SC + g * 224 + (8 * i + 2 * t) * 4); x[2 * i] = __uint_as_float(v.x); x[2 * i + 1] = __uint_as_float(v.y); }
                    float m = fmaxf(fmaxf(fmaxf(x[0], x[1]), fmaxf(x[2], x[3])), fmaxf(fmaxf(x[4], x[5]), fmaxf(x[6], x[7])));
                    m = fmaxf(m, fmaxf(x[8], x[9]));
                    m = fmaxf(m, __shfl_xor_sync(0xffffffff, m, 1)); m = fmaxf(m, __shfl_xor_sync(0xffffffff, m, 2));
                    float sum0 = 0, sum1 = 0;
#pragma unroll
                    for (int i = 0; i < 5; i++) { x[2 * i] = __expf(x[2 * i] - m); sum0 += x[2 * i]; x[2 * i + 1] = __expf(x[2 * i + 1] - m); sum1 += x[2 * i + 1]; }
                    float sum = sum0 + sum1;
                    sum += __shfl_xor_sync(0xffffffff, sum, 1); sum += __shfl_xor_sync(0xffffffff, sum, 2);
                    float inv = __fdividef(1.0f, sum);
                    if (inv == 123.f) TL(14);
                    TL(4);
                    uint32_t pb[5];
#pragma unroll
                    for (int i = 0; i < 5; i++) pb[i] = pack_bf16(x[2 * i] * inv, x[2 * i + 1] * inv);
#pragma unroll
                    for (int u = 0; u < 2; u++) {
                        float o0[4] = {0, 0, 0, 0}, o1[4] = {0, 0, 0, 0}, o2[4] = {0, 0, 0, 0};
                        mma16816(o0, a0[u], pb[0], pb[1]); mma16816(o1, a1[u], pb[2], pb[3]); mma16816(o2, a2[u], pb[4], 0u);
                        const uint32_t lo = movmatrix_t(pack_bf16((o0[0] + o1[0]) + o2[0], (o0[1] + o1[1]) + o2[1]));
                        const uint32_t hi = movmatrix_t(pack_bf16((o0[2] + o1[2]) + o2[2], (o0[3] + o1[3]) + o2[3]));
                        const uint32_t oa = sb + OFF_O + g * T_STRIDE + (16 * (warp + 4 * u) + 2 * t) * 2;
                        sts32(oa, lo); sts32(oa + 16, hi);
                    }
                    TL(5);
                } else {
                    if (lane < 8) mbar_expect_tx(b_mem + 8 * lane, 1280);
                }
            }
        }
        __syncthreads();
        {
            LAUNDER();
            TL(7);
            const uint32_t wsm = WSM();
            uint32_t ob[16];
            const uint32_t oa = sb + OFF_O + (lane & 7) * T_STRIDE + (lane >> 3) * 16;
#pragma unroll
            for (int i = 0; i < 4; i++) ldsm_x4(ob + 4 * i, oa + i * 64);
            const uint32_t rs_base = OFF_RS + hh * 1280 + t * 16;
            const int ntile = warp < 4 ? 3 : 2;
#pragma unroll 1
            for (int tl = 0; tl < ntile; tl++) {
                float d0[4] = {0, 0, 0, 0}, d1[4] = {0, 0, 0, 0}, d2[4] = {0, 0, 0, 0}, d3[4] = {0, 0, 0, 0};
                const bool more = tl + 1 < ntile;
                const uint32_t nx = wsm + (28 + 8 * tl) * 512;
                mma16816(d0, (uint32_t*)&wa[0], ob[0], ob[1]);   if (more) wa[0] = lds128(nx);
                mma16816(d1, (uint32_t*)&wa[1], ob[2], ob[3]);   if (more) wa[1] = lds128(nx + 512);
                mma16816(d2, (uint32_t*)&wa[2], ob[4], ob[5]);   if (more) wa[2] = lds128(nx + 1024);
                mma16816(d3, (uint32_t*)&wa[3], ob[6], ob[7]);   if (more) wa[3] = lds128(nx + 1536);
                mma16816(d0, (uint32_t*)&wa[4], ob[8], ob[9]);   if (more) wa[4] = lds128(nx + 2048);
                mma16816(d1, (uint32_t*)&wa[5], ob[10], ob[11]); if (more) wa[5] = lds128(nx + 2560);
                mma16816(d2, (uint32_t*)&wa[6], ob[12], ob[13]); if (more) wa[6] = lds128(nx + 3072);
                mma16816(d3, (uint32_t*)&wa[7], ob[14], ob[15]); if (more) wa[7] = lds128(nx + 3584);
                const int col = 16 * (warp + 8 * tl) + 2 * g; const int own = col / 40; const int cp = (col - own * 40) >> 1;
                const uint32_t dbase = mapa_u32(sb, 2 * own + j);
                st_async_v4(dbase + rs_base + cp * 64, __float_as_uint((d0[0] + d1[0]) + (d2[0] + d3[0])), __float_as_uint((d0[1] + d1[1]) + (d2[1] + d3[1])),
                            __float_as_uint((d0[2] + d1[2]) + (d2[2] + d3[2])), __float_as_uint((d0[3] + d1[3]) + (d2[3] + d3[3])), dbase + OFF_BAR + 72);
            }
            TL(8);
        }
        {
            LAUNDER();
            if (warp >= 5) {
                const int x = tid_ - 160;
                const int ot = x < 80 ? x : 79;
                const uint32_t gs = epoch * 64 + s; const uint32_t tag = (gs + 1) & 15u; const int slot = gs & 1;
                uint4* gp = &g_gx[slot][0][rank][ot];
                mbar_wait(b_rs, ph);
                TL(9); TG(12);
                uint4 u[8];
#pragma unroll
                for (int q = 0; q < 8; q++) u[q] = lds128(sb + OFF_RS + q * 1280 + ot * 16);
                float4 a;
                a.x = ((__uint_as_float(u[0].x) + __uint_as_float(u[1].x)) + (__uint_as_float(u[2].x) + __uint_as_float(u[3].x))) + ((__uint_as_float(u[4].x) + __uint_as_float(u[5].x)) + (__uint_as_float(u[6].x) + __uint_as_float(u[7].x)));
                a.y = ((__uint_as_float(u[0].y) + __uint_as_float(u[1].y)) + (__uint_as_float(u[2].y) + __uint_as_float(u[3].y))) + ((__uint_as_float(u[4].y) + __uint_as_float(u[5].y)) + (__uint_as_float(u[6].y) + __uint_as_float(u[7].y)));
                a.z = ((__uint_as_float(u[0].z) + __uint_as_float(u[1].z)) + (__uint_as_float(u[2].z) + __uint_as_float(u[3].z))) + ((__uint_as_float(u[4].z) + __uint_as_float(u[5].z)) + (__uint_as_float(u[6].z) + __uint_as_float(u[7].z)));
                a.w = ((__uint_as_float(u[0].w) + __uint_as_float(u[1].w)) + (__uint_as_float(u[2].w) + __uint_as_float(u[3].w))) + ((__uint_as_float(u[4].w) + __uint_as_float(u[5].w)) + (__uint_as_float(u[6].w) + __uint_as_float(u[7].w)));
                uint4 mine = make_uint4((__float_as_uint(a.x) & ~15u) | tag, (__float_as_uint(a.y) & ~15u) | tag, (__float_as_uint(a.z) & ~15u) | tag, (__float_as_uint(a.w) & ~15u) | tag);
                if (x < 80) st_relaxed_v4(gp + cid * 1280, mine);
                uint4 v[3];
                const uint4* rp0 = gp + (cid ^ 1) * 1280; const uint4* rp1 = gp + (cid ^ 2) * 1280; const uint4* rp2 = gp + (cid ^ 3) * 1280;
                int lim = 0;
                while (true) {
                    v[0] = ld_relaxed_v4(rp0); v[1] = ld_relaxed_v4(rp1); v[2] = ld_relaxed_v4(rp2);
                    uint32_t bad = 0;
#pragma unroll
                    for (int c = 0; c < 3; c++) bad |= (v[c].x ^ tag) | (v[c].y ^ tag) | (v[c].z ^ tag) | (v[c].w ^ tag);
                    if ((bad & 15u) == 0) break;
                    if (++lim > SPIN_LIMIT) break;
                }
                float f0 = (__uint_as_float(mine.x) + __uint_as_float(v[0].x)) + (__uint_as_float(v[1].x) + __uint_as_float(v[2].x));
                float f1 = (__uint_as_float(mine.y) + __uint_as_float(v[0].y)) + (__uint_as_float(v[1].y) + __uint_as_float(v[2].y));
                float f2 = (__uint_as_float(mine.z) + __uint_as_float(v[0].z)) + (__uint_as_float(v[1].z) + __uint_as_float(v[2].z));
                float f3 = (__uint_as_float(mine.w) + __uint_as_float(v[0].w)) + (__uint_as_float(v[1].w) + __uint_as_float(v[2].w));
                const int cp = ot >> 2, tt = ot & 3;
                sts32(sb + OFF_ST + (2 * tt) * 80 + cp * 4, pack_bf16(f0, f2));
                sts32(sb + OFF_ST + (2 * tt + 1) * 80 + cp * 4, pack_bf16(f1, f3));
                TL(10); TG(13);
                bar_sync(5, 128);
                if (x < 80) {
                    const int c = x % 40, d0 = x / 40;
                    uint4 w = lds128(sb + OFF_ST + c * 16);
                    const uint32_t off = OFF_MEM + d0 * 5120 + c * 16;
#pragma unroll
                    for (int i = 0; i < 8; i++) {
                        const uint32_t rb = mapa_u32(sb, (d0 * 8 + i + rank) & 15);
                        st_async_v4(rb + off + i * 640, w.x, w.y, w.z, w.w, rb + OFF_BAR + 8 * i);
                    }
                }
            } else if (warp == 4) {
                if (lane == 0 && (s & 3) == 3 && (wait_kv & 1)) red_release_inc(&g_st.d_at[(s >> 2) * 32]);
                __syncwarp();
            } else if (warp == 3) {
                bar_sync(5, 128);
                if (lane == 0 && s < 62 && !(wait_kv & 2)) prefetch_kv(s + 1);
                __syncwarp();
            }
            TL(11);
        }
    }
    cluster_sync_all();
}

__device__ float g_mod[3840];
__device__ bf16 g_h[2048 * 640];
__device__ bf16 g_q[2048 * 4096];
__device__ bf16 g_o[2048 * 4096];
__device__ bf16 g_x1[2048 * 640];
__device__ bf16 g_h2[2048 * 640];
__device__ bf16 g_act[2048 * 1728];
__device__ float g_slab[2048 * 640];

namespace gk {
constexpr int STAGES = 4;
constexpr int STAGE_BYTES = 49152;
constexpr int OFF_SCR = STAGES * STAGE_BYTES;
constexpr int OFF_BAR = OFF_SCR + 32768;
constexpr int SMEM_BYTES = OFF_BAR + 256 + 2048;
#define LOW_LEAD 3
constexpr int N_MOD = 60, N_L1 = 256, N_KV = 32, N_Q = 16;
constexpr int I_L1 = N_MOD, I_W = I_L1 + N_L1;
constexpr int N_LOW = I_W + 16 * (N_KV + N_Q);
constexpr int NFINE = 16 - FINE_RB;
constexpr int N_HIGH = 16 * (32 + 16 + 16) + (16 - NFINE) * (3 * WO_COARSE + 14 + 9) + NFINE * (5 * WO_FINE + 27 + 45);
struct Item { int type, rb, nt, ks; };
__host__ __device__ inline Item decode_low(int t) {
    Item it; it.rb = 0; it.nt = 0; it.ks = 0;
    if (t < I_L1) { it.type = T_MOD; it.nt = t; return it; }
    if (t < I_W) { it.type = T_L1; it.rb = (t - I_L1) >> 4; it.nt = (t - I_L1) & 15; return it; }
    t -= I_W;
    if (t < 64) { it.type = T_KV; it.rb = t >> 5; it.nt = t & 31; return it; }
    t -= 64;
    if (t < 14 * 48) { const int w = t / 48; t -= w * 48; if (t < 16) { it.type = T_Q; it.rb = w; it.nt = t; } else { it.type = T_KV; it.rb = w + 2; it.nt = t - 16; } return it; }
    t -= 14 * 48;
    it.type = T_Q; it.rb = 14 + (t >> 4); it.nt = t & 15; return it;
}
__device__ __forceinline__ bool is_wide(const Item& it) {
    if (it.type == T_KV || it.type == T_Q) return true;
    if (it.type == T_F1) return !fine(it.rb);
    if (it.type == T_WO || it.type == T_F2) return !fine(it.rb) && it.nt < 2;
    return false;
}
__device__ __forceinline__ int red_col(const Item& it) { return fine(it.rb) ? it.nt * 128 : it.nt * 256; }
__device__ __forceinline__ int pack_item(const Item& it) { return it.type | (it.rb << 4) | (it.nt << 8) | (it.ks << 16); }
__device__ __forceinline__ Item unpack_item(int v) { Item it; it.type = v & 15; it.rb = (v >> 4) & 15; it.nt = (v >> 8) & 255; it.ks = (v >> 16) & 255; return it; }
}

struct GParams {
    CUtensorMap tA_h, tA_o, tA_h2, tA_act, tB_q, tB_k, tB_v, tB_o, tB_g, tB_u, tB_d, tS_q, tS_k, tS_v, tS_act, tS_o, tL_q, tL_k, tL_v, tL_km, tL_vm, tR_acc;
};

__device__ __forceinline__ void wait_ge(const uint32_t* p, uint32_t target) {
    int lim = 0;
    while ((int32_t)(ld_acquire(p) - target) < 0) { __nanosleep(64); if (++lim > SPIN_LIMIT) break; }
}
__device__ __forceinline__ void red_add_relaxed(uint32_t* p, uint32_t v) { asm volatile("red.relaxed.gpu.global.add.u32 [%0], %1;" :: "l"(p), "r"(v) : "memory"); }
__device__ __forceinline__ void st_relaxed_u32(uint32_t* p, uint32_t v) { asm volatile("st.relaxed.gpu.global.u32 [%0], %1;" :: "l"(p), "r"(v) : "memory"); }
__device__ __forceinline__ void red_add_release(uint32_t* p, uint32_t v) { asm volatile("red.release.gpu.global.add.u32 [%0], %1;" :: "l"(p), "r"(v) : "memory"); }

__device__ __forceinline__ void wgmma_fence() { asm volatile("wgmma.fence.sync.aligned;" ::: "memory"); }
__device__ __forceinline__ void wgmma_commit() { asm volatile("wgmma.commit_group.sync.aligned;" ::: "memory"); }
template<int N> __device__ __forceinline__ void wgmma_wait() { asm volatile("wgmma.wait_group.sync.aligned %0;" :: "n"(N) : "memory"); }

template<int N> __device__ __forceinline__ void fence_acc(float* d) {
#pragma unroll
    for (int i = 0; i < N; i++) asm volatile("" : "+f"(d[i]) :: "memory");
}
#define ACC8(b) "+f"(d[b]), "+f"(d[b+1]), "+f"(d[b+2]), "+f"(d[b+3]), "+f"(d[b+4]), "+f"(d[b+5]), "+f"(d[b+6]), "+f"(d[b+7])
#define ACC32(b) ACC8(b), ACC8(b+8), ACC8(b+16), ACC8(b+24)
__device__ __forceinline__ void wgmma_n128(float* d, uint64_t da, uint64_t db, int scale_d) {
    asm volatile("{ .reg .pred p; setp.ne.b32 p, %66, 0;\n"
        "wgmma.mma_async.sync.aligned.m64n128k16.f32.bf16.bf16 {%0,%1,%2,%3,%4,%5,%6,%7,%8,%9,%10,%11,%12,%13,%14,%15,%16,%17,%18,%19,%20,%21,%22,%23,%24,%25,%26,%27,%28,%29,%30,%31,"
        "%32,%33,%34,%35,%36,%37,%38,%39,%40,%41,%42,%43,%44,%45,%46,%47,%48,%49,%50,%51,%52,%53,%54,%55,%56,%57,%58,%59,%60,%61,%62,%63}, %64, %65, p, 1, 1, 0, 1; }"
        : ACC32(0), ACC32(32) : "l"(da), "l"(db), "r"(scale_d));
}
__device__ __forceinline__ void wgmma_n256(float* d, uint64_t da, uint64_t db, int scale_d) {
    asm volatile("{ .reg .pred p; setp.ne.b32 p, %130, 0;\n"
        "wgmma.mma_async.sync.aligned.m64n256k16.f32.bf16.bf16 {%0,%1,%2,%3,%4,%5,%6,%7,%8,%9,%10,%11,%12,%13,%14,%15,%16,%17,%18,%19,%20,%21,%22,%23,%24,%25,%26,%27,%28,%29,%30,%31,"
        "%32,%33,%34,%35,%36,%37,%38,%39,%40,%41,%42,%43,%44,%45,%46,%47,%48,%49,%50,%51,%52,%53,%54,%55,%56,%57,%58,%59,%60,%61,%62,%63,"
        "%64,%65,%66,%67,%68,%69,%70,%71,%72,%73,%74,%75,%76,%77,%78,%79,%80,%81,%82,%83,%84,%85,%86,%87,%88,%89,%90,%91,%92,%93,%94,%95,"
        "%96,%97,%98,%99,%100,%101,%102,%103,%104,%105,%106,%107,%108,%109,%110,%111,%112,%113,%114,%115,%116,%117,%118,%119,%120,%121,%122,%123,%124,%125,%126,%127}, %128, %129, p, 1, 1, 0, 1; }"
        : ACC32(0), ACC32(32), ACC32(64), ACC32(96) : "l"(da), "l"(db), "r"(scale_d));
}
__device__ __forceinline__ uint64_t make_desc(uint32_t addr, uint32_t lbo, uint32_t sbo) {
    return (uint64_t)((addr & 0x3FFFF) >> 4) | ((uint64_t)(lbo >> 4) << 16) | ((uint64_t)(sbo >> 4) << 32) | ((uint64_t)1 << 62);
}

__device__ __forceinline__ float div_fix(float a, float b, float rb) { float q = a * rb; float r = fmaf(-q, b, a); return fmaf(r, rb, q); }
__device__ __forceinline__ void row_item(int mode, uint32_t sx, uint32_t sa, uint32_t sp, uint32_t bar_empty, float* __restrict__ acc, bf16* __restrict__ yout, bf16* __restrict__ out, int lane) {
    float x[20];
#pragma unroll
    for (int i = 0; i < 5; i++) {
        const uint2 v = lds64(sx + i * 256 + lane * 8);
        x[4 * i] = __uint_as_float(v.x << 16); x[4 * i + 1] = __uint_as_float(v.x & 0xffff0000u);
        x[4 * i + 2] = __uint_as_float(v.y << 16); x[4 * i + 3] = __uint_as_float(v.y & 0xffff0000u);
    }
    if (mode) {
#pragma unroll
        for (int i = 0; i < 5; i++) {
            const uint4 a = lds128(sa + i * 512 + lane * 16), gt = lds128(sp + i * 512 + lane * 16);
            x[4 * i] = bf16r(x[4 * i] + bf16r(__uint_as_float(gt.x) * bf16r(__uint_as_float(a.x)))); x[4 * i + 1] = bf16r(x[4 * i + 1] + bf16r(__uint_as_float(gt.y) * bf16r(__uint_as_float(a.y))));
            x[4 * i + 2] = bf16r(x[4 * i + 2] + bf16r(__uint_as_float(gt.z) * bf16r(__uint_as_float(a.z)))); x[4 * i + 3] = bf16r(x[4 * i + 3] + bf16r(__uint_as_float(gt.w) * bf16r(__uint_as_float(a.w))));
            *(uint2*)(yout + i * 128 + lane * 4) = make_uint2(pack_bf16(x[4 * i], x[4 * i + 1]), pack_bf16(x[4 * i + 2], x[4 * i + 3]));
            *(float4*)(acc + i * 128 + lane * 4) = make_float4(0.f, 0.f, 0.f, 0.f);
        }
        sp += 2560;
    }
    if (mode != 2) {
        float s = 0;
#pragma unroll
        for (int i = 0; i < 20; i++) s += x[i];
#pragma unroll
        for (int o = 16; o; o >>= 1) s += __shfl_xor_sync(0xffffffff, s, o);
        const float mean = s * (1.0f / 640.0f);
        float q = 0;
#pragma unroll
        for (int i = 0; i < 20; i++) { float d = x[i] - mean; q += d * d; }
#pragma unroll
        for (int o = 16; o; o >>= 1) q += __shfl_xor_sync(0xffffffff, q, o);
        const float m16 = bf16r(mean);
        const float sd = bf16r(sqrtf(bf16r(bf16r(q * (1.0f / 640.0f)) + 1e-5f)));
        const float rs = __frcp_rn(sd);
#pragma unroll
        for (int i = 0; i < 5; i++) {
            const uint4 sh = lds128(sp + i * 512 + lane * 16), sc = lds128(sp + 2560 + i * 512 + lane * 16);
            float y0 = bf16r(bf16r(div_fix(bf16r(x[4 * i] - m16), sd, rs)) * bf16r(1.0f + __uint_as_float(sc.x))) + __uint_as_float(sh.x);
            float y1 = bf16r(bf16r(div_fix(bf16r(x[4 * i + 1] - m16), sd, rs)) * bf16r(1.0f + __uint_as_float(sc.y))) + __uint_as_float(sh.y);
            float y2 = bf16r(bf16r(div_fix(bf16r(x[4 * i + 2] - m16), sd, rs)) * bf16r(1.0f + __uint_as_float(sc.z))) + __uint_as_float(sh.z);
            float y3 = bf16r(bf16r(div_fix(bf16r(x[4 * i + 3] - m16), sd, rs)) * bf16r(1.0f + __uint_as_float(sc.w))) + __uint_as_float(sh.w);
            *(uint2*)(out + i * 128 + lane * 4) = make_uint2(pack_bf16(y0, y1), pack_bf16(y2, y3));
        }
    }
    __syncwarp();
    if (lane == 0) mbar_arrive(bar_empty);
}

__device__ __forceinline__ float gelu_tanh(float x) {
    float u2 = x * fmaf(x * x, 2.0f * 0.7978845608028654f * 0.044715f * 1.4426950408889634f, 2.0f * 0.7978845608028654f * 1.4426950408889634f);
    float e; asm("ex2.approx.ftz.f32 %0, %1;" : "=f"(e) : "f"(-u2));
    return __fdividef(x, 1.0f + e);
}
__device__ __forceinline__ uint4 ldg128(const void* p) { uint4 v; asm volatile("ld.global.v4.u32 {%0,%1,%2,%3}, [%4];" : "=r"(v.x), "=r"(v.y), "=r"(v.z), "=r"(v.w) : "l"(p) : "memory"); return v; }
__device__ __forceinline__ float4 ldcg_f4(const float* p) { float4 v; asm volatile("ld.global.cg.v4.f32 {%0,%1,%2,%3}, [%4];" : "=f"(v.x), "=f"(v.y), "=f"(v.z), "=f"(v.w) : "l"(p) : "memory"); return v; }
__device__ __forceinline__ uint4 ldcg128(const void* p) { uint4 v; asm volatile("ld.global.cg.v4.u32 {%0,%1,%2,%3}, [%4];" : "=r"(v.x), "=r"(v.y), "=r"(v.z), "=r"(v.w) : "l"(p) : "memory"); return v; }

__device__ __forceinline__ void attn_scores(uint32_t sq, uint32_t sk, uint32_t skm, int sg, int mt, int lane, uint32_t (&p)[6][2]) {
    const int g = lane >> 2, t = lane & 3, l7 = lane & 7;
    float s[5][4];
#pragma unroll
    for (int kt = 0; kt < 5; kt++) s[kt][0] = s[kt][1] = s[kt][2] = s[kt][3] = 0.f;
    const uint32_t qrow = sq + (sg * 32 + mt * 16 + (lane & 15)) * 128;
    const uint32_t krow = sk + (sg * 32 + l7) * 128, kmrow = skm + (sg * 8 + l7) * 128;
#pragma unroll
    for (int c = 0; c < 4; c++) {
        uint32_t a0[4], a1[4];
        ldsm_x4(a0, qrow + (c >> 1) * 16384 + ((((4 * c + (lane >> 4)) & 7) ^ l7) << 4));
        ldsm_x4(a1, qrow + (c >> 1) * 16384 + ((((4 * c + 2 + (lane >> 4)) & 7) ^ l7) << 4));
        const uint32_t sw = (((4 * c + (lane >> 3)) & 7) ^ l7) << 4;
#pragma unroll
        for (int kt = 0; kt < 5; kt++) {
            uint32_t b[4];
            ldsm_x4(b, kt == 0 ? kmrow + (c >> 1) * 4096 + sw : krow + (kt - 1) * 1024 + (c >> 1) * 16384 + sw);
            mma16816(s[kt], a0, b[0], b[1]); mma16816(s[kt], a1, b[2], b[3]);
        }
    }
    const float scale = 0.08838834764831845f;
    const int r0 = mt * 16 + g, r1 = r0 + 8;
    float m0 = -INFINITY, m1 = -INFINITY;
#pragma unroll
    for (int kt = 0; kt < 5; kt++) {
#pragma unroll
        for (int i = 0; i < 4; i++) {
            float v = bf16r(bf16r(s[kt][i]) * scale);
            if (kt > 0) { int key = (kt - 1) * 8 + 2 * t + (i & 1); if (key > (i < 2 ? r0 : r1)) v = -1.0e9f; }
            s[kt][i] = v;
            if (i < 2) m0 = fmaxf(m0, v); else m1 = fmaxf(m1, v);
        }
    }
    m0 = fmaxf(m0, __shfl_xor_sync(0xffffffff, m0, 1)); m0 = fmaxf(m0, __shfl_xor_sync(0xffffffff, m0, 2));
    m1 = fmaxf(m1, __shfl_xor_sync(0xffffffff, m1, 1)); m1 = fmaxf(m1, __shfl_xor_sync(0xffffffff, m1, 2));
    float l0 = 0, l1 = 0;
#pragma unroll
    for (int kt = 0; kt < 5; kt++) {
        s[kt][0] = __expf(s[kt][0] - m0); s[kt][1] = __expf(s[kt][1] - m0); l0 += s[kt][0] + s[kt][1];
        s[kt][2] = __expf(s[kt][2] - m1); s[kt][3] = __expf(s[kt][3] - m1); l1 += s[kt][2] + s[kt][3];
    }
    l0 += __shfl_xor_sync(0xffffffff, l0, 1); l0 += __shfl_xor_sync(0xffffffff, l0, 2);
    l1 += __shfl_xor_sync(0xffffffff, l1, 1); l1 += __shfl_xor_sync(0xffffffff, l1, 2);
    const float i0 = __fdividef(1.0f, l0), i1 = __fdividef(1.0f, l1);
#pragma unroll
    for (int kt = 0; kt < 5; kt++) { p[kt][0] = pack_bf16(s[kt][0] * i0, s[kt][1] * i0); p[kt][1] = pack_bf16(s[kt][2] * i1, s[kt][3] * i1); }
    p[5][0] = p[5][1] = 0;
}
__device__ __forceinline__ void attn_pv(uint32_t sv, uint32_t svm, int sg, int lane, const uint32_t (&p)[6][2], float* d) {
    const int l7 = lane & 7, hi = (lane >> 3) & 1, ec = lane >> 4;
    const uint32_t r0 = hi ? sv + (sg * 32 + l7) * 128 : svm + (sg * 8 + l7) * 128;
    const uint32_t sub0 = hi ? 16384 : 4096;
    const uint32_t r1 = sv + (sg * 32 + 8 + hi * 8 + l7) * 128;
    const uint32_t r2 = sv + (sg * 32 + 24 + l7) * 128;
#pragma unroll
    for (int i = 0; i < 8; i++) {
        const uint32_t sw = (((2 * i + ec) & 7) ^ l7) << 4;
        uint32_t b0[4], b1[4], b2[4];
        ldsm_x4_t(b0, r0 + (i >> 2) * sub0 + sw); ldsm_x4_t(b1, r1 + (i >> 2) * 16384 + sw); ldsm_x4_t(b2, r2 + (i >> 2) * 16384 + sw);
        float* o0 = d + 8 * i; float* o1 = o0 + 4;
        o0[0] = o0[1] = o0[2] = o0[3] = o1[0] = o1[1] = o1[2] = o1[3] = 0.f;
        { uint32_t a[4] = {p[0][0], p[0][1], p[1][0], p[1][1]}; mma16816(o0, a, b0[0], b0[1]); mma16816(o1, a, b0[2], b0[3]); }
        { uint32_t a[4] = {p[2][0], p[2][1], p[3][0], p[3][1]}; mma16816(o0, a, b1[0], b1[1]); mma16816(o1, a, b1[2], b1[3]); }
        { uint32_t a[4] = {p[4][0], p[4][1], p[5][0], p[5][1]}; mma16816(o0, a, b2[0], b2[1]); mma16816(o1, a, b2[2], b2[3]); }
    }
}
__device__ __forceinline__ void bulk_load(uint32_t dst, const void* src, uint32_t bytes, uint32_t bar) {
    asm volatile("cp.async.bulk.shared::cluster.global.mbarrier::complete_tx::bytes [%0], [%1], %2, [%3];" :: "r"(dst), "l"(src), "r"(bytes), "r"(bar) : "memory");
}

__device__ __forceinline__ void stsm_x4(uint32_t addr, uint32_t a, uint32_t b, uint32_t c, uint32_t d) {
    asm volatile("stmatrix.sync.aligned.m8n8.x4.shared.b16 [%0], {%1,%2,%3,%4};" :: "r"(addr), "r"(a), "r"(b), "r"(c), "r"(d) : "memory");
}
__device__ __forceinline__ void tma_reduce_2d(const CUtensorMap* map, uint32_t src, int c0, int c1) {
    asm volatile("cp.reduce.async.bulk.tensor.2d.global.shared::cta.add.tile.bulk_group [%0, {%2, %3}], [%1];" :: "l"(map), "r"(src), "r"(c0), "r"(c1) : "memory");
}
__device__ __forceinline__ void tma_store_2d(const CUtensorMap* map, uint32_t src, int c0, int c1) {
    asm volatile("cp.async.bulk.tensor.2d.global.shared::cta.bulk_group [%0, {%2, %3}], [%1];" :: "l"(map), "r"(src), "r"(c0), "r"(c1) : "memory");
}

__global__ void __launch_bounds__(384, 1)
g_kernel(const __grid_constant__ GParams P, const bf16* __restrict__ x, const bf16* __restrict__ cvec, const bf16* __restrict__ w_mod, bf16* __restrict__ out, int nctas, int wait_r)
{
    using namespace gk;
    extern __shared__ __align__(1024) uint8_t smem[];
    const uint32_t sb = smem_u32(smem);
    const int tid = threadIdx.x, warp = tid >> 5, lane = tid & 31;
    const uint32_t b_full = sb + OFF_BAR, b_empty = b_full + 8 * STAGES, b_wfull = b_empty + 8 * STAGES, b_wempty = b_wfull + 16;
    const uint32_t b_cdone = b_wempty + 16, b_sfree = b_cdone + 16;
    volatile int* wslot = (volatile int*)(smem + OFF_BAR + 192);
    const uint32_t epoch = ld_relaxed(&g_epoch);
    const uint32_t e1 = epoch + 1;
    if (tid == 0) {
        wslot[4] = 0;
        for (int i = 0; i < STAGES; i++) { mbar_init(b_full + 8 * i, 1); mbar_init(b_empty + 8 * i, 8); }
        for (int i = 0; i < 2; i++) { mbar_init(b_wfull + 8 * i, 1); mbar_init(b_wempty + 8 * i, 9); mbar_init(b_cdone + 8 * i, 4); mbar_init(b_sfree + 8 * i, 1); }
        asm volatile("fence.mbarrier_init.release.cluster;" ::: "memory");
    }
    __syncthreads();

    if (warp < 4) {
        asm volatile("setmaxnreg.dec.sync.aligned.u32 40;");
        if (warp == 0 && lane == 0) {
            uint32_t stage = 0, sph = 1, wi = 0, wph = 1;
            bool low_left = true;
            uint32_t lx0 = 0, lx1 = 0, lx2 = 0;
            int lim = 0, issued = 0, nat = 0;
            volatile int* fin_cnt = wslot + 4;
            while (true) {
                Item it; it.type = T_END; it.rb = it.nt = it.ks = 0;
                int tk = 0; (void)tk;
                while (true) {
                    uint4 rd = ld_relaxed_v4(&g_st.ready[0]); const uint4 ex = ld_relaxed_v4(&g_st.exh[0]);
                    const uint32_t dat = nat < 16 ? ld_relaxed(&g_st.d_at[nat * 32]) : 0;
                    if (nat < 16 && dat == e1 * (wait_r ? 112u : 48u)) { if (!(rd.x >> nat & 1)) publish_group(T_AT, nat, e1); nat++; }
                    { const int na = __popc(rd.x & 0xffffu); if (na > nat) nat = na; }
                    rd.x |= (1u << nat) - 1;
                    lx0 |= ex.x; lx1 |= ex.y; lx2 |= ex.z;
                    uint32_t a0 = rd.x & ~lx0, a1 = rd.y & ~lx1, a2 = rd.z & ~lx2;
                    bool got = false;
                    if ((a0 | a1 | a2) && (rd.x >> (FINE_RB - 1) & 1) && *fin_cnt != issued) {
                        int l2 = 0; while (*fin_cnt != issued && ++l2 < SPIN_LIMIT) { }
                        continue;
                    }
                    while (a0 | a1 | a2) {
                        const int gi = a0 ? __ffs(a0) - 1 : (a1 ? 32 + __ffs(a1) - 1 : 64 + __ffs(a2) - 1);
                        const int ty = T_AT + (gi >> 4), rb = gi & 15, n = group_size(ty, rb);
                        const int i = (int)atomicAdd(&g_st.cnt[gi * 8], 1u);
                        const uint32_t bit = 1u << (gi & 31);
                        if (i >= n - 1) {
                            if (gi < 32) { lx0 |= bit; a0 &= ~bit; } else if (gi < 64) { lx1 |= bit; a1 &= ~bit; } else { lx2 |= bit; a2 &= ~bit; }
                            if (i == n - 1) asm volatile("red.relaxed.gpu.global.or.b32 [%0], %1;" :: "l"(&g_st.exh[gi >> 5]), "r"(bit) : "memory");
                        }
                        if (i < n) {
                            it.type = ty; it.rb = rb; it.nt = i;
                            if (ty == T_WO || ty == T_F2) { const int nn = n_nt(rb); it.ks = i / nn; it.nt = i - it.ks * nn; }
                            asm volatile("fence.acq_rel.gpu;" ::: "memory");
                            got = true; break;
                        }
                    }
                    if (got) {
                        break;
                    }
                    if (low_left && (int)rd.w < I_W + 64 + (nat + LOW_LEAD) * 48) {
                        const int lt = (int)atomicAdd(&g_st.lq_claim, 1u);
                        if (lt < N_LOW) {
                            it = decode_low(lt);
                            if (it.type == T_L1) wait_ge(&g_st.c_mod_a, e1 * 20);
                            else if (it.type != T_MOD) wait_ge(&g_st.f_h[it.rb * 32], e1 * 16);
                            break;
                        }
                        low_left = false;
                    }
                    if ((lx0 & lx1 & lx2) == 0xffffffffu) break;
                    __nanosleep(40);
                    if (++lim > SPIN_LIMIT) break;
                }
                issued++;
                if (it.type == T_L2) wait_ge(&g_st.c_mod_all, e1 * 60);
                asm volatile("fence.proxy.async.global;" ::: "memory");
                mbar_wait(b_wempty + 8 * wi, wph);
                wslot[wi] = pack_item(it);
                mbar_arrive(b_wfull + 8 * wi);
                if (++wi == 2) { wi = 0; wph ^= 1; }
                if (it.type == T_END) break;
                int nkb = 0, kb0 = 0;
                const CUtensorMap *mA = nullptr, *mB0 = nullptr, *mB1 = nullptr; int n0 = 0, n1 = 0, nbox = 4;
                switch (it.type) {
                    case T_KV: nkb = 10; mA = &P.tA_h; mB0 = mB1 = (it.nt < 16) ? &P.tB_k : &P.tB_v; n0 = (it.nt & 15) * 256; n1 = n0 + 128; break;
                    case T_Q: nkb = 10; mA = &P.tA_h; mB0 = mB1 = &P.tB_q; n0 = it.nt * 256; n1 = n0 + 128; break;
                    case T_F1: nkb = 10; mA = &P.tA_h2; mB0 = &P.tB_g; mB1 = &P.tB_u; if (fine(it.rb)) { n0 = n1 = it.nt * 64; nbox = 2; } else n0 = n1 = it.nt * 128; break;
                    case T_WO: nkb = 64 / wo_split(it.rb); kb0 = it.ks * nkb; mA = &P.tA_o; mB0 = mB1 = &P.tB_o; n0 = red_col(it); if (is_wide(it)) n1 = n0 + 128; else { n1 = n0 + 64; nbox = 2; } break;
                    case T_F2: nkb = 27 / f2_split(it.rb); kb0 = it.ks * nkb; mA = &P.tA_act; mB0 = mB1 = &P.tB_d; n0 = red_col(it); if (is_wide(it)) n1 = n0 + 128; else { n1 = n0 + 64; nbox = 2; } break;
                    default: break;
                }
                if (it.type == T_AT) {
#pragma unroll 1
                    for (int i = 0; i < 3; i++) {
                        mbar_wait(b_empty + 8 * stage, sph);
                        const uint32_t st = sb + stage * STAGE_BYTES, bar = b_full + 8 * stage;
                        mbar_expect_tx(bar, i ? 40960 : 32768);
                        const CUtensorMap* m = i == 0 ? &P.tL_q : (i == 1 ? &P.tL_k : &P.tL_v);
                        tma_load_2d(st + 16384, m, it.nt * 128, it.rb * 128, bar);
                        tma_load_2d(st + 32768, m, it.nt * 128 + 64, it.rb * 128, bar);
                        if (i) {
                            const CUtensorMap* mm = i == 1 ? &P.tL_km : &P.tL_vm;
                            tma_load_2d(st, mm, it.nt * 128, it.rb * 32, bar);
                            tma_load_2d(st + 4096, mm, it.nt * 128 + 64, it.rb * 32, bar);
                        }
                        if (++stage == STAGES) { stage = 0; sph ^= 1; }
                    }
                } else if (it.type == T_L1 || it.type == T_L2 || it.type == T_FIN) {
                    const int mode = it.type == T_L1 ? 0 : (it.type == T_L2 ? 1 : 2);
                    const uint32_t pbytes = mode == 0 ? 5120 : (mode == 1 ? 7680 : 2560);
                    const float* psrc = g_mod + (mode == 0 ? 0 : (mode == 1 ? 2 * 640 : 5 * 640));
                    {
                        mbar_wait(b_empty + 8 * stage, sph);
                        const uint32_t st = sb + stage * STAGE_BYTES, bar = b_full + 8 * stage;
                        const size_t ro = ((size_t)it.rb * 128 + it.nt * 8) * 640;
                        mbar_expect_tx(bar, 10240 + (mode ? 20480 : 0) + pbytes);
                        bulk_load(st, (mode == 2 ? g_x1 : x) + ro, 10240, bar);
                        if (mode) bulk_load(st + 10240, g_slab + ro, 20480, bar);
                        bulk_load(st + 30720, psrc, pbytes, bar);
                        if (++stage == STAGES) { stage = 0; sph ^= 1; }
                    }
                }
                for (int kb = 0; kb < nkb; kb++) {
                    mbar_wait(b_empty + 8 * stage, sph);
                    const uint32_t st = sb + stage * STAGE_BYTES, bar = b_full + 8 * stage;
                    mbar_expect_tx(bar, 16384 + nbox * 8192);
                    const int k = (kb0 + kb) * 64;
                    tma_load_2d(st, mA, k, it.rb * 128, bar);
                    tma_load_2d(st + 16384, mB0, n0, k, bar);
                    if (nbox == 4) {
                        tma_load_2d(st + 16384 + 8192, mB0, n0 + 64, k, bar);
                        tma_load_2d(st + 16384 + 16384, mB1, n1, k, bar);
                        tma_load_2d(st + 16384 + 24576, mB1, n1 + 64, k, bar);
                    } else {
                        tma_load_2d(st + 16384 + 8192, mB1, n1, k, bar);
                    }
                    if (++stage == STAGES) { stage = 0; sph ^= 1; }
                }
            }
        } else if (warp == 1 && lane == 0) {
            uint32_t wi = 0, wph = 0, cph = 0;
            while (true) {
                mbar_wait(b_wfull + 8 * wi, wph);
                const Item it = unpack_item(wslot[wi]);
                mbar_arrive(b_wempty + 8 * wi);
                if (++wi == 2) { wi = 0; wph ^= 1; }
                if (it.type == T_END) break;
                const bool red = it.type == T_WO || it.type == T_F2;
                const bool tma = it.type == T_KV || it.type == T_Q || it.type == T_F1 || it.type == T_AT || red;
                const bool narrow = it.type == T_F1 && fine(it.rb);
                const int rounds = red ? (is_wide(it) ? 4 : 2) : ((it.type == T_KV || it.type == T_Q) ? 2 : 1);
                const CUtensorMap* mS = it.type == T_F1 ? &P.tS_act : (it.type == T_AT ? &P.tS_o : (it.type == T_Q ? &P.tS_q : (it.nt < 16 ? &P.tS_k : &P.tS_v)));
                const int gcol = red ? red_col(it) : (narrow ? it.nt * 64 : (rounds == 1 ? it.nt * 128 : (it.nt & 15) * 256));
                for (int rnd = 0; rnd < rounds; rnd++) {
                    for (int wg = 0; wg < 2; wg++) {
                        mbar_wait(b_cdone + 8 * wg, cph);
                        const uint32_t stg = sb + OFF_SCR + wg * 16384;
                        const int grow = it.rb * 128 + wg * 64;
                        if (red) {
                            tma_reduce_2d(&P.tR_acc, stg, gcol + rnd * 64, grow);
                            tma_reduce_2d(&P.tR_acc, stg + 8192, gcol + rnd * 64 + 32, grow);
                        } else if (tma) {
                            tma_store_2d(mS, stg, gcol + rnd * 128, grow);
                            if (!narrow) tma_store_2d(mS, stg + 8192, gcol + rnd * 128 + 64, grow);
                        }
                        if (tma) asm volatile("cp.async.bulk.commit_group;" ::: "memory");
                    }
                    cph ^= 1;
                    if (tma) asm volatile("cp.async.bulk.wait_group.read 0;" ::: "memory");
                    mbar_arrive(b_sfree); mbar_arrive(b_sfree + 8);
                }
                if (tma) { asm volatile("cp.async.bulk.wait_group 0;" ::: "memory"); asm volatile("fence.proxy.async.global;" ::: "memory"); }
                if (it.type <= T_KV) asm volatile("fence.acq_rel.gpu;" ::: "memory");
                uint32_t* cnt = nullptr; uint32_t tgt = 0; int nxt = -1;
                switch (it.type) {
                    case T_KV: st_relaxed_u32(&g_kvflag[it.rb * 64 + it.nt * 2], e1); st_relaxed_u32(&g_kvflag[it.rb * 64 + it.nt * 2 + 1], e1);
                    case T_Q: red_release_inc(&g_st.d_at[it.rb * 32]); break;
                    case T_MOD: if (it.nt < 20) red_add_relaxed(&g_st.c_mod_a, 1); red_add_relaxed(&g_st.c_mod_all, 1); break;
                    case T_L1: red_add_relaxed(&g_st.f_h[it.rb * 32], 1); break;
                    case T_AT: cnt = &g_st.c_at[it.rb * 32]; tgt = 32; nxt = T_WO; break;
                    case T_WO: cnt = &g_st.c_wo[it.rb * 32]; tgt = group_size(T_WO, it.rb); nxt = T_L2; break;
                    case T_L2: cnt = &g_st.f_h2[it.rb * 32]; tgt = 16; nxt = T_F1; break;
                    case T_F1: cnt = &g_st.c_act[it.rb * 32]; tgt = group_size(T_F1, it.rb); nxt = T_F2; break;
                    case T_F2: cnt = &g_st.c_f2[it.rb * 32]; tgt = group_size(T_F2, it.rb); nxt = T_FIN; break;
                    default: break;
                }
                if (cnt) { if (atom_add_acqrel(cnt, 1) + 1 == e1 * tgt) publish_group(nxt, it.rb, e1); }
            }
            uint32_t old = atom_add_acqrel(&g_st.done, 1);
            if (old + 1 == e1 * (uint32_t)nctas) {
                for (int i = 0; i < 96; i++) g_st.cnt[i * 8] = 0;
                for (int i = 0; i < 3; i++) { g_st.ready[i] = 0; g_st.exh[i] = 0; }
                g_st.lq_claim = 0;
                st_release(&g_epoch, e1);
            }
        }
    } else {
        asm volatile("setmaxnreg.inc.sync.aligned.u32 232;");
        const int ct = tid - 128, cw = warp - 4, wg = cw >> 2;
        const int g = lane >> 2, t = lane & 3;
        uint32_t stage = 0, sph = 0, wi = 0, wph = 0, fph = 1; int ndone = 0;
        while (true) {
            if (ct == 0) wslot[4] = ndone;
            ndone++;
            mbar_wait(b_wfull + 8 * wi, wph);
            const Item it = unpack_item(wslot[wi]);
            __syncwarp();
            if (lane == 0) mbar_arrive(b_wempty + 8 * wi);
            if (++wi == 2) { wi = 0; wph ^= 1; }
            if (it.type == T_END) break;
            const bool narrow = it.type == T_F1 && fine(it.rb);
            if (is_wide(it)) {
                const bool red = it.type == T_WO || it.type == T_F2;
                const int nkb = it.type == T_WO ? 64 / wo_split(it.rb) : (it.type == T_F2 ? 27 / f2_split(it.rb) : 10);
                float d[128];
#pragma unroll
                for (int i = 0; i < 128; i++) d[i] = 0.f;
                for (int kb = 0; kb < nkb; kb++) {
                    mbar_wait(b_full + 8 * stage, sph);
                    const uint32_t st = sb + stage * STAGE_BYTES;
                    const uint64_t da = make_desc(st + wg * 8192, 16, 1024), db = make_desc(st + 16384, 8192, 1024);
                    wgmma_fence();
#pragma unroll
                    for (int k = 0; k < 4; k++) wgmma_n256(d, da + k * 2, db + k * 128, 1);
                    wgmma_commit();
                    wgmma_wait<1>();
                    if (kb > 0 && lane == 0) mbar_arrive(b_empty + 8 * ((stage + STAGES - 1) % STAGES));
                    if (++stage == STAGES) { stage = 0; sph ^= 1; }
                }
                wgmma_wait<0>();
                fence_acc<128>(d);
                if (lane == 0) mbar_arrive(b_empty + 8 * ((stage + STAGES - 1) % STAGES));
                if (red) {
                    const uint32_t sbase = sb + OFF_SCR + wg * 16384 + ((cw & 3) * 16 + g) * 128 + (t & 1) * 8;
#pragma unroll
                    for (int rnd = 0; rnd < 4; rnd++) {
                        mbar_wait(b_sfree + 8 * wg, fph); fph ^= 1;
#pragma unroll
                        for (int i = 0; i < 8; i++) {
                            const float* dd = d + rnd * 32 + i * 4;
                            const uint32_t a = sbase + (i >> 2) * 8192 + ((((2 * i + (t >> 1)) & 7) ^ (g & 7)) << 4);
                            sts64(a, __float_as_uint(dd[0]), __float_as_uint(dd[1]));
                            sts64(a + 1024, __float_as_uint(dd[2]), __float_as_uint(dd[3]));
                        }
                        asm volatile("fence.proxy.async.shared::cta;" ::: "memory");
                        __syncwarp();
                        if (lane == 0) mbar_arrive(b_cdone + 8 * wg);
                    }
                    continue;
                }
                const uint32_t sbase = sb + OFF_SCR + wg * 16384 + ((cw & 3) * 16 + ((lane >> 3) & 1) * 8 + (lane & 7)) * 128;
                const int sx = lane & 7, hi = lane >> 4;
                if (it.type == T_F1) {
#pragma unroll
                    for (int i = 0; i < 64; i++) d[i] = bf16r(gelu_tanh(bf16r(d[i]))) * bf16r(d[64 + i]);
                }
#pragma unroll
                for (int rnd = 0; rnd < 2; rnd++) {
                    if (rnd == 1 && it.type == T_F1) break;
                    mbar_wait(b_sfree + 8 * wg, fph); fph ^= 1;
#pragma unroll
                    for (int i = 0; i < 8; i++) {
                        const float* dd = d + rnd * 64 + i * 8;
                        const int chunk = (2 * i + hi) & 7;
                        stsm_x4(sbase + (i >> 2) * 8192 + ((chunk ^ sx) << 4), pack_bf16(dd[0], dd[1]), pack_bf16(dd[2], dd[3]), pack_bf16(dd[4], dd[5]), pack_bf16(dd[6], dd[7]));
                    }
                    asm volatile("fence.proxy.async.shared::cta;" ::: "memory");
                    __syncwarp();
                    if (lane == 0) mbar_arrive(b_cdone + 8 * wg);
                }
                continue;
            } else if (narrow) {
                float d[64];
#pragma unroll
                for (int i = 0; i < 64; i++) d[i] = 0.f;
                const int nkb = 10;
                for (int kb = 0; kb < nkb; kb++) {
                    mbar_wait(b_full + 8 * stage, sph);
                    const uint32_t st = sb + stage * STAGE_BYTES;
                    const uint64_t da = make_desc(st + wg * 8192, 16, 1024), db = make_desc(st + 16384, 8192, 1024);
                    wgmma_fence();
#pragma unroll
                    for (int k = 0; k < 4; k++) wgmma_n128(d, da + k * 2, db + k * 128, 1);
                    wgmma_commit();
                    wgmma_wait<1>();
                    if (kb > 0 && lane == 0) mbar_arrive(b_empty + 8 * ((stage + STAGES - 1) % STAGES));
                    if (++stage == STAGES) { stage = 0; sph ^= 1; }
                }
                wgmma_wait<0>();
                fence_acc<64>(d);
                if (lane == 0) mbar_arrive(b_empty + 8 * ((stage + STAGES - 1) % STAGES));
                {
                    const uint32_t sbase = sb + OFF_SCR + wg * 16384 + ((cw & 3) * 16 + ((lane >> 3) & 1) * 8 + (lane & 7)) * 128;
#pragma unroll
                    for (int i = 0; i < 32; i++) d[i] = bf16r(gelu_tanh(bf16r(d[i]))) * bf16r(d[32 + i]);
                    mbar_wait(b_sfree + 8 * wg, fph); fph ^= 1;
#pragma unroll
                    for (int i = 0; i < 4; i++) {
                        const float* dd = d + i * 8;
                        const int chunk = 2 * i + (lane >> 4);
                        stsm_x4(sbase + ((chunk ^ (lane & 7)) << 4), pack_bf16(dd[0], dd[1]), pack_bf16(dd[2], dd[3]), pack_bf16(dd[4], dd[5]), pack_bf16(dd[6], dd[7]));
                    }
                    asm volatile("fence.proxy.async.shared::cta;" ::: "memory");
                }
            } else if (it.type == T_WO || it.type == T_F2) {
                float d[64];
#pragma unroll
                for (int i = 0; i < 64; i++) d[i] = 0.f;
                const int nkb = it.type == T_WO ? 64 / wo_split(it.rb) : 27 / f2_split(it.rb);
                for (int kb = 0; kb < nkb; kb++) {
                    mbar_wait(b_full + 8 * stage, sph);
                    const uint32_t st = sb + stage * STAGE_BYTES;
                    const uint64_t da = make_desc(st + wg * 8192, 16, 1024), db = make_desc(st + 16384, 8192, 1024);
                    wgmma_fence();
#pragma unroll
                    for (int k = 0; k < 4; k++) wgmma_n128(d, da + k * 2, db + k * 128, 1);
                    wgmma_commit();
                    wgmma_wait<1>();
                    if (kb > 0 && lane == 0) mbar_arrive(b_empty + 8 * ((stage + STAGES - 1) % STAGES));
                    if (++stage == STAGES) { stage = 0; sph ^= 1; }
                }
                wgmma_wait<0>();
                fence_acc<64>(d);
                if (lane == 0) mbar_arrive(b_empty + 8 * ((stage + STAGES - 1) % STAGES));
                {
                    const int r0 = (cw & 3) * 16 + g;
                    const uint32_t sbase = sb + OFF_SCR + wg * 16384 + r0 * 128 + (t & 1) * 8;
#pragma unroll
                    for (int rnd = 0; rnd < 2; rnd++) {
                        mbar_wait(b_sfree + 8 * wg, fph); fph ^= 1;
#pragma unroll
                        for (int i = 0; i < 8; i++) {
                            const float* dd = d + rnd * 32 + i * 4;
                            const uint32_t a = sbase + (i >> 2) * 8192 + ((((2 * i + (t >> 1)) & 7) ^ (g & 7)) << 4);
                            sts64(a, __float_as_uint(dd[0]), __float_as_uint(dd[1]));
                            sts64(a + 1024, __float_as_uint(dd[2]), __float_as_uint(dd[3]));
                        }
                        asm volatile("fence.proxy.async.shared::cta;" ::: "memory");
                        if (rnd == 0) { __syncwarp(); if (lane == 0) mbar_arrive(b_cdone + 8 * wg); }
                    }
                }
            } else if (it.type == T_AT) {
                uint32_t p[6][2];
                float d[64];
                const uint32_t s0 = stage, s1 = (stage + 1) % STAGES, s2 = (stage + 2) % STAGES;
                mbar_wait(b_full + 8 * s0, sph);
                mbar_wait(b_full + 8 * s1, s1 < s0 ? sph ^ 1 : sph);
                attn_scores(sb + s0 * STAGE_BYTES + 16384, sb + s1 * STAGE_BYTES + 16384, sb + s1 * STAGE_BYTES, cw >> 1, cw & 1, lane, p);
                __syncwarp();
                if (lane == 0) { mbar_arrive(b_empty + 8 * s0); mbar_arrive(b_empty + 8 * s1); }
                mbar_wait(b_full + 8 * s2, s2 < s0 ? sph ^ 1 : sph);
                attn_pv(sb + s2 * STAGE_BYTES + 16384, sb + s2 * STAGE_BYTES, cw >> 1, lane, p, d);
                __syncwarp();
                if (lane == 0) mbar_arrive(b_empty + 8 * s2);
                stage += 3; if (stage >= STAGES) { stage -= STAGES; sph ^= 1; }
                const uint32_t sbase = sb + OFF_SCR + wg * 16384 + ((cw & 3) * 16 + ((lane >> 3) & 1) * 8 + (lane & 7)) * 128;
                mbar_wait(b_sfree + 8 * wg, fph); fph ^= 1;
#pragma unroll
                for (int i = 0; i < 8; i++) {
                    const float* dd = d + i * 8;
                    const int chunk = (2 * i + (lane >> 4)) & 7;
                    stsm_x4(sbase + (i >> 2) * 8192 + ((chunk ^ (lane & 7)) << 4), pack_bf16(dd[0], dd[1]), pack_bf16(dd[2], dd[3]), pack_bf16(dd[4], dd[5]), pack_bf16(dd[6], dd[7]));
                }
                asm volatile("fence.proxy.async.shared::cta;" ::: "memory");
            } else if (it.type == T_L1 || it.type == T_L2 || it.type == T_FIN) {
                const int mode = it.type == T_L1 ? 0 : (it.type == T_L2 ? 1 : 2);
                {
                    const size_t ro = ((size_t)it.rb * 128 + it.nt * 8 + cw) * 640;
                    const uint32_t st = sb + stage * STAGE_BYTES;
                    mbar_wait(b_full + 8 * stage, sph);
                    row_item(mode, st + cw * 1280, st + 10240 + cw * 2560, st + 30720, b_empty + 8 * stage, g_slab + ro, (mode == 2 ? out : g_x1) + ro, (mode ? g_h2 : g_h) + ro, lane);
                    if (++stage == STAGES) { stage = 0; sph ^= 1; }
                }
            } else if (it.type == T_MOD) {
                const int kg = ct >> 3, c8 = ct & 7;
                float acc[8] = {0, 0, 0, 0, 0, 0, 0, 0};
                const bf16* wp = w_mod + (size_t)kg * 20 * 3840 + it.nt * 64 + c8 * 8;
                {
                    uint4 w[20]; float sl[20];
#pragma unroll
                    for (int i = 0; i < 20; i++) { w[i] = __ldg((const uint4*)(wp + (size_t)i * 3840)); sl[i] = __bfloat162float(cvec[kg * 20 + i]); }
#pragma unroll
                    for (int i = 0; i < 20; i++) {
                        const float s = bf16r(__fdividef(sl[i], 1.0f + __expf(-sl[i])));
                        acc[0] += s * __uint_as_float(w[i].x << 16); acc[1] += s * __uint_as_float(w[i].x & 0xffff0000u);
                        acc[2] += s * __uint_as_float(w[i].y << 16); acc[3] += s * __uint_as_float(w[i].y & 0xffff0000u);
                        acc[4] += s * __uint_as_float(w[i].z << 16); acc[5] += s * __uint_as_float(w[i].z & 0xffff0000u);
                        acc[6] += s * __uint_as_float(w[i].w << 16); acc[7] += s * __uint_as_float(w[i].w & 0xffff0000u);
                    }
                }
#pragma unroll
                for (int i = 0; i < 8; i++) { acc[i] += __shfl_xor_sync(0xffffffff, acc[i], 8); acc[i] += __shfl_xor_sync(0xffffffff, acc[i], 16); }
                float* scr = (float*)(smem + OFF_BAR + 256);
                bar_sync(3, 256);
                if (lane < 8) {
#pragma unroll
                    for (int i = 0; i < 8; i++) scr[cw * 64 + lane * 8 + i] = acc[i];
                }
                bar_sync(3, 256);
                if (ct < 64) {
                    float sum = 0;
#pragma unroll
                    for (int i = 0; i < 8; i++) sum += scr[i * 64 + ct];
                    g_mod[it.nt * 64 + ct] = bf16r(sum);
                }
            }
            if (it.type == T_MOD || it.type == T_L1 || it.type == T_L2 || it.type == T_FIN) { mbar_wait(b_sfree + 8 * wg, fph); fph ^= 1; }
            __syncwarp();
            if (lane == 0) mbar_arrive(b_cdone + 8 * wg);
        }
    }
}

typedef CUresult (*PFN_encodeTiled)(CUtensorMap*, CUtensorMapDataType, cuuint32_t, void*, const cuuint64_t*, const cuuint64_t*, const cuuint32_t*, const cuuint32_t*, CUtensorMapInterleave, CUtensorMapSwizzle, CUtensorMapL2promotion, CUtensorMapFloatOOBfill);

static void make_map(PFN_encodeTiled fn, CUtensorMap* m, const void* ptr, uint64_t inner, uint64_t outer, uint32_t box_inner, uint32_t box_outer, bool f32 = false) {
    cuuint64_t dims[2] = {inner, outer};
    cuuint64_t strides[1] = {inner * (f32 ? 4 : 2)};
    cuuint32_t box[2] = {box_inner, box_outer};
    cuuint32_t es[2] = {1, 1};
    fn(m, f32 ? CU_TENSOR_MAP_DATA_TYPE_FLOAT32 : CU_TENSOR_MAP_DATA_TYPE_BFLOAT16, 2, (void*)ptr, dims, strides, box, es, CU_TENSOR_MAP_INTERLEAVE_NONE, CU_TENSOR_MAP_SWIZZLE_128B, CU_TENSOR_MAP_L2_PROMOTION_L2_256B, CU_TENSOR_MAP_FLOAT_OOB_FILL_NONE);
}

#define G_LESS 0
static int g_dbg_mode = 0;

extern "C" void kernel_launch(void* const* d_in, const int* in_sizes, int n_in, void* d_out, int out_size) {
    const bf16* x = (const bf16*)d_in[0];
    const bf16* mem0 = (const bf16*)d_in[1];
    const bf16* Wq = (const bf16*)d_in[2];
    const bf16* Wk = (const bf16*)d_in[3];
    const bf16* Wv = (const bf16*)d_in[4];
    const bf16* Wo = (const bf16*)d_in[5];
    const bf16* Wg = (const bf16*)d_in[8];
    const bf16* Wu = (const bf16*)d_in[9];
    const bf16* Wd = (const bf16*)d_in[10];
    const bf16* cvec = (const bf16*)d_in[11];
    const bf16* wmod = (const bf16*)d_in[12];
    static PFN_encodeTiled fn = nullptr;
    static int nsm = 0;
    if (!fn) {
        cudaDriverEntryPointQueryResult qr;
        cudaGetDriverEntryPoint("cuTensorMapEncodeTiled", (void**)&fn, cudaEnableDefault, &qr);
        cudaFuncSetAttribute(r_kernel, cudaFuncAttributeMaxDynamicSharedMemorySize, rk::SMEM_BYTES);
        cudaFuncSetAttribute(r_kernel, cudaFuncAttributeNonPortableClusterSizeAllowed, 1);
        cudaFuncSetAttribute(g_kernel, cudaFuncAttributeMaxDynamicSharedMemorySize, gk::SMEM_BYTES);
        cudaDeviceGetAttribute(&nsm, cudaDevAttrMultiProcessorCount, 0);
    }
    void *ph, *po, *ph2, *pact, *pq, *pk, *pv;
    cudaGetSymbolAddress(&pq, g_q); cudaGetSymbolAddress(&pk, g_k); cudaGetSymbolAddress(&pv, g_v);
    cudaGetSymbolAddress(&ph, g_h); cudaGetSymbolAddress(&po, g_o); cudaGetSymbolAddress(&ph2, g_h2); cudaGetSymbolAddress(&pact, g_act);
    GParams P;
    make_map(fn, &P.tA_h, ph, 640, 2048, 64, 128);
    make_map(fn, &P.tA_o, po, 4096, 2048, 64, 128);
    make_map(fn, &P.tA_h2, ph2, 640, 2048, 64, 128);
    make_map(fn, &P.tA_act, pact, 1728, 2048, 64, 128);
    make_map(fn, &P.tB_q, Wq, 4096, 640, 64, 64);
    make_map(fn, &P.tB_k, Wk, 4096, 640, 64, 64);
    make_map(fn, &P.tB_v, Wv, 4096, 640, 64, 64);
    make_map(fn, &P.tB_o, Wo, 640, 4096, 64, 64);
    make_map(fn, &P.tB_g, Wg, 1728, 640, 64, 64);
    make_map(fn, &P.tB_u, Wu, 1728, 640, 64, 64);
    make_map(fn, &P.tB_d, Wd, 640, 1728, 64, 64);
    make_map(fn, &P.tS_q, pq, 4096, 2048, 64, 64);
    make_map(fn, &P.tS_k, pk, 4096, 2048, 64, 64);
    make_map(fn, &P.tS_v, pv, 4096, 2048, 64, 64);
    make_map(fn, &P.tS_act, pact, 1728, 2048, 64, 64);
    void *pkm, *pvm; cudaGetSymbolAddress(&pkm, g_km); cudaGetSymbolAddress(&pvm, g_vm);
    make_map(fn, &P.tS_o, po, 4096, 2048, 64, 64);
    make_map(fn, &P.tL_q, pq, 4096, 2048, 64, 128);
    make_map(fn, &P.tL_k, pk, 4096, 2048, 64, 128);
    make_map(fn, &P.tL_v, pv, 4096, 2048, 64, 128);
    make_map(fn, &P.tL_km, pkm, 4096, 512, 64, 32);
    make_map(fn, &P.tL_vm, pvm, 4096, 512, 64, 32);
    void* pacc; cudaGetSymbolAddress(&pacc, g_slab);
    make_map(fn, &P.tR_acc, pacc, 640, 2048, 32, 64, true);
    cudaStream_t st = cudaStreamPerThread;
    if (g_dbg_mode != 1) {
        cudaLaunchConfig_t cfg = {};
        cfg.gridDim = dim3(64); cfg.blockDim = dim3(256); cfg.dynamicSmemBytes = rk::SMEM_BYTES; cfg.stream = st;
        cudaLaunchAttribute at[1]; at[0].id = cudaLaunchAttributeClusterDimension; at[0].val.clusterDim.x = 16; at[0].val.clusterDim.y = 1; at[0].val.clusterDim.z = 1;
        cfg.attrs = at; cfg.numAttrs = 1;
        CUtensorMap tk, tv;
        make_map(fn, &tk, pk, 4096, 2048, 64, 32);
        make_map(fn, &tv, pv, 4096, 2048, 64, 32);
        cudaLaunchKernelEx(&cfg, r_kernel, tk, tv, mem0, Wq, Wk, Wv, Wo, 1);
    }
    {
        cudaLaunchConfig_t cfg = {};
        const int ng = g_dbg_mode == 1 ? nsm : nsm - G_LESS;
        cfg.gridDim = dim3(ng); cfg.blockDim = dim3(384); cfg.dynamicSmemBytes = gk::SMEM_BYTES; cfg.stream = st;
        cudaLaunchAttribute at[1]; at[0].id = cudaLaunchAttributeProgrammaticStreamSerialization; at[0].val.programmaticStreamSerializationAllowed = 1;
        cfg.attrs = at; cfg.numAttrs = g_dbg_mode == 1 ? 0 : 1;
        cudaLaunchKernelEx(&cfg, g_kernel, P, x, cvec, wmod, (bf16*)d_out, ng, g_dbg_mode == 1 ? 0 : 1);
    }
}
```

```cpp
#include <cuda_runtime.h>
#include <cuda_bf16.h>
#include <cuda.h>
#include <stdint.h>

typedef __nv_bfloat16 bf16;

__device__ __forceinline__ uint32_t smem_u32(const void* p) { return (uint32_t)__cvta_generic_to_shared(p); }
__device__ __forceinline__ uint32_t mapa_u32(uint32_t a, uint32_t r) { uint32_t o; asm volatile("mapa.shared::cluster.u32 %0, %1, %2;" : "=r"(o) : "r"(a), "r"(r)); return o; }
__device__ __forceinline__ void mbar_init(uint32_t bar, uint32_t cnt) { asm volatile("mbarrier.init.shared::cta.b64 [%0], %1;" :: "r"(bar), "r"(cnt) : "memory"); }
__device__ __forceinline__ void mbar_expect_tx(uint32_t bar, uint32_t bytes) { asm volatile("mbarrier.arrive.expect_tx.shared::cta.b64 _, [%0], %1;" :: "r"(bar), "r"(bytes) : "memory"); }
__device__ __forceinline__ void mbar_arrive(uint32_t bar) { asm volatile("mbarrier.arrive.shared::cta.b64 _, [%0];" :: "r"(bar) : "memory"); }
#define SPIN_LIMIT 400000
__device__ __forceinline__ void mbar_wait(uint32_t bar, uint32_t ph) {
    uint32_t ok = 0; int lim = 0;
    while (true) {
        asm volatile("{ .reg .pred p; mbarrier.try_wait.parity.shared::cta.b64 p, [%1], %2; selp.u32 %0, 1, 0, p; }" : "=r"(ok) : "r"(bar), "r"(ph) : "memory");
        if (ok) break;
        if (++lim > SPIN_LIMIT) break;
    }
}
__device__ __forceinline__ void mbar_wait_cluster(uint32_t bar, uint32_t ph) {
    uint32_t ok = 0; int lim = 0;
    while (true) {
        asm volatile("{ .reg .pred p; mbarrier.try_wait.parity.acquire.cluster.shared::cta.b64 p, [%1], %2; selp.u32 %0, 1, 0, p; }" : "=r"(ok) : "r"(bar), "r"(ph) : "memory");
        if (ok) break;
        if (++lim > SPIN_LIMIT) break;
    }
}
__device__ __forceinline__ void st_async_v4(uint32_t addr, uint32_t a, uint32_t b, uint32_t c, uint32_t d, uint32_t bar) {
    asm volatile("st.async.weak.shared::cluster.mbarrier::complete_tx::bytes.v4.b32 [%0], {%1,%2,%3,%4}, [%5];" :: "r"(addr), "r"(a), "r"(b), "r"(c), "r"(d), "r"(bar) : "memory");
}
__device__ __forceinline__ void ldsm_x4(uint32_t* r, uint32_t addr) {
    asm volatile("ldmatrix.sync.aligned.m8n8.x4.shared.b16 {%0,%1,%2,%3}, [%4];" : "=r"(r[0]), "=r"(r[1]), "=r"(r[2]), "=r"(r[3]) : "r"(addr) : "memory");
}
__device__ __forceinline__ void ldsm_x4_t(uint32_t* r, uint32_t addr) {
    asm volatile("ldmatrix.sync.aligned.m8n8.x4.trans.shared.b16 {%0,%1,%2,%3}, [%4];" : "=r"(r[0]), "=r"(r[1]), "=r"(r[2]), "=r"(r[3]) : "r"(addr) : "memory");
}
__device__ __forceinline__ void mma16816(float* d, const uint32_t* a, uint32_t b0, uint32_t b1) {
    asm volatile("mma.sync.aligned.m16n8k16.row.col.f32.bf16.bf16.f32 {%0,%1,%2,%3}, {%4,%5,%6,%7}, {%8,%9}, {%0,%1,%2,%3};"
        : "+f"(d[0]), "+f"(d[1]), "+f"(d[2]), "+f"(d[3]) : "r"(a[0]), "r"(a[1]), "r"(a[2]), "r"(a[3]), "r"(b0), "r"(b1));
}
__device__ __forceinline__ uint32_t pack_bf16(float lo, float hi) {
    uint32_t r; asm("cvt.rn.bf16x2.f32 %0, %1, %2;" : "=r"(r) : "f"(hi), "f"(lo)); return r;
}
__device__ __forceinline__ float bf16r(float x) { return __bfloat162float(__float2bfloat16_rn(x)); }
__device__ __forceinline__ uint4 lds128(uint32_t a) { uint4 v; asm volatile("ld.shared.v4.u32 {%0,%1,%2,%3}, [%4];" : "=r"(v.x), "=r"(v.y), "=r"(v.z), "=r"(v.w) : "r"(a) : "memory"); return v; }
__device__ __forceinline__ void sts128(uint32_t a, uint4 v) { asm volatile("st.shared.v4.u32 [%0], {%1,%2,%3,%4};" :: "r"(a), "r"(v.x), "r"(v.y), "r"(v.z), "r"(v.w) : "memory"); }
__device__ __forceinline__ void sts32(uint32_t a, uint32_t v) { asm volatile("st.shared.u32 [%0], %1;" :: "r"(a), "r"(v) : "memory"); }
__device__ __forceinline__ void sts64(uint32_t a, uint32_t x, uint32_t y) { asm volatile("st.shared.v2.u32 [%0], {%1,%2};" :: "r"(a), "r"(x), "r"(y) : "memory"); }
__device__ __forceinline__ void sts16(uint32_t a, uint16_t v) { asm volatile("st.shared.u16 [%0], %1;" :: "r"(a), "h"(v) : "memory"); }
__device__ __forceinline__ uint2 lds64(uint32_t a) { uint2 v; asm volatile("ld.shared.v2.u32 {%0,%1}, [%2];" : "=r"(v.x), "=r"(v.y) : "r"(a) : "memory"); return v; }
__device__ __forceinline__ void cp_async16(uint32_t dst, const void* src) { asm volatile("cp.async.cg.shared.global [%0], [%1], 16;" :: "r"(dst), "l"(src) : "memory"); }
__device__ __forceinline__ void cp_async_wait_all() { asm volatile("cp.async.wait_all;" ::: "memory"); }
__device__ __forceinline__ void bar_sync(int id, int n) { asm volatile("bar.sync %0, %1;" :: "r"(id), "r"(n) : "memory"); }
__device__ __forceinline__ uint4 ld_relaxed_v4(const void* p) {
    uint4 v; asm volatile("ld.relaxed.gpu.global.v4.u32 {%0,%1,%2,%3}, [%4];" : "=r"(v.x), "=r"(v.y), "=r"(v.z), "=r"(v.w) : "l"(p) : "memory"); return v;
}
__device__ __forceinline__ void st_relaxed_v4(void* p, uint4 v) {
    asm volatile("st.relaxed.gpu.global.v4.u32 [%0], {%1,%2,%3,%4};" :: "l"(p), "r"(v.x), "r"(v.y), "r"(v.z), "r"(v.w) : "memory");
}
__device__ __forceinline__ uint32_t ld_acquire(const uint32_t* p) { uint32_t v; asm volatile("ld.acquire.gpu.global.u32 %0, [%1];" : "=r"(v) : "l"(p) : "memory"); return v; }
__device__ __forceinline__ uint32_t ld_relaxed(const uint32_t* p) { uint32_t v; asm volatile("ld.relaxed.gpu.global.u32 %0, [%1];" : "=r"(v) : "l"(p) : "memory"); return v; }
__device__ __forceinline__ void st_release(uint32_t* p, uint32_t v) { asm volatile("st.release.gpu.global.u32 [%0], %1;" :: "l"(p), "r"(v) : "memory"); }
__device__ __forceinline__ void cluster_sync_all() {
    asm volatile("barrier.cluster.arrive.release.aligned;" ::: "memory");
    asm volatile("barrier.cluster.wait.acquire.aligned;" ::: "memory");
}

__device__ bf16 g_k[2048 * 4096];
__device__ bf16 g_v[2048 * 4096];
__device__ bf16 g_km[64 * 8 * 4096];
__device__ bf16 g_vm[64 * 8 * 4096];
__device__ uint4 g_gx[2][4][16][80];
__device__ uint32_t g_kvflag[16 * 64];
__device__ uint32_t g_epoch;
struct GState {
    uint32_t done, c_mod_a, c_mod_all, unused0;
    uint32_t pad0[28];
    uint32_t ready[3], lq_claim, exh[4];
    uint32_t pad1[24];
    uint32_t cnt[96 * 8];
    uint32_t f_h[16 * 32];
    uint32_t d_at[16 * 32];
    uint32_t c_at[16 * 32];
    uint32_t c_wo[16 * 32];
    uint32_t f_h2[16 * 32];
    uint32_t c_act[16 * 32];
    uint32_t c_f2[16 * 32];
};
__device__ GState g_st;
namespace gk {
enum { T_MOD, T_L1, T_KV, T_Q, T_AT, T_WO, T_L2, T_F1, T_F2, T_FIN, T_SKIP, T_END };
#define FINE_RB 14
__host__ __device__ __forceinline__ bool fine(int rb) { return rb >= FINE_RB; }
#define WO_FINE 16
#define WO_COARSE 8
__host__ __device__ __forceinline__ int wo_split(int rb) { return fine(rb) ? WO_FINE : WO_COARSE; }
__host__ __device__ __forceinline__ int f2_split(int rb) { return fine(rb) ? 9 : 3; }
__host__ __device__ __forceinline__ int n_nt(int rb) { return fine(rb) ? 5 : 3; }
__host__ __device__ __forceinline__ int n_f1(int rb) { return fine(rb) ? 27 : 14; }
__host__ __device__ __forceinline__ int group_size(int ty, int rb) {
    switch (ty) {
        case T_AT: return 32;
        case T_WO: return n_nt(rb) * wo_split(rb);
        case T_F1: return n_f1(rb);
        case T_F2: return n_nt(rb) * f2_split(rb);
        default: return 16;
    }
}
}
__device__ __forceinline__ uint32_t atom_add_acqrel(uint32_t* p, uint32_t v) {
    uint32_t o; asm volatile("atom.acq_rel.gpu.global.add.u32 %0, [%1], %2;" : "=r"(o) : "l"(p), "r"(v) : "memory"); return o;
}
__device__ __forceinline__ void red_release_inc(uint32_t* p) { asm volatile("red.release.gpu.global.add.u32 [%0], 1;" :: "l"(p) : "memory"); }
__device__ __forceinline__ void publish_group(int ty, int rb, uint32_t) {
    const int gi = (ty - gk::T_AT) * 16 + rb;
    asm volatile("red.release.gpu.global.or.b32 [%0], %1;" :: "l"(&g_st.ready[gi >> 5]), "r"(1u << (gi & 31)) : "memory");
}
#define RT(i)

#define POLL_DELAY 300
namespace rk {
constexpr int MEM_STRIDE = 1296;
constexpr int T_STRIDE = 272;
constexpr int OFF_W = 0;
constexpr int OFF_KX = 163840;
constexpr int OFF_VX = OFF_KX + 8192;
constexpr int OFF_MEM = OFF_VX + 8192;
constexpr int OFF_Q = OFF_MEM + 10240;
constexpr int OFF_KM = OFF_Q + 8 * T_STRIDE;
constexpr int OFF_VM = OFF_KM + 8 * T_STRIDE;
constexpr int OFF_O = OFF_VM + 8 * T_STRIDE;
constexpr int OFF_SC = OFF_O + 8 * T_STRIDE;
constexpr int OFF_RED = OFF_SC + 8 * 56 * 4;
constexpr int OFF_RS = OFF_RED + 6144;
constexpr int OFF_ST = OFF_RS + 8 * 80 * 16;
constexpr int OFF_BAR = OFF_ST + 640;
constexpr int OFF_TL = OFF_BAR + 128;
constexpr int SMEM_BYTES = OFF_TL + 512;

__device__ __forceinline__ uint32_t ldg_nc(const void* p) { uint32_t v; asm volatile("ld.global.nc.u32 %0, [%1];" : "=r"(v) : "l"(p)); return v; }
__device__ __forceinline__ void load_raw(uint32_t* a, const bf16* __restrict__ W, int ld, int ka, int kb, int cb, int g, int t) {
    const bf16* p = W + (uint32_t)((ka + 2 * t) * ld + cb + 2 * g);
    const bf16* q = W + (uint32_t)((kb + 2 * t) * ld + cb + 2 * g);
    a[0] = ldg_nc(p); a[1] = ldg_nc(p + ld); a[2] = ldg_nc(q); a[3] = ldg_nc(q + ld);
}
__device__ __forceinline__ void fix_frag(uint32_t* a) {
    const uint32_t w0 = a[0], w1 = a[1], w2 = a[2], w3 = a[3];
    a[0] = __byte_perm(w0, w1, 0x5410); a[1] = __byte_perm(w0, w1, 0x7632);
    a[2] = __byte_perm(w2, w3, 0x5410); a[3] = __byte_perm(w2, w3, 0x7632);
}
__device__ __forceinline__ int chunk_src(int d, int kh, int n) { return (d - 8 * kh - n / 5) & 15; }
__device__ __forceinline__ int chunk_col(int d, int kh, int n) { const int s = chunk_src(d, kh, n); return 320 * (s & 1) + 40 * (s >> 1) + 8 * (n % 5); }
}

#define RSTEP 20
#define TL(i)
#define TG(i)

__device__ __forceinline__ void tma_load_2d(uint32_t dst, const CUtensorMap* map, int c0, int c1, uint32_t bar) {
    asm volatile("cp.async.bulk.tensor.2d.shared::cluster.global.mbarrier::complete_tx::bytes [%0], [%1, {%3, %4}], [%2];"
        :: "r"(dst), "l"(map), "r"(bar), "r"(c0), "r"(c1) : "memory");
}
__device__ __forceinline__ uint32_t movmatrix_t(uint32_t a) { uint32_t d; asm volatile("movmatrix.sync.aligned.m8n8.trans.b16 %0, %1;" : "=r"(d) : "r"(a)); return d; }
__device__ __forceinline__ void stg128(void* p, uint4 v) { asm volatile("st.global.v4.u32 [%0], {%1,%2,%3,%4};" :: "l"(p), "r"(v.x), "r"(v.y), "r"(v.z), "r"(v.w) : "memory"); }

__global__ void __launch_bounds__(256, 1)
r_kernel(const __grid_constant__ CUtensorMap tmK, const __grid_constant__ CUtensorMap tmV, const bf16* __restrict__ mem0, const bf16* __restrict__ Wq, const bf16* __restrict__ Wk, const bf16* __restrict__ Wv, const bf16* __restrict__ Wo, int wait_kv)
{
    using namespace rk;
    extern __shared__ __align__(1024) uint8_t smem[];
    const uint32_t sb = smem_u32(smem);
    const int tid = threadIdx.x, warp = tid >> 5, lane = tid & 31, g = lane >> 2, t = lane & 3;
    uint32_t rank, cid;
    asm volatile("mov.u32 %0, %%cluster_ctarank;" : "=r"(rank));
    asm volatile("mov.u32 %0, %%clusterid.x;" : "=r"(cid));
    const int hh = rank >> 1, j = rank & 1, h = cid * 8 + hh;
    const int kh = warp & 1, mb = warp >> 1;
    const uint32_t b_mem = sb + OFF_BAR, b_qkv = b_mem + 64, b_rs = b_mem + 72, b_kv = b_mem + 80;

    RT(64);
    asm volatile("griddepcontrol.launch_dependents;");
    const uint32_t epoch = ld_relaxed(&g_epoch);

    if (tid == 0) {
        for (int i = 0; i < 8; i++) mbar_init(b_mem + 8 * i, 1);
        mbar_init(b_qkv, 9); mbar_init(b_rs, 1); mbar_init(b_kv, 1);
        asm volatile("fence.mbarrier_init.release.cluster;" ::: "memory");
    }
    const uint32_t wsm = sb + OFF_W + (warp < 4 ? warp * 22528 : 4 * 22528 + (warp - 4) * 18432) + lane * 16;
    {
        const size_t co = (size_t)h * 128 + 64 * j;
        for (int i = tid; i < 640; i += 256) {
            asm volatile("prefetch.global.L2 [%0];" :: "l"(Wv + (size_t)i * 4096 + co));
            asm volatile("prefetch.global.L2 [%0];" :: "l"(Wo + ((size_t)h * 128 + i / 5) * 640 + 320 * j + (i % 5) * 64));
            asm volatile("prefetch.global.L2 [%0];" :: "l"(Wq + (size_t)i * 4096 + co));
            asm volatile("prefetch.global.L2 [%0];" :: "l"(Wk + (size_t)i * 4096 + co));
        }
    }
    uint32_t wq[20][4], wk[20][4];
    {
        const int cb = h * 128 + 64 * j + 16 * mb;
#pragma unroll
        for (int i = 0; i < 20; i++) load_raw(wq[i], Wv, 4096, chunk_col(rank, kh, 2 * i), chunk_col(rank, kh, 2 * i + 1), cb, g, t);
        const bf16* Woh = Wo + (size_t)h * 128 * 640;
        const int c3 = 320 * j + 16 * warp;
#pragma unroll
        for (int i = 0; i < 16; i++) load_raw(wk[i], Woh, 640, (i & 7) * 16, (i & 7) * 16 + 8, c3 + 128 * (i >> 3), g, t);
#pragma unroll
        for (int i = 0; i < 20; i++) { fix_frag(wq[i]); sts128(wsm + i * 512, make_uint4(wq[i][0], wq[i][1], wq[i][2], wq[i][3])); }
        if (warp < 4) {
#pragma unroll
            for (int i = 0; i < 8; i++) load_raw(wq[i], Woh, 640, i * 16, i * 16 + 8, c3 + 256, g, t);
        }
#pragma unroll
        for (int i = 0; i < 16; i++) { fix_frag(wk[i]); sts128(wsm + (20 + i) * 512, make_uint4(wk[i][0], wk[i][1], wk[i][2], wk[i][3])); }
#pragma unroll
        for (int i = 0; i < 20; i++) load_raw(wk[i], Wk, 4096, chunk_col(rank, kh, 2 * i), chunk_col(rank, kh, 2 * i + 1), cb, g, t);
        if (warp < 4) {
#pragma unroll
            for (int i = 0; i < 8; i++) { fix_frag(wq[i]); sts128(wsm + (36 + i) * 512, make_uint4(wq[i][0], wq[i][1], wq[i][2], wq[i][3])); }
        }
#pragma unroll
        for (int i = 0; i < 20; i++) load_raw(wq[i], Wq, 4096, chunk_col(rank, kh, 2 * i), chunk_col(rank, kh, 2 * i + 1), cb, g, t);
#pragma unroll
        for (int i = 0; i < 20; i++) { fix_frag(wk[i]); fix_frag(wq[i]); }
    }
    for (int i = tid; i < 640; i += 256) {
        int row = i / 80, c = i % 80;
        uint4 v = __ldg((const uint4*)(mem0 + row * 640 + c * 8));
        const int jj = c / 40, h5 = (c % 40) / 5;
        sts128(sb + OFF_MEM + (((int)rank - (2 * h5 + jj)) & 15) * 640 + row * 80 + (c % 5) * 16, v);
    }
    auto prefetch_kv = [&](int s) {
        if ((wait_kv & 1) && (s & 3) == 0) {
            const uint32_t* fk = &g_kvflag[(s >> 2) * 64 + h];
            int lim = 0;
            while (ld_acquire(fk) != epoch + 1) { if (++lim > SPIN_LIMIT) break; }
            while (ld_acquire(fk + 32) != epoch + 1) { if (++lim > SPIN_LIMIT) break; }
            asm volatile("fence.proxy.async.global;" ::: "memory");
        }
        mbar_expect_tx(b_kv, 16384);
        tma_load_2d(sb + OFF_KX, &tmK, h * 128, s * 32, b_kv);
        tma_load_2d(sb + OFF_KX + 4096, &tmK, h * 128 + 64, s * 32, b_kv);
        tma_load_2d(sb + OFF_VX, &tmV, h * 128, s * 32, b_kv);
        tma_load_2d(sb + OFF_VX + 4096, &tmV, h * 128 + 64, s * 32, b_kv);
    };
    __syncthreads();
    RT(65);
    __syncthreads();
    cluster_sync_all();

    const float scale = 0.08838834764831845f;
#define LAUNDER() int tid_ = threadIdx.x; asm volatile("" : "+r"(tid_)); const int warp = tid_ >> 5, lane = tid_ & 31, g = lane >> 2, t = lane & 3; (void)g; (void)t; (void)warp;
#define WSM() (sb + OFF_W + (warp < 4 ? warp * 22528 : 4 * 22528 + (warp - 4) * 18432) + lane * 16)

#pragma unroll 1
    for (int s = 0; s < 64; s++) {
        const uint32_t ph = s & 1;
        RT(s);
        {
            LAUNDER();
            TL(0);
            const int kh = warp & 1, mb = warp >> 1;
            const uint32_t wsm = WSM();
            const uint32_t mb0 = sb + OFF_MEM + kh * 5120 + (lane & 7) * 80 + (lane >> 3) * 16;
            const uint32_t mb1 = mb0 + ((lane >> 3) >= 1 ? 560 : 0), mb2 = mb0 + ((lane >> 3) >= 2 ? 560 : 0), mb3 = mb0 + ((lane >> 3) >= 3 ? 560 : 0);
            auto baddr = [&](int it) {
                const int r5 = (4 * it) % 5, c = ((4 * it) / 5) * 640 + r5 * 16;
                return (r5 <= 1 ? mb0 : (r5 == 4 ? mb1 : (r5 == 3 ? mb2 : mb3))) + c;
            };
            uint4 va[6];
            va[0] = lds128(wsm); va[1] = lds128(wsm + 512); va[2] = lds128(wsm + 1024); va[3] = lds128(wsm + 1536);
            if (s > 0) { mbar_wait(b_mem, ph ^ 1); mbar_wait(b_mem + 8, ph ^ 1); }
            TL(1); TG(15);
            float aq0[4] = {0, 0, 0, 0}, aq1[4] = {0, 0, 0, 0}, ak0[4] = {0, 0, 0, 0}, ak1[4] = {0, 0, 0, 0}, av0[4] = {0, 0, 0, 0}, av1[4] = {0, 0, 0, 0};
            uint32_t b[3][4];
            ldsm_x4(b[0], baddr(0)); ldsm_x4(b[1], baddr(1));
            if (tid_ == 0) {
                mbar_expect_tx(b_qkv, 3072);
                if (s < 63) mbar_expect_tx(b_rs, 10240);
            }
#pragma unroll
            for (int i = 0; i < 10; i++) {
                if (i + 2 < 10) {
                    const int it = i + 2, sl = (4 * it + 3) / 5, slp = (4 * (it - 1) + 3) / 5;
                    if (sl != slp && s > 0) mbar_wait(b_mem + 8 * sl, ph ^ 1);
                    ldsm_x4(b[(i + 2) % 3], baddr(i + 2));
                    va[(2 * i + 4) % 6] = lds128(wsm + (2 * i + 4) * 512); va[(2 * i + 5) % 6] = lds128(wsm + (2 * i + 5) * 512);
                }
                const uint32_t* bb = b[i % 3];
                mma16816(aq0, wq[2 * i], bb[0], bb[1]); mma16816(ak0, wk[2 * i], bb[0], bb[1]); mma16816(av0, (uint32_t*)&va[(2 * i) % 6], bb[0], bb[1]);
                mma16816(aq1, wq[2 * i + 1], bb[2], bb[3]); mma16816(ak1, wk[2 * i + 1], bb[2], bb[3]); mma16816(av1, (uint32_t*)&va[(2 * i + 1) % 6], bb[2], bb[3]);
            }
            float snd[4], fin[4];
#pragma unroll
            for (int i = 0; i < 4; i++) { float q = aq0[i] + aq1[i], k = ak0[i] + ak1[i]; snd[i] = kh ? q : k; fin[i] = kh ? k : q; av0[i] += av1[i]; }
            sts128(sb + OFF_RED + tid_ * 16, make_uint4(__float_as_uint(snd[0]), __float_as_uint(snd[1]), __float_as_uint(snd[2]), __float_as_uint(snd[3])));
            sts64(sb + OFF_RED + 4096 + tid_ * 8, __float_as_uint(kh ? av0[0] : av0[1]), __float_as_uint(kh ? av0[2] : av0[3]));
            bar_sync(1 + mb, 64);
            uint4 r = lds128(sb + OFF_RED + (tid_ ^ 32) * 16);
            uint2 r2 = lds64(sb + OFF_RED + 4096 + (tid_ ^ 32) * 8);
            fin[0] += __uint_as_float(r.x); fin[1] += __uint_as_float(r.y); fin[2] += __uint_as_float(r.z); fin[3] += __uint_as_float(r.w);
            float f0 = (kh ? av0[1] : av0[0]) + __uint_as_float(r2.x), f1 = (kh ? av0[3] : av0[2]) + __uint_as_float(r2.y);
            TL(2);
            const uint32_t cofs = (64 * j + 16 * mb) * 2;
            const uint32_t buf = sb + (kh ? OFF_KM : OFF_Q) + cofs;
            sts32(buf + (2 * t) * T_STRIDE + g * 4, pack_bf16(fin[0], fin[2]));
            sts32(buf + (2 * t + 1) * T_STRIDE + g * 4, pack_bf16(fin[1], fin[3]));
            sts32(sb + OFF_VM + cofs + (2 * t + kh) * T_STRIDE + g * 4, pack_bf16(f0, f1));
            __syncwarp();
            if (lane < 24) {
                const uint32_t peer_off = mapa_u32(sb, rank ^ 1) - sb;
                const int row = lane < 16 ? (lane >> 1) : 2 * ((lane - 16) >> 1) + kh;
                const uint32_t a = (lane < 16 ? buf : sb + OFF_VM + cofs) + row * T_STRIDE + (lane & 1) * 16;
                uint4 v = lds128(a);
                st_async_v4(a + peer_off, v.x, v.y, v.z, v.w, b_qkv + peer_off);
                if ((kh || lane >= 16) && !(wait_kv & 8)) {
                    bf16* dst = (lane < 16 ? g_km : g_vm) + ((uint32_t)(s * 8 + row) * 4096u + h * 128 + 64 * j + 16 * mb + (lane & 1) * 8);
                    stg128(dst, v);
                }
            }
            if (lane == 0) mbar_arrive(b_qkv);
            if (s == 0 && tid_ == 224) prefetch_kv(0);
            TL(3);
        }
        if (s == 63) {
            __syncthreads();
            if (threadIdx.x == 0 && (wait_kv & 1)) red_release_inc(&g_st.d_at[15 * 32]);
            break;
        }
        uint4 wa[8];
        {
            LAUNDER();
            const uint32_t wsm = WSM();
            if (!(wait_kv & 2) || s == 0) mbar_wait(b_kv, ph);
            if (warp >= 4 && warp < 7) {
                const int kw = warp - 4;
                uint32_t ka[8][4];
                if (kw < 2) {
                    const uint32_t kaddr = sb + OFF_KX + (16 * kw + (lane & 15)) * 128;
#pragma unroll
                    for (int i = 0; i < 8; i++) ldsm_x4(ka[i], kaddr + (i >> 2) * 4096 + ((((2 * i + (lane >> 4)) & 7) ^ (lane & 7)) << 4));
                    mbar_wait(b_qkv, ph);
                } else {
                    mbar_wait(b_qkv, ph);
                    const uint32_t kaddr = sb + OFF_KM + (lane & 7) * T_STRIDE + (lane >> 4) * 16;
#pragma unroll
                    for (int i = 0; i < 8; i++) ldsm_x4(ka[i], kaddr + i * 32);
                }
                TL(5);
                const uint32_t qa = sb + OFF_Q + (lane & 7) * T_STRIDE + (lane >> 3) * 16;
                uint32_t qb[4][4];
#pragma unroll
                for (int i = 0; i < 4; i++) ldsm_x4(qb[i], qa + i * 64);
                float s0[4] = {0, 0, 0, 0}, s1[4] = {0, 0, 0, 0}, s2[4] = {0, 0, 0, 0}, s3[4] = {0, 0, 0, 0};
                mma16816(s0, ka[0], qb[0][0], qb[0][1]); mma16816(s1, ka[1], qb[0][2], qb[0][3]);
                mma16816(s2, ka[2], qb[1][0], qb[1][1]); mma16816(s3, ka[3], qb[1][2], qb[1][3]);
                mma16816(s0, ka[4], qb[2][0], qb[2][1]); mma16816(s1, ka[5], qb[2][2], qb[2][3]);
                mma16816(s2, ka[6], qb[3][0], qb[3][1]); mma16816(s3, ka[7], qb[3][2], qb[3][3]);
                const uint32_t sc = sb + OFF_SC + (16 * kw + g) * 4 + (2 * t) * 224;
                sts32(sc, __float_as_uint(bf16r(bf16r((s0[0] + s1[0]) + (s2[0] + s3[0])) * scale)));
                sts32(sc + 224, __float_as_uint(bf16r(bf16r((s0[1] + s1[1]) + (s2[1] + s3[1])) * scale)));
                if (kw < 2) {
                    sts32(sc + 32, __float_as_uint(bf16r(bf16r((s0[2] + s1[2]) + (s2[2] + s3[2])) * scale)));
                    sts32(sc + 32 + 224, __float_as_uint(bf16r(bf16r((s0[3] + s1[3]) + (s2[3] + s3[3])) * scale)));
                }
                asm volatile("bar.arrive 6, 224;" ::: "memory");
                TL(4);
#pragma unroll
                for (int i = 0; i < 8; i++) wa[i] = lds128(wsm + (20 + i) * 512);
            } else {
#pragma unroll
                for (int i = 0; i < 8; i++) wa[i] = lds128(wsm + (20 + i) * 512);
                if (warp < 4) {
                    mbar_wait(b_qkv, ph);
                    uint32_t a0[2][4], a1[2][4], a2[2][4];
#pragma unroll
                    for (int u = 0; u < 2; u++) {
                        const int et = warp + 4 * u;
                        const uint32_t vx = sb + OFF_VX + u * 4096 + ((lane >> 4) * 8 + (lane & 7)) * 128 + ((((2 * warp + ((lane >> 3) & 1)) & 7) ^ (lane & 7)) << 4);
                        ldsm_x4_t(a0[u], vx); ldsm_x4_t(a1[u], vx + 16 * 128);
                        ldsm_x4_t(a2[u], sb + OFF_VM + (lane & 7) * T_STRIDE + (16 * et + ((lane >> 3) & 1) * 8) * 2);
                    }
                    bar_sync(6, 224);
                    TL(6);
                    float x[10];
#pragma unroll
                    for (int i = 0; i < 5; i++) { uint2 v = lds64(sb + OFF_SC + g * 224 + (8 * i + 2 * t) * 4); x[2 * i] = __uint_as_float(v.x); x[2 * i + 1] = __uint_as_float(v.y); }
                    float m = fmaxf(fmaxf(fmaxf(x[0], x[1]), fmaxf(x[2], x[3])), fmaxf(fmaxf(x[4], x[5]), fmaxf(x[6], x[7])));
                    m = fmaxf(m, fmaxf(x[8], x[9]));
                    m = fmaxf(m, __shfl_xor_sync(0xffffffff, m, 1)); m = fmaxf(m, __shfl_xor_sync(0xffffffff, m, 2));
                    float sum0 = 0, sum1 = 0;
#pragma unroll
                    for (int i = 0; i < 5; i++) { x[2 * i] = __expf(x[2 * i] - m); sum0 += x[2 * i]; x[2 * i + 1] = __expf(x[2 * i + 1] - m); sum1 += x[2 * i + 1]; }
                    float sum = sum0 + sum1;
                    sum += __shfl_xor_sync(0xffffffff, sum, 1); sum += __shfl_xor_sync(0xffffffff, sum, 2);
                    float inv = __fdividef(1.0f, sum);
                    if (inv == 123.f) TL(14);
                    TL(4);
                    uint32_t pb[5];
#pragma unroll
                    for (int i = 0; i < 5; i++) pb[i] = pack_bf16(x[2 * i] * inv, x[2 * i + 1] * inv);
#pragma unroll
                    for (int u = 0; u < 2; u++) {
                        float o0[4] = {0, 0, 0, 0}, o1[4] = {0, 0, 0, 0}, o2[4] = {0, 0, 0, 0};
                        mma16816(o0, a0[u], pb[0], pb[1]); mma16816(o1, a1[u], pb[2], pb[3]); mma16816(o2, a2[u], pb[4], 0u);
                        const uint32_t lo = movmatrix_t(pack_bf16((o0[0] + o1[0]) + o2[0], (o0[1] + o1[1]) + o2[1]));
                        const uint32_t hi = movmatrix_t(pack_bf16((o0[2] + o1[2]) + o2[2], (o0[3] + o1[3]) + o2[3]));
                        const uint32_t oa = sb + OFF_O + g * T_STRIDE + (16 * (warp + 4 * u) + 2 * t) * 2;
                        sts32(oa, lo); sts32(oa + 16, hi);
                    }
                    TL(5);
                } else {
                    if (lane < 8) mbar_expect_tx(b_mem + 8 * lane, 1280);
                }
            }
        }
        __syncthreads();
        {
            LAUNDER();
            TL(7);
            const uint32_t wsm = WSM();
            uint32_t ob[16];
            const uint32_t oa = sb + OFF_O + (lane & 7) * T_STRIDE + (lane >> 3) * 16;
#pragma unroll
            for (int i = 0; i < 4; i++) ldsm_x4(ob + 4 * i, oa + i * 64);
            const uint32_t rs_base = OFF_RS + hh * 1280 + t * 16;
            const int ntile = warp < 4 ? 3 : 2;
#pragma unroll 1
            for (int tl = 0; tl < ntile; tl++) {
                float d0[4] = {0, 0, 0, 0}, d1[4] = {0, 0, 0, 0}, d2[4] = {0, 0, 0, 0}, d3[4] = {0, 0, 0, 0};
                const bool more = tl + 1 < ntile;
                const uint32_t nx = wsm + (28 + 8 * tl) * 512;
                mma16816(d0, (uint32_t*)&wa[0], ob[0], ob[1]);   if (more) wa[0] = lds128(nx);
                mma16816(d1, (uint32_t*)&wa[1], ob[2], ob[3]);   if (more) wa[1] = lds128(nx + 512);
                mma16816(d2, (uint32_t*)&wa[2], ob[4], ob[5]);   if (more) wa[2] = lds128(nx + 1024);
                mma16816(d3, (uint32_t*)&wa[3], ob[6], ob[7]);   if (more) wa[3] = lds128(nx + 1536);
                mma16816(d0, (uint32_t*)&wa[4], ob[8], ob[9]);   if (more) wa[4] = lds128(nx + 2048);
                mma16816(d1, (uint32_t*)&wa[5], ob[10], ob[11]); if (more) wa[5] = lds128(nx + 2560);
                mma16816(d2, (uint32_t*)&wa[6], ob[12], ob[13]); if (more) wa[6] = lds128(nx + 3072);
                mma16816(d3, (uint32_t*)&wa[7], ob[14], ob[15]); if (more) wa[7] = lds128(nx + 3584);
                const int col = 16 * (warp + 8 * tl) + 2 * g; const int own = col / 40; const int cp = (col - own * 40) >> 1;
                const uint32_t dbase = mapa_u32(sb, 2 * own + j);
                st_async_v4(dbase + rs_base + cp * 64, __float_as_uint((d0[0] + d1[0]) + (d2[0] + d3[0])), __float_as_uint((d0[1] + d1[1]) + (d2[1] + d3[1])),
                            __float_as_uint((d0[2] + d1[2]) + (d2[2] + d3[2])), __float_as_uint((d0[3] + d1[3]) + (d2[3] + d3[3])), dbase + OFF_BAR + 72);
            }
            TL(8);
        }
        {
            LAUNDER();
            if (warp >= 5) {
                const int x = tid_ - 160;
                const int ot = x < 80 ? x : 79;
                const uint32_t gs = epoch * 64 + s; const uint32_t tag = (gs + 1) & 15u; const int slot = gs & 1;
                uint4* gp = &g_gx[slot][0][rank][ot];
                mbar_wait(b_rs, ph);
                TL(9); TG(12);
                uint4 u[8];
#pragma unroll
                for (int q = 0; q < 8; q++) u[q] = lds128(sb + OFF_RS + q * 1280 + ot * 16);
                float4 a;
                a.x = ((__uint_as_float(u[0].x) + __uint_as_float(u[1].x)) + (__uint_as_float(u[2].x) + __uint_as_float(u[3].x))) + ((__uint_as_float(u[4].x) + __uint_as_float(u[5].x)) + (__uint_as_float(u[6].x) + __uint_as_float(u[7].x)));
                a.y = ((__uint_as_float(u[0].y) + __uint_as_float(u[1].y)) + (__uint_as_float(u[2].y) + __uint_as_float(u[3].y))) + ((__uint_as_float(u[4].y) + __uint_as_float(u[5].y)) + (__uint_as_float(u[6].y) + __uint_as_float(u[7].y)));
                a.z = ((__uint_as_float(u[0].z) + __uint_as_float(u[1].z)) + (__uint_as_float(u[2].z) + __uint_as_float(u[3].z))) + ((__uint_as_float(u[4].z) + __uint_as_float(u[5].z)) + (__uint_as_float(u[6].z) + __uint_as_float(u[7].z)));
                a.w = ((__uint_as_float(u[0].w) + __uint_as_float(u[1].w)) + (__uint_as_float(u[2].w) + __uint_as_float(u[3].w))) + ((__uint_as_float(u[4].w) + __uint_as_float(u[5].w)) + (__uint_as_float(u[6].w) + __uint_as_float(u[7].w)));
                uint4 mine = make_uint4((__float_as_uint(a.x) & ~15u) | tag, (__float_as_uint(a.y) & ~15u) | tag, (__float_as_uint(a.z) & ~15u) | tag, (__float_as_uint(a.w) & ~15u) | tag);
                if (x < 80) st_relaxed_v4(gp + cid * 1280, mine);
                { uint32_t c0, c1; asm volatile("mov.u32 %0, %%clock;" : "=r"(c0) :: "memory"); do { asm volatile("mov.u32 %0, %%clock;" : "=r"(c1) :: "memory"); } while (c1 - c0 < POLL_DELAY); }
                uint4 v[3];
                const uint4* rp0 = gp + (cid ^ 1) * 1280; const uint4* rp1 = gp + (cid ^ 2) * 1280; const uint4* rp2 = gp + (cid ^ 3) * 1280;
                int lim = 0;
                while (true) {
                    v[0] = ld_relaxed_v4(rp0); v[1] = ld_relaxed_v4(rp1); v[2] = ld_relaxed_v4(rp2);
                    uint32_t bad = 0;
#pragma unroll
                    for (int c = 0; c < 3; c++) bad |= (v[c].x ^ tag) | (v[c].y ^ tag) | (v[c].z ^ tag) | (v[c].w ^ tag);
                    if ((bad & 15u) == 0) break;
                    if (++lim > SPIN_LIMIT) break;
                }
                float f0 = (__uint_as_float(mine.x) + __uint_as_float(v[0].x)) + (__uint_as_float(v[1].x) + __uint_as_float(v[2].x));
                float f1 = (__uint_as_float(mine.y) + __uint_as_float(v[0].y)) + (__uint_as_float(v[1].y) + __uint_as_float(v[2].y));
                float f2 = (__uint_as_float(mine.z) + __uint_as_float(v[0].z)) + (__uint_as_float(v[1].z) + __uint_as_float(v[2].z));
                float f3 = (__uint_as_float(mine.w) + __uint_as_float(v[0].w)) + (__uint_as_float(v[1].w) + __uint_as_float(v[2].w));
                const int cp = ot >> 2, tt = ot & 3;
                sts32(sb + OFF_ST + (2 * tt) * 80 + cp * 4, pack_bf16(f0, f2));
                sts32(sb + OFF_ST + (2 * tt + 1) * 80 + cp * 4, pack_bf16(f1, f3));
                TL(10); TG(13);
                bar_sync(5, 128);
                if (x < 80) {
                    const int c = x % 40, d0 = x / 40;
                    uint4 w = lds128(sb + OFF_ST + c * 16);
                    const uint32_t off = OFF_MEM + d0 * 5120 + c * 16;
#pragma unroll
                    for (int i = 0; i < 8; i++) {
                        const uint32_t rb = mapa_u32(sb, (d0 * 8 + i + rank) & 15);
                        st_async_v4(rb + off + i * 640, w.x, w.y, w.z, w.w, rb + OFF_BAR + 8 * i);
                    }
                }
            } else if (warp == 4) {
                if (lane == 0 && (s & 3) == 3 && (wait_kv & 1)) red_release_inc(&g_st.d_at[(s >> 2) * 32]);
                __syncwarp();
            } else if (warp == 3) {
                bar_sync(5, 128);
                if (lane == 0 && s < 62 && !(wait_kv & 2)) prefetch_kv(s + 1);
                __syncwarp();
            }
            TL(11);
        }
    }
    cluster_sync_all();
}

__device__ float g_mod[3840];
__device__ bf16 g_h[2048 * 640];
__device__ bf16 g_q[2048 * 4096];
__device__ bf16 g_o[2048 * 4096];
__device__ bf16 g_x1[2048 * 640];
__device__ bf16 g_h2[2048 * 640];
__device__ bf16 g_act[2048 * 1728];
__device__ float g_slab[2048 * 640];

namespace gk {
constexpr int STAGES = 4;
constexpr int STAGE_BYTES = 49152;
constexpr int OFF_SCR = STAGES * STAGE_BYTES;
constexpr int OFF_BAR = OFF_SCR + 32768;
constexpr int SMEM_BYTES = OFF_BAR + 256 + 2048;
#define PRECLAIM_RB 15
#define LOW_LEAD 3
constexpr int N_MOD = 60, N_L1 = 256, N_KV = 32, N_Q = 16;
constexpr int I_L1 = N_MOD, I_W = I_L1 + N_L1;
constexpr int N_LOW = I_W + 16 * (N_KV + N_Q);
constexpr int NFINE = 16 - FINE_RB;
constexpr int N_HIGH = 16 * (32 + 16 + 16) + (16 - NFINE) * (3 * WO_COARSE + 14 + 9) + NFINE * (5 * WO_FINE + 27 + 45);
struct Item { int type, rb, nt, ks; };
__host__ __device__ inline Item decode_low(int t) {
    Item it; it.rb = 0; it.nt = 0; it.ks = 0;
    if (t < I_L1) { it.type = T_MOD; it.nt = t; return it; }
    if (t < I_W) { it.type = T_L1; it.rb = (t - I_L1) >> 4; it.nt = (t - I_L1) & 15; return it; }
    t -= I_W;
    if (t < 64) { it.type = T_KV; it.rb = t >> 5; it.nt = t & 31; return it; }
    t -= 64;
    if (t < 14 * 48) { const int w = t / 48; t -= w * 48; if (t < 16) { it.type = T_Q; it.rb = w; it.nt = t; } else { it.type = T_KV; it.rb = w + 2; it.nt = t - 16; } return it; }
    t -= 14 * 48;
    it.type = T_Q; it.rb = 14 + (t >> 4); it.nt = t & 15; return it;
}
__device__ __forceinline__ bool is_wide(const Item& it) {
    if (it.type == T_KV || it.type == T_Q) return true;
    if (it.type == T_F1) return !fine(it.rb);
    if (it.type == T_WO || it.type == T_F2) return !fine(it.rb) && it.nt < 2;
    return false;
}
__device__ __forceinline__ int red_col(const Item& it) { return fine(it.rb) ? it.nt * 128 : it.nt * 256; }
__device__ __forceinline__ int pack_item(const Item& it) { return it.type | (it.rb << 4) | (it.nt << 8) | (it.ks << 16); }
__device__ __forceinline__ Item unpack_item(int v) { Item it; it.type = v & 15; it.rb = (v >> 4) & 15; it.nt = (v >> 8) & 255; it.ks = (v >> 16) & 255; return it; }
}

struct GParams {
    CUtensorMap tA_h, tA_o, tA_h2, tA_act, tB_q, tB_k, tB_v, tB_o, tB_g, tB_u, tB_d, tS_q, tS_k, tS_v, tS_act, tS_o, tL_q, tL_k, tL_v, tL_km, tL_vm, tR_acc;
};

__device__ __forceinline__ void wait_ge(const uint32_t* p, uint32_t target) {
    int lim = 0;
    while ((int32_t)(ld_acquire(p) - target) < 0) { __nanosleep(64); if (++lim > SPIN_LIMIT) break; }
}
__device__ __forceinline__ void red_add_relaxed(uint32_t* p, uint32_t v) { asm volatile("red.relaxed.gpu.global.add.u32 [%0], %1;" :: "l"(p), "r"(v) : "memory"); }
__device__ __forceinline__ void st_relaxed_u32(uint32_t* p, uint32_t v) { asm volatile("st.relaxed.gpu.global.u32 [%0], %1;" :: "l"(p), "r"(v) : "memory"); }
__device__ __forceinline__ void red_add_release(uint32_t* p, uint32_t v) { asm volatile("red.release.gpu.global.add.u32 [%0], %1;" :: "l"(p), "r"(v) : "memory"); }

__device__ __forceinline__ void wgmma_fence() { asm volatile("wgmma.fence.sync.aligned;" ::: "memory"); }
__device__ __forceinline__ void wgmma_commit() { asm volatile("wgmma.commit_group.sync.aligned;" ::: "memory"); }
template<int N> __device__ __forceinline__ void wgmma_wait() { asm volatile("wgmma.wait_group.sync.aligned %0;" :: "n"(N) : "memory"); }

template<int N> __device__ __forceinline__ void fence_acc(float* d) {
#pragma unroll
    for (int i = 0; i < N; i++) asm volatile("" : "+f"(d[i]) :: "memory");
}
#define ACC8(b) "+f"(d[b]), "+f"(d[b+1]), "+f"(d[b+2]), "+f"(d[b+3]), "+f"(d[b+4]), "+f"(d[b+5]), "+f"(d[b+6]), "+f"(d[b+7])
#define ACC32(b) ACC8(b), ACC8(b+8), ACC8(b+16), ACC8(b+24)
__device__ __forceinline__ void wgmma_n128(float* d, uint64_t da, uint64_t db, int scale_d) {
    asm volatile("{ .reg .pred p; setp.ne.b32 p, %66, 0;\n"
        "wgmma.mma_async.sync.aligned.m64n128k16.f32.bf16.bf16 {%0,%1,%2,%3,%4,%5,%6,%7,%8,%9,%10,%11,%12,%13,%14,%15,%16,%17,%18,%19,%20,%21,%22,%23,%24,%25,%26,%27,%28,%29,%30,%31,"
        "%32,%33,%34,%35,%36,%37,%38,%39,%40,%41,%42,%43,%44,%45,%46,%47,%48,%49,%50,%51,%52,%53,%54,%55,%56,%57,%58,%59,%60,%61,%62,%63}, %64, %65, p, 1, 1, 0, 1; }"
        : ACC32(0), ACC32(32) : "l"(da), "l"(db), "r"(scale_d));
}
__device__ __forceinline__ void wgmma_n256(float* d, uint64_t da, uint64_t db, int scale_d) {
    asm volatile("{ .reg .pred p; setp.ne.b32 p, %130, 0;\n"
        "wgmma.mma_async.sync.aligned.m64n256k16.f32.bf16.bf16 {%0,%1,%2,%3,%4,%5,%6,%7,%8,%9,%10,%11,%12,%13,%14,%15,%16,%17,%18,%19,%20,%21,%22,%23,%24,%25,%26,%27,%28,%29,%30,%31,"
        "%32,%33,%34,%35,%36,%37,%38,%39,%40,%41,%42,%43,%44,%45,%46,%47,%48,%49,%50,%51,%52,%53,%54,%55,%56,%57,%58,%59,%60,%61,%62,%63,"
        "%64,%65,%66,%67,%68,%69,%70,%71,%72,%73,%74,%75,%76,%77,%78,%79,%80,%81,%82,%83,%84,%85,%86,%87,%88,%89,%90,%91,%92,%93,%94,%95,"
        "%96,%97,%98,%99,%100,%101,%102,%103,%104,%105,%106,%107,%108,%109,%110,%111,%112,%113,%114,%115,%116,%117,%118,%119,%120,%121,%122,%123,%124,%125,%126,%127}, %128, %129, p, 1, 1, 0, 1; }"
        : ACC32(0), ACC32(32), ACC32(64), ACC32(96) : "l"(da), "l"(db), "r"(scale_d));
}
__device__ __forceinline__ uint64_t make_desc(uint32_t addr, uint32_t lbo, uint32_t sbo) {
    return (uint64_t)((addr & 0x3FFFF) >> 4) | ((uint64_t)(lbo >> 4) << 16) | ((uint64_t)(sbo >> 4) << 32) | ((uint64_t)1 << 62);
}

__device__ __forceinline__ float div_fix(float a, float b, float rb) { float q = a * rb; float r = fmaf(-q, b, a); return fmaf(r, rb, q); }
__device__ __forceinline__ void row_item(int mode, uint32_t sx, uint32_t sa, uint32_t sp, uint32_t bar_empty, float* __restrict__ acc, bf16* __restrict__ yout, bf16* __restrict__ out, int lane) {
    float x[20];
#pragma unroll
    for (int i = 0; i < 5; i++) {
        const uint2 v = lds64(sx + i * 256 + lane * 8);
        x[4 * i] = __uint_as_float(v.x << 16); x[4 * i + 1] = __uint_as_float(v.x & 0xffff0000u);
        x[4 * i + 2] = __uint_as_float(v.y << 16); x[4 * i + 3] = __uint_as_float(v.y & 0xffff0000u);
    }
    if (mode) {
#pragma unroll
        for (int i = 0; i < 5; i++) {
            const uint4 a = lds128(sa + i * 512 + lane * 16), gt = lds128(sp + i * 512 + lane * 16);
            x[4 * i] = bf16r(x[4 * i] + bf16r(__uint_as_float(gt.x) * bf16r(__uint_as_float(a.x)))); x[4 * i + 1] = bf16r(x[4 * i + 1] + bf16r(__uint_as_float(gt.y) * bf16r(__uint_as_float(a.y))));
            x[4 * i + 2] = bf16r(x[4 * i + 2] + bf16r(__uint_as_float(gt.z) * bf16r(__uint_as_float(a.z)))); x[4 * i + 3] = bf16r(x[4 * i + 3] + bf16r(__uint_as_float(gt.w) * bf16r(__uint_as_float(a.w))));
            *(uint2*)(yout + i * 128 + lane * 4) = make_uint2(pack_bf16(x[4 * i], x[4 * i + 1]), pack_bf16(x[4 * i + 2], x[4 * i + 3]));
            *(float4*)(acc + i * 128 + lane * 4) = make_float4(0.f, 0.f, 0.f, 0.f);
        }
        sp += 2560;
    }
    if (mode != 2) {
        float s = 0;
#pragma unroll
        for (int i = 0; i < 20; i++) s += x[i];
#pragma unroll
        for (int o = 16; o; o >>= 1) s += __shfl_xor_sync(0xffffffff, s, o);
        const float mean = s * (1.0f / 640.0f);
        float q = 0;
#pragma unroll
        for (int i = 0; i < 20; i++) { float d = x[i] - mean; q += d * d; }
#pragma unroll
        for (int o = 16; o; o >>= 1) q += __shfl_xor_sync(0xffffffff, q, o);
        const float m16 = bf16r(mean);
        const float sd = bf16r(sqrtf(bf16r(bf16r(q * (1.0f / 640.0f)) + 1e-5f)));
        const float rs = __frcp_rn(sd);
#pragma unroll
        for (int i = 0; i < 5; i++) {
            const uint4 sh = lds128(sp + i * 512 + lane * 16), sc = lds128(sp + 2560 + i * 512 + lane * 16);
            float y0 = bf16r(bf16r(div_fix(bf16r(x[4 * i] - m16), sd, rs)) * bf16r(1.0f + __uint_as_float(sc.x))) + __uint_as_float(sh.x);
            float y1 = bf16r(bf16r(div_fix(bf16r(x[4 * i + 1] - m16), sd, rs)) * bf16r(1.0f + __uint_as_float(sc.y))) + __uint_as_float(sh.y);
            float y2 = bf16r(bf16r(div_fix(bf16r(x[4 * i + 2] - m16), sd, rs)) * bf16r(1.0f + __uint_as_float(sc.z))) + __uint_as_float(sh.z);
            float y3 = bf16r(bf16r(div_fix(bf16r(x[4 * i + 3] - m16), sd, rs)) * bf16r(1.0f + __uint_as_float(sc.w))) + __uint_as_float(sh.w);
            *(uint2*)(out + i * 128 + lane * 4) = make_uint2(pack_bf16(y0, y1), pack_bf16(y2, y3));
        }
    }
    __syncwarp();
    if (lane == 0) mbar_arrive(bar_empty);
}

__device__ __forceinline__ float gelu_tanh(float x) {
    float u2 = x * fmaf(x * x, 2.0f * 0.7978845608028654f * 0.044715f * 1.4426950408889634f, 2.0f * 0.7978845608028654f * 1.4426950408889634f);
    float e; asm("ex2.approx.ftz.f32 %0, %1;" : "=f"(e) : "f"(-u2));
    return __fdividef(x, 1.0f + e);
}
__device__ __forceinline__ uint4 ldg128(const void* p) { uint4 v; asm volatile("ld.global.v4.u32 {%0,%1,%2,%3}, [%4];" : "=r"(v.x), "=r"(v.y), "=r"(v.z), "=r"(v.w) : "l"(p) : "memory"); return v; }
__device__ __forceinline__ float4 ldcg_f4(const float* p) { float4 v; asm volatile("ld.global.cg.v4.f32 {%0,%1,%2,%3}, [%4];" : "=f"(v.x), "=f"(v.y), "=f"(v.z), "=f"(v.w) : "l"(p) : "memory"); return v; }
__device__ __forceinline__ uint4 ldcg128(const void* p) { uint4 v; asm volatile("ld.global.cg.v4.u32 {%0,%1,%2,%3}, [%4];" : "=r"(v.x), "=r"(v.y), "=r"(v.z), "=r"(v.w) : "l"(p) : "memory"); return v; }

__device__ __forceinline__ void attn_scores(uint32_t sq, uint32_t sk, uint32_t skm, int sg, int mt, int lane, uint32_t (&p)[6][2]) {
    const int g = lane >> 2, t = lane & 3, l7 = lane & 7;
    float s[5][4];
#pragma unroll
    for (int kt = 0; kt < 5; kt++) s[kt][0] = s[kt][1] = s[kt][2] = s[kt][3] = 0.f;
    const uint32_t qrow = sq + (sg * 32 + mt * 16 + (lane & 15)) * 128;
    const uint32_t krow = sk + (sg * 32 + l7) * 128, kmrow = skm + (sg * 8 + l7) * 128;
#pragma unroll
    for (int c = 0; c < 4; c++) {
        uint32_t a0[4], a1[4];
        ldsm_x4(a0, qrow + (c >> 1) * 16384 + ((((4 * c + (lane >> 4)) & 7) ^ l7) << 4));
        ldsm_x4(a1, qrow + (c >> 1) * 16384 + ((((4 * c + 2 + (lane >> 4)) & 7) ^ l7) << 4));
        const uint32_t sw = (((4 * c + (lane >> 3)) & 7) ^ l7) << 4;
#pragma unroll
        for (int kt = 0; kt < 5; kt++) {
            uint32_t b[4];
            ldsm_x4(b, kt == 0 ? kmrow + (c >> 1) * 4096 + sw : krow + (kt - 1) * 1024 + (c >> 1) * 16384 + sw);
            mma16816(s[kt], a0, b[0], b[1]); mma16816(s[kt], a1, b[2], b[3]);
        }
    }
    const float scale = 0.08838834764831845f;
    const int r0 = mt * 16 + g, r1 = r0 + 8;
    float m0 = -INFINITY, m1 = -INFINITY;
#pragma unroll
    for (int kt = 0; kt < 5; kt++) {
#pragma unroll
        for (int i = 0; i < 4; i++) {
            float v = bf16r(bf16r(s[kt][i]) * scale);
            if (kt > 0) { int key = (kt - 1) * 8 + 2 * t + (i & 1); if (key > (i < 2 ? r0 : r1)) v = -1.0e9f; }
            s[kt][i] = v;
            if (i < 2) m0 = fmaxf(m0, v); else m1 = fmaxf(m1, v);
        }
    }
    m0 = fmaxf(m0, __shfl_xor_sync(0xffffffff, m0, 1)); m0 = fmaxf(m0, __shfl_xor_sync(0xffffffff, m0, 2));
    m1 = fmaxf(m1, __shfl_xor_sync(0xffffffff, m1, 1)); m1 = fmaxf(m1, __shfl_xor_sync(0xffffffff, m1, 2));
    float l0 = 0, l1 = 0;
#pragma unroll
    for (int kt = 0; kt < 5; kt++) {
        s[kt][0] = __expf(s[kt][0] - m0); s[kt][1] = __expf(s[kt][1] - m0); l0 += s[kt][0] + s[kt][1];
        s[kt][2] = __expf(s[kt][2] - m1); s[kt][3] = __expf(s[kt][3] - m1); l1 += s[kt][2] + s[kt][3];
    }
    l0 += __shfl_xor_sync(0xffffffff, l0, 1); l0 += __shfl_xor_sync(0xffffffff, l0, 2);
    l1 += __shfl_xor_sync(0xffffffff, l1, 1); l1 += __shfl_xor_sync(0xffffffff, l1, 2);
    const float i0 = __fdividef(1.0f, l0), i1 = __fdividef(1.0f, l1);
#pragma unroll
    for (int kt = 0; kt < 5; kt++) { p[kt][0] = pack_bf16(s[kt][0] * i0, s[kt][1] * i0); p[kt][1] = pack_bf16(s[kt][2] * i1, s[kt][3] * i1); }
    p[5][0] = p[5][1] = 0;
}
__device__ __forceinline__ void attn_pv(uint32_t sv, uint32_t svm, int sg, int lane, const uint32_t (&p)[6][2], float* d) {
    const int l7 = lane & 7, hi = (lane >> 3) & 1, ec = lane >> 4;
    const uint32_t r0 = hi ? sv + (sg * 32 + l7) * 128 : svm + (sg * 8 + l7) * 128;
    const uint32_t sub0 = hi ? 16384 : 4096;
    const uint32_t r1 = sv + (sg * 32 + 8 + hi * 8 + l7) * 128;
    const uint32_t r2 = sv + (sg * 32 + 24 + l7) * 128;
#pragma unroll
    for (int i = 0; i < 8; i++) {
        const uint32_t sw = (((2 * i + ec) & 7) ^ l7) << 4;
        uint32_t b0[4], b1[4], b2[4];
        ldsm_x4_t(b0, r0 + (i >> 2) * sub0 + sw); ldsm_x4_t(b1, r1 + (i >> 2) * 16384 + sw); ldsm_x4_t(b2, r2 + (i >> 2) * 16384 + sw);
        float* o0 = d + 8 * i; float* o1 = o0 + 4;
        o0[0] = o0[1] = o0[2] = o0[3] = o1[0] = o1[1] = o1[2] = o1[3] = 0.f;
        { uint32_t a[4] = {p[0][0], p[0][1], p[1][0], p[1][1]}; mma16816(o0, a, b0[0], b0[1]); mma16816(o1, a, b0[2], b0[3]); }
        { uint32_t a[4] = {p[2][0], p[2][1], p[3][0], p[3][1]}; mma16816(o0, a, b1[0], b1[1]); mma16816(o1, a, b1[2], b1[3]); }
        { uint32_t a[4] = {p[4][0], p[4][1], p[5][0], p[5][1]}; mma16816(o0, a, b2[0], b2[1]); mma16816(o1, a, b2[2], b2[3]); }
    }
}
__device__ __forceinline__ void bulk_load(uint32_t dst, const void* src, uint32_t bytes, uint32_t bar) {
    asm volatile("cp.async.bulk.shared::cluster.global.mbarrier::complete_tx::bytes [%0], [%1], %2, [%3];" :: "r"(dst), "l"(src), "r"(bytes), "r"(bar) : "memory");
}

__device__ __forceinline__ void stsm_x4(uint32_t addr, uint32_t a, uint32_t b, uint32_t c, uint32_t d) {
    asm volatile("stmatrix.sync.aligned.m8n8.x4.shared.b16 [%0], {%1,%2,%3,%4};" :: "r"(addr), "r"(a), "r"(b), "r"(c), "r"(d) : "memory");
}
__device__ __forceinline__ void tma_reduce_2d(const CUtensorMap* map, uint32_t src, int c0, int c1) {
    asm volatile("cp.reduce.async.bulk.tensor.2d.global.shared::cta.add.tile.bulk_group [%0, {%2, %3}], [%1];" :: "l"(map), "r"(src), "r"(c0), "r"(c1) : "memory");
}
__device__ __forceinline__ void tma_store_2d(const CUtensorMap* map, uint32_t src, int c0, int c1) {
    asm volatile("cp.async.bulk.tensor.2d.global.shared::cta.bulk_group [%0, {%2, %3}], [%1];" :: "l"(map), "r"(src), "r"(c0), "r"(c1) : "memory");
}

__global__ void __launch_bounds__(384, 1)
g_kernel(const __grid_constant__ GParams P, const bf16* __restrict__ x, const bf16* __restrict__ cvec, const bf16* __restrict__ w_mod, bf16* __restrict__ out, int nctas, int wait_r)
{
    using namespace gk;
    extern __shared__ __align__(1024) uint8_t smem[];
    const uint32_t sb = smem_u32(smem);
    const int tid = threadIdx.x, warp = tid >> 5, lane = tid & 31;
    const uint32_t b_full = sb + OFF_BAR, b_empty = b_full + 8 * STAGES, b_wfull = b_empty + 8 * STAGES, b_wempty = b_wfull + 16;
    const uint32_t b_cdone = b_wempty + 16, b_sfree = b_cdone + 16;
    volatile int* wslot = (volatile int*)(smem + OFF_BAR + 192);
    const uint32_t epoch = ld_relaxed(&g_epoch);
    const uint32_t e1 = epoch + 1;
    if (tid == 0) {
        wslot[4] = 0;
        for (int i = 0; i < STAGES; i++) { mbar_init(b_full + 8 * i, 1); mbar_init(b_empty + 8 * i, 8); }
        for (int i = 0; i < 2; i++) { mbar_init(b_wfull + 8 * i, 1); mbar_init(b_wempty + 8 * i, 9); mbar_init(b_cdone + 8 * i, 4); mbar_init(b_sfree + 8 * i, 1); }
        asm volatile("fence.mbarrier_init.release.cluster;" ::: "memory");
    }
    __syncthreads();

    if (warp < 4) {
        asm volatile("setmaxnreg.dec.sync.aligned.u32 40;");
        if (warp == 0 && lane == 0) {
            uint32_t stage = 0, sph = 1, wi = 0, wph = 1;
            bool low_left = true;
            uint32_t lx0 = 0, lx1 = 0, lx2 = 0;
            int lim = 0, issued = 0, nat = 0;
            volatile int* fin_cnt = wslot + 4;
            while (true) {
                Item it; it.type = T_END; it.rb = it.nt = it.ks = 0;
                int tk = 0; (void)tk;
                while (true) {
                    uint4 rd = ld_relaxed_v4(&g_st.ready[0]); const uint4 ex = ld_relaxed_v4(&g_st.exh[0]);
                    const uint32_t dat = nat < 16 ? ld_relaxed(&g_st.d_at[nat * 32]) : 0;
                    if (nat < 16 && dat == e1 * (wait_r ? 112u : 48u)) { if (!(rd.x >> nat & 1)) publish_group(T_AT, nat, e1); nat++; }
                    { const int na = __popc(rd.x & 0xffffu); if (na > nat) nat = na; }
                    rd.x |= (1u << nat) - 1;
                    lx0 |= ex.x; lx1 |= ex.y; lx2 |= ex.z;
                    uint32_t a0 = rd.x & ~lx0, a1 = rd.y & ~lx1, a2 = rd.z & ~lx2;
                    bool got = false;
                    if ((a0 | a1 | a2) && (rd.x >> (FINE_RB - 1) & 1) && *fin_cnt != issued) {
                        int l2 = 0; while (*fin_cnt != issued && ++l2 < SPIN_LIMIT) { }
                        continue;
                    }
                    while (a0 | a1 | a2) {
                        const int gi = a0 ? __ffs(a0) - 1 : (a1 ? 32 + __ffs(a1) - 1 : 64 + __ffs(a2) - 1);
                        const int ty = T_AT + (gi >> 4), rb = gi & 15, n = group_size(ty, rb);
                        const int i = (int)atomicAdd(&g_st.cnt[gi * 8], 1u);
                        const uint32_t bit = 1u << (gi & 31);
                        if (i >= n - 1) {
                            if (gi < 32) { lx0 |= bit; a0 &= ~bit; } else if (gi < 64) { lx1 |= bit; a1 &= ~bit; } else { lx2 |= bit; a2 &= ~bit; }
                            if (i == n - 1) asm volatile("red.relaxed.gpu.global.or.b32 [%0], %1;" :: "l"(&g_st.exh[gi >> 5]), "r"(bit) : "memory");
                        }
                        if (i < n) {
                            it.type = ty; it.rb = rb; it.nt = i;
                            if (ty == T_WO || ty == T_F2) { const int nn = n_nt(rb); it.ks = i / nn; it.nt = i - it.ks * nn; }
                            asm volatile("fence.acq_rel.gpu;" ::: "memory");
                            got = true; break;
                        }
                    }
                    if (got) {
                        break;
                    }
                    if (low_left && (int)rd.w < I_W + 64 + (nat + LOW_LEAD) * 48) {
                        const int lt = (int)atomicAdd(&g_st.lq_claim, 1u);
                        if (lt < N_LOW) {
                            it = decode_low(lt);
                            if (it.type == T_L1) wait_ge(&g_st.c_mod_a, e1 * 20);
                            else if (it.type != T_MOD) wait_ge(&g_st.f_h[it.rb * 32], e1 * 16);
                            break;
                        }
                        low_left = false;
                    }
                    if ((lx0 & lx1 & lx2) == 0xffffffffu) break;
                    if (!low_left && nat >= PRECLAIM_RB) {
                        const uint32_t rdw[3] = {rd.x, rd.y, rd.z}, lxw[3] = {lx0, lx1, lx2};
                        int gsel = -1;
#pragma unroll
                        for (int rb = 15; rb >= PRECLAIM_RB; rb--) {
#pragma unroll
                            for (int k = 5; k >= 0; k--) {
                                const int gi = k * 16 + rb;
                                const bool rdy = rdw[gi >> 5] >> (gi & 31) & 1, exq = lxw[gi >> 5] >> (gi & 31) & 1;
                                const bool pre = k == 0 ? (nat == rb) : (rdw[(gi - 16) >> 5] >> ((gi - 16) & 31) & 1);
                                if (!rdy && !exq && pre) gsel = gi;
                            }
                        }
                        if (gsel >= 0) {
                            const int gi = gsel, ty = T_AT + (gi >> 4), rb = gi & 15, n = group_size(ty, rb);
                            const int i = (int)atomicAdd(&g_st.cnt[gi * 8], 1u);
                            const uint32_t bit = 1u << (gi & 31);
                            if (i >= n - 1) {
                                if (gi < 32) lx0 |= bit; else if (gi < 64) lx1 |= bit; else lx2 |= bit;
                                if (i == n - 1) asm volatile("red.relaxed.gpu.global.or.b32 [%0], %1;" :: "l"(&g_st.exh[gi >> 5]), "r"(bit) : "memory");
                            }
                            if (i < n) {
                                it.type = ty; it.rb = rb; it.nt = i;
                                if (ty == T_WO || ty == T_F2) { const int nn = n_nt(rb); it.ks = i / nn; it.nt = i - it.ks * nn; }
                                const uint32_t* dp = (ty == T_AT ? g_st.d_at : ty == T_WO ? g_st.c_at : ty == T_L2 ? g_st.c_wo : ty == T_F1 ? g_st.f_h2 : ty == T_F2 ? g_st.c_act : g_st.c_f2) + rb * 32;
                                const uint32_t dt = e1 * (ty == T_AT ? (wait_r ? 112u : 48u) : (uint32_t)group_size(ty - 1, rb));
                                int l3 = 0;
                                while ((int32_t)(ld_acquire(dp) - dt) < 0) { if (++l3 > SPIN_LIMIT) break; }
                                break;
                            }
                            continue;
                        }
                    }
                    __nanosleep(40);
                    if (++lim > SPIN_LIMIT) break;
                }
                issued++;
                if (it.type == T_L2) wait_ge(&g_st.c_mod_all, e1 * 60);
                asm volatile("fence.proxy.async.global;" ::: "memory");
                mbar_wait(b_wempty + 8 * wi, wph);
                wslot[wi] = pack_item(it);
                mbar_arrive(b_wfull + 8 * wi);
                if (++wi == 2) { wi = 0; wph ^= 1; }
                if (it.type == T_END) break;
                int nkb = 0, kb0 = 0;
                const CUtensorMap *mA = nullptr, *mB0 = nullptr, *mB1 = nullptr; int n0 = 0, n1 = 0, nbox = 4;
                switch (it.type) {
                    case T_KV: nkb = 10; mA = &P.tA_h; mB0 = mB1 = (it.nt < 16) ? &P.tB_k : &P.tB_v; n0 = (it.nt & 15) * 256; n1 = n0 + 128; break;
                    case T_Q: nkb = 10; mA = &P.tA_h; mB0 = mB1 = &P.tB_q; n0 = it.nt * 256; n1 = n0 + 128; break;
                    case T_F1: nkb = 10; mA = &P.tA_h2; mB0 = &P.tB_g; mB1 = &P.tB_u; if (fine(it.rb)) { n0 = n1 = it.nt * 64; nbox = 2; } else n0 = n1 = it.nt * 128; break;
                    case T_WO: nkb = 64 / wo_split(it.rb); kb0 = it.ks * nkb; mA = &P.tA_o; mB0 = mB1 = &P.tB_o; n0 = red_col(it); if (is_wide(it)) n1 = n0 + 128; else { n1 = n0 + 64; nbox = 2; } break;
                    case T_F2: nkb = 27 / f2_split(it.rb); kb0 = it.ks * nkb; mA = &P.tA_act; mB0 = mB1 = &P.tB_d; n0 = red_col(it); if (is_wide(it)) n1 = n0 + 128; else { n1 = n0 + 64; nbox = 2; } break;
                    default: break;
                }
                if (it.type == T_AT) {
#pragma unroll 1
                    for (int i = 0; i < 3; i++) {
                        mbar_wait(b_empty + 8 * stage, sph);
                        const uint32_t st = sb + stage * STAGE_BYTES, bar = b_full + 8 * stage;
                        mbar_expect_tx(bar, i ? 40960 : 32768);
                        const CUtensorMap* m = i == 0 ? &P.tL_q : (i == 1 ? &P.tL_k : &P.tL_v);
                        tma_load_2d(st + 16384, m, it.nt * 128, it.rb * 128, bar);
                        tma_load_2d(st + 32768, m, it.nt * 128 + 64, it.rb * 128, bar);
                        if (i) {
                            const CUtensorMap* mm = i == 1 ? &P.tL_km : &P.tL_vm;
                            tma_load_2d(st, mm, it.nt * 128, it.rb * 32, bar);
                            tma_load_2d(st + 4096, mm, it.nt * 128 + 64, it.rb * 32, bar);
                        }
                        if (++stage == STAGES) { stage = 0; sph ^= 1; }
                    }
                } else if (it.type == T_L1 || it.type == T_L2 || it.type == T_FIN) {
                    const int mode = it.type == T_L1 ? 0 : (it.type == T_L2 ? 1 : 2);
                    const uint32_t pbytes = mode == 0 ? 5120 : (mode == 1 ? 7680 : 2560);
                    const float* psrc = g_mod + (mode == 0 ? 0 : (mode == 1 ? 2 * 640 : 5 * 640));
                    {
                        mbar_wait(b_empty + 8 * stage, sph);
                        const uint32_t st = sb + stage * STAGE_BYTES, bar = b_full + 8 * stage;
                        const size_t ro = ((size_t)it.rb * 128 + it.nt * 8) * 640;
                        mbar_expect_tx(bar, 10240 + (mode ? 20480 : 0) + pbytes);
                        bulk_load(st, (mode == 2 ? g_x1 : x) + ro, 10240, bar);
                        if (mode) bulk_load(st + 10240, g_slab + ro, 20480, bar);
                        bulk_load(st + 30720, psrc, pbytes, bar);
                        if (++stage == STAGES) { stage = 0; sph ^= 1; }
                    }
                }
                for (int kb = 0; kb < nkb; kb++) {
                    mbar_wait(b_empty + 8 * stage, sph);
                    const uint32_t st = sb + stage * STAGE_BYTES, bar = b_full + 8 * stage;
                    mbar_expect_tx(bar, 16384 + nbox * 8192);
                    const int k = (kb0 + kb) * 64;
                    tma_load_2d(st, mA, k, it.rb * 128, bar);
                    tma_load_2d(st + 16384, mB0, n0, k, bar);
                    if (nbox == 4) {
                        tma_load_2d(st + 16384 + 8192, mB0, n0 + 64, k, bar);
                        tma_load_2d(st + 16384 + 16384, mB1, n1, k, bar);
                        tma_load_2d(st + 16384 + 24576, mB1, n1 + 64, k, bar);
                    } else {
                        tma_load_2d(st + 16384 + 8192, mB1, n1, k, bar);
                    }
                    if (++stage == STAGES) { stage = 0; sph ^= 1; }
                }
            }
        } else if (warp == 1 && lane == 0) {
            uint32_t wi = 0, wph = 0, cph = 0;
            while (true) {
                mbar_wait(b_wfull + 8 * wi, wph);
                const Item it = unpack_item(wslot[wi]);
                mbar_arrive(b_wempty + 8 * wi);
                if (++wi == 2) { wi = 0; wph ^= 1; }
                if (it.type == T_END) break;
                const bool red = it.type == T_WO || it.type == T_F2;
                const bool tma = it.type == T_KV || it.type == T_Q || it.type == T_F1 || it.type == T_AT || red;
                const bool narrow = it.type == T_F1 && fine(it.rb);
                const int rounds = red ? (is_wide(it) ? 4 : 2) : ((it.type == T_KV || it.type == T_Q) ? 2 : 1);
                const CUtensorMap* mS = it.type == T_F1 ? &P.tS_act : (it.type == T_AT ? &P.tS_o : (it.type == T_Q ? &P.tS_q : (it.nt < 16 ? &P.tS_k : &P.tS_v)));
                const int gcol = red ? red_col(it) : (narrow ? it.nt * 64 : (rounds == 1 ? it.nt * 128 : (it.nt & 15) * 256));
                for (int rnd = 0; rnd < rounds; rnd++) {
                    for (int wg = 0; wg < 2; wg++) {
                        mbar_wait(b_cdone + 8 * wg, cph);
                        const uint32_t stg = sb + OFF_SCR + wg * 16384;
                        const int grow = it.rb * 128 + wg * 64;
                        if (red) {
                            tma_reduce_2d(&P.tR_acc, stg, gcol + rnd * 64, grow);
                            tma_reduce_2d(&P.tR_acc, stg + 8192, gcol + rnd * 64 + 32, grow);
                        } else if (tma) {
                            tma_store_2d(mS, stg, gcol + rnd * 128, grow);
                            if (!narrow) tma_store_2d(mS, stg + 8192, gcol + rnd * 128 + 64, grow);
                        }
                        if (tma) asm volatile("cp.async.bulk.commit_group;" ::: "memory");
                    }
                    cph ^= 1;
                    if (tma) asm volatile("cp.async.bulk.wait_group.read 0;" ::: "memory");
                    mbar_arrive(b_sfree); mbar_arrive(b_sfree + 8);
                }
                if (tma) { asm volatile("cp.async.bulk.wait_group 0;" ::: "memory"); asm volatile("fence.proxy.async.global;" ::: "memory"); }
                if (it.type <= T_KV) asm volatile("fence.acq_rel.gpu;" ::: "memory");
                uint32_t* cnt = nullptr; uint32_t tgt = 0; int nxt = -1;
                switch (it.type) {
                    case T_KV: st_relaxed_u32(&g_kvflag[it.rb * 64 + it.nt * 2], e1); st_relaxed_u32(&g_kvflag[it.rb * 64 + it.nt * 2 + 1], e1);
                    case T_Q: red_release_inc(&g_st.d_at[it.rb * 32]); break;
                    case T_MOD: if (it.nt < 20) red_add_relaxed(&g_st.c_mod_a, 1); red_add_relaxed(&g_st.c_mod_all, 1); break;
                    case T_L1: red_add_relaxed(&g_st.f_h[it.rb * 32], 1); break;
                    case T_AT: cnt = &g_st.c_at[it.rb * 32]; tgt = 32; nxt = T_WO; break;
                    case T_WO: cnt = &g_st.c_wo[it.rb * 32]; tgt = group_size(T_WO, it.rb); nxt = T_L2; break;
                    case T_L2: cnt = &g_st.f_h2[it.rb * 32]; tgt = 16; nxt = T_F1; break;
                    case T_F1: cnt = &g_st.c_act[it.rb * 32]; tgt = group_size(T_F1, it.rb); nxt = T_F2; break;
                    case T_F2: cnt = &g_st.c_f2[it.rb * 32]; tgt = group_size(T_F2, it.rb); nxt = T_FIN; break;
                    default: break;
                }
                if (cnt) { if (atom_add_acqrel(cnt, 1) + 1 == e1 * tgt) publish_group(nxt, it.rb, e1); }
            }
            uint32_t old = atom_add_acqrel(&g_st.done, 1);
            if (old + 1 == e1 * (uint32_t)nctas) {
                for (int i = 0; i < 96; i++) g_st.cnt[i * 8] = 0;
                for (int i = 0; i < 3; i++) { g_st.ready[i] = 0; g_st.exh[i] = 0; }
                g_st.lq_claim = 0;
                st_release(&g_epoch, e1);
            }
        }
    } else {
        asm volatile("setmaxnreg.inc.sync.aligned.u32 232;");
        const int ct = tid - 128, cw = warp - 4, wg = cw >> 2;
        const int g = lane >> 2, t = lane & 3;
        uint32_t stage = 0, sph = 0, wi = 0, wph = 0, fph = 1; int ndone = 0;
        while (true) {
            if (ct == 0) wslot[4] = ndone;
            ndone++;
            mbar_wait(b_wfull + 8 * wi, wph);
            const Item it = unpack_item(wslot[wi]);
            __syncwarp();
            if (lane == 0) mbar_arrive(b_wempty + 8 * wi);
            if (++wi == 2) { wi = 0; wph ^= 1; }
            if (it.type == T_END) break;
            const bool narrow = it.type == T_F1 && fine(it.rb);
            if (is_wide(it)) {
                const bool red = it.type == T_WO || it.type == T_F2;
                const int nkb = it.type == T_WO ? 64 / wo_split(it.rb) : (it.type == T_F2 ? 27 / f2_split(it.rb) : 10);
                float d[128];
#pragma unroll
                for (int i = 0; i < 128; i++) d[i] = 0.f;
                for (int kb = 0; kb < nkb; kb++) {
                    mbar_wait(b_full + 8 * stage, sph);
                    const uint32_t st = sb + stage * STAGE_BYTES;
                    const uint64_t da = make_desc(st + wg * 8192, 16, 1024), db = make_desc(st + 16384, 8192, 1024);
                    wgmma_fence();
#pragma unroll
                    for (int k = 0; k < 4; k++) wgmma_n256(d, da + k * 2, db + k * 128, 1);
                    wgmma_commit();
                    wgmma_wait<1>();
                    if (kb > 0 && lane == 0) mbar_arrive(b_empty + 8 * ((stage + STAGES - 1) % STAGES));
                    if (++stage == STAGES) { stage = 0; sph ^= 1; }
                }
                wgmma_wait<0>();
                fence_acc<128>(d);
                if (lane == 0) mbar_arrive(b_empty + 8 * ((stage + STAGES - 1) % STAGES));
                if (red) {
                    const uint32_t sbase = sb + OFF_SCR + wg * 16384 + ((cw & 3) * 16 + g) * 128 + (t & 1) * 8;
#pragma unroll
                    for (int rnd = 0; rnd < 4; rnd++) {
                        mbar_wait(b_sfree + 8 * wg, fph); fph ^= 1;
#pragma unroll
                        for (int i = 0; i < 8; i++) {
                            const float* dd = d + rnd * 32 + i * 4;
                            const uint32_t a = sbase + (i >> 2) * 8192 + ((((2 * i + (t >> 1)) & 7) ^ (g & 7)) << 4);
                            sts64(a, __float_as_uint(dd[0]), __float_as_uint(dd[1]));
                            sts64(a + 1024, __float_as_uint(dd[2]), __float_as_uint(dd[3]));
                        }
                        asm volatile("fence.proxy.async.shared::cta;" ::: "memory");
                        __syncwarp();
                        if (lane == 0) mbar_arrive(b_cdone + 8 * wg);
                    }
                    continue;
                }
                const uint32_t sbase = sb + OFF_SCR + wg * 16384 + ((cw & 3) * 16 + ((lane >> 3) & 1) * 8 + (lane & 7)) * 128;
                const int sx = lane & 7, hi = lane >> 4;
                if (it.type == T_F1) {
#pragma unroll
                    for (int i = 0; i < 64; i++) d[i] = bf16r(gelu_tanh(bf16r(d[i]))) * bf16r(d[64 + i]);
                }
#pragma unroll
                for (int rnd = 0; rnd < 2; rnd++) {
                    if (rnd == 1 && it.type == T_F1) break;
                    mbar_wait(b_sfree + 8 * wg, fph); fph ^= 1;
#pragma unroll
                    for (int i = 0; i < 8; i++) {
                        const float* dd = d + rnd * 64 + i * 8;
                        const int chunk = (2 * i + hi) & 7;
                        stsm_x4(sbase + (i >> 2) * 8192 + ((chunk ^ sx) << 4), pack_bf16(dd[0], dd[1]), pack_bf16(dd[2], dd[3]), pack_bf16(dd[4], dd[5]), pack_bf16(dd[6], dd[7]));
                    }
                    asm volatile("fence.proxy.async.shared::cta;" ::: "memory");
                    __syncwarp();
                    if (lane == 0) mbar_arrive(b_cdone + 8 * wg);
                }
                continue;
            } else if (narrow) {
                float d[64];
#pragma unroll
                for (int i = 0; i < 64; i++) d[i] = 0.f;
                const int nkb = 10;
                for (int kb = 0; kb < nkb; kb++) {
                    mbar_wait(b_full + 8 * stage, sph);
                    const uint32_t st = sb + stage * STAGE_BYTES;
                    const uint64_t da = make_desc(st + wg * 8192, 16, 1024), db = make_desc(st + 16384, 8192, 1024);
                    wgmma_fence();
#pragma unroll
                    for (int k = 0; k < 4; k++) wgmma_n128(d, da + k * 2, db + k * 128, 1);
                    wgmma_commit();
                    wgmma_wait<1>();
                    if (kb > 0 && lane == 0) mbar_arrive(b_empty + 8 * ((stage + STAGES - 1) % STAGES));
                    if (++stage == STAGES) { stage = 0; sph ^= 1; }
                }
                wgmma_wait<0>();
                fence_acc<64>(d);
                if (lane == 0) mbar_arrive(b_empty + 8 * ((stage + STAGES - 1) % STAGES));
                {
                    const uint32_t sbase = sb + OFF_SCR + wg * 16384 + ((cw & 3) * 16 + ((lane >> 3) & 1) * 8 + (lane & 7)) * 128;
#pragma unroll
                    for (int i = 0; i < 32; i++) d[i] = bf16r(gelu_tanh(bf16r(d[i]))) * bf16r(d[32 + i]);
                    mbar_wait(b_sfree + 8 * wg, fph); fph ^= 1;
#pragma unroll
                    for (int i = 0; i < 4; i++) {
                        const float* dd = d + i * 8;
                        const int chunk = 2 * i + (lane >> 4);
                        stsm_x4(sbase + ((chunk ^ (lane & 7)) << 4), pack_bf16(dd[0], dd[1]), pack_bf16(dd[2], dd[3]), pack_bf16(dd[4], dd[5]), pack_bf16(dd[6], dd[7]));
                    }
                    asm volatile("fence.proxy.async.shared::cta;" ::: "memory");
                }
            } else if (it.type == T_WO || it.type == T_F2) {
                float d[64];
#pragma unroll
                for (int i = 0; i < 64; i++) d[i] = 0.f;
                const int nkb = it.type == T_WO ? 64 / wo_split(it.rb) : 27 / f2_split(it.rb);
                for (int kb = 0; kb < nkb; kb++) {
                    mbar_wait(b_full + 8 * stage, sph);
                    const uint32_t st = sb + stage * STAGE_BYTES;
                    const uint64_t da = make_desc(st + wg * 8192, 16, 1024), db = make_desc(st + 16384, 8192, 1024);
                    wgmma_fence();
#pragma unroll
                    for (int k = 0; k < 4; k++) wgmma_n128(d, da + k * 2, db + k * 128, 1);
                    wgmma_commit();
                    wgmma_wait<1>();
                    if (kb > 0 && lane == 0) mbar_arrive(b_empty + 8 * ((stage + STAGES - 1) % STAGES));
                    if (++stage == STAGES) { stage = 0; sph ^= 1; }
                }
                wgmma_wait<0>();
                fence_acc<64>(d);
                if (lane == 0) mbar_arrive(b_empty + 8 * ((stage + STAGES - 1) % STAGES));
                {
                    const int r0 = (cw & 3) * 16 + g;
                    const uint32_t sbase = sb + OFF_SCR + wg * 16384 + r0 * 128 + (t & 1) * 8;
#pragma unroll
                    for (int rnd = 0; rnd < 2; rnd++) {
                        mbar_wait(b_sfree + 8 * wg, fph); fph ^= 1;
#pragma unroll
                        for (int i = 0; i < 8; i++) {
                            const float* dd = d + rnd * 32 + i * 4;
                            const uint32_t a = sbase + (i >> 2) * 8192 + ((((2 * i + (t >> 1)) & 7) ^ (g & 7)) << 4);
                            sts64(a, __float_as_uint(dd[0]), __float_as_uint(dd[1]));
                            sts64(a + 1024, __float_as_uint(dd[2]), __float_as_uint(dd[3]));
                        }
                        asm volatile("fence.proxy.async.shared::cta;" ::: "memory");
                        if (rnd == 0) { __syncwarp(); if (lane == 0) mbar_arrive(b_cdone + 8 * wg); }
                    }
                }
            } else if (it.type == T_AT) {
                uint32_t p[6][2];
                float d[64];
                const uint32_t s0 = stage, s1 = (stage + 1) % STAGES, s2 = (stage + 2) % STAGES;
                mbar_wait(b_full + 8 * s0, sph);
                mbar_wait(b_full + 8 * s1, s1 < s0 ? sph ^ 1 : sph);
                attn_scores(sb + s0 * STAGE_BYTES + 16384, sb + s1 * STAGE_BYTES + 16384, sb + s1 * STAGE_BYTES, cw >> 1, cw & 1, lane, p);
                __syncwarp();
                if (lane == 0) { mbar_arrive(b_empty + 8 * s0); mbar_arrive(b_empty + 8 * s1); }
                mbar_wait(b_full + 8 * s2, s2 < s0 ? sph ^ 1 : sph);
                attn_pv(sb + s2 * STAGE_BYTES + 16384, sb + s2 * STAGE_BYTES, cw >> 1, lane, p, d);
                __syncwarp();
                if (lane == 0) mbar_arrive(b_empty + 8 * s2);
                stage += 3; if (stage >= STAGES) { stage -= STAGES; sph ^= 1; }
                const uint32_t sbase = sb + OFF_SCR + wg * 16384 + ((cw & 3) * 16 + ((lane >> 3) & 1) * 8 + (lane & 7)) * 128;
                mbar_wait(b_sfree + 8 * wg, fph); fph ^= 1;
#pragma unroll
                for (int i = 0; i < 8; i++) {
                    const float* dd = d + i * 8;
                    const int chunk = (2 * i + (lane >> 4)) & 7;
                    stsm_x4(sbase + (i >> 2) * 8192 + ((chunk ^ (lane & 7)) << 4), pack_bf16(dd[0], dd[1]), pack_bf16(dd[2], dd[3]), pack_bf16(dd[4], dd[5]), pack_bf16(dd[6], dd[7]));
                }
                asm volatile("fence.proxy.async.shared::cta;" ::: "memory");
            } else if (it.type == T_L1 || it.type == T_L2 || it.type == T_FIN) {
                const int mode = it.type == T_L1 ? 0 : (it.type == T_L2 ? 1 : 2);
                {
                    const size_t ro = ((size_t)it.rb * 128 + it.nt * 8 + cw) * 640;
                    const uint32_t st = sb + stage * STAGE_BYTES;
                    mbar_wait(b_full + 8 * stage, sph);
                    row_item(mode, st + cw * 1280, st + 10240 + cw * 2560, st + 30720, b_empty + 8 * stage, g_slab + ro, (mode == 2 ? out : g_x1) + ro, (mode ? g_h2 : g_h) + ro, lane);
                    if (++stage == STAGES) { stage = 0; sph ^= 1; }
                }
            } else if (it.type == T_MOD) {
                const int kg = ct >> 3, c8 = ct & 7;
                float acc[8] = {0, 0, 0, 0, 0, 0, 0, 0};
                const bf16* wp = w_mod + (size_t)kg * 20 * 3840 + it.nt * 64 + c8 * 8;
                {
                    uint4 w[20]; float sl[20];
#pragma unroll
                    for (int i = 0; i < 20; i++) { w[i] = __ldg((const uint4*)(wp + (size_t)i * 3840)); sl[i] = __bfloat162float(cvec[kg * 20 + i]); }
#pragma unroll
                    for (int i = 0; i < 20; i++) {
                        const float s = bf16r(__fdividef(sl[i], 1.0f + __expf(-sl[i])));
                        acc[0] += s * __uint_as_float(w[i].x << 16); acc[1] += s * __uint_as_float(w[i].x & 0xffff0000u);
                        acc[2] += s * __uint_as_float(w[i].y << 16); acc[3] += s * __uint_as_float(w[i].y & 0xffff0000u);
                        acc[4] += s * __uint_as_float(w[i].z << 16); acc[5] += s * __uint_as_float(w[i].z & 0xffff0000u);
                        acc[6] += s * __uint_as_float(w[i].w << 16); acc[7] += s * __uint_as_float(w[i].w & 0xffff0000u);
                    }
                }
#pragma unroll
                for (int i = 0; i < 8; i++) { acc[i] += __shfl_xor_sync(0xffffffff, acc[i], 8); acc[i] += __shfl_xor_sync(0xffffffff, acc[i], 16); }
                float* scr = (float*)(smem + OFF_BAR + 256);
                bar_sync(3, 256);
                if (lane < 8) {
#pragma unroll
                    for (int i = 0; i < 8; i++) scr[cw * 64 + lane * 8 + i] = acc[i];
                }
                bar_sync(3, 256);
                if (ct < 64) {
                    float sum = 0;
#pragma unroll
                    for (int i = 0; i < 8; i++) sum += scr[i * 64 + ct];
                    g_mod[it.nt * 64 + ct] = bf16r(sum);
                }
            }
            if (it.type == T_MOD || it.type == T_L1 || it.type == T_L2 || it.type == T_FIN) { mbar_wait(b_sfree + 8 * wg, fph); fph ^= 1; }
            __syncwarp();
            if (lane == 0) mbar_arrive(b_cdone + 8 * wg);
        }
    }
}

typedef CUresult (*PFN_encodeTiled)(CUtensorMap*, CUtensorMapDataType, cuuint32_t, void*, const cuuint64_t*, const cuuint64_t*, const cuuint32_t*, const cuuint32_t*, CUtensorMapInterleave, CUtensorMapSwizzle, CUtensorMapL2promotion, CUtensorMapFloatOOBfill);

static void make_map(PFN_encodeTiled fn, CUtensorMap* m, const void* ptr, uint64_t inner, uint64_t outer, uint32_t box_inner, uint32_t box_outer, bool f32 = false) {
    cuuint64_t dims[2] = {inner, outer};
    cuuint64_t strides[1] = {inner * (f32 ? 4 : 2)};
    cuuint32_t box[2] = {box_inner, box_outer};
    cuuint32_t es[2] = {1, 1};
    fn(m, f32 ? CU_TENSOR_MAP_DATA_TYPE_FLOAT32 : CU_TENSOR_MAP_DATA_TYPE_BFLOAT16, 2, (void*)ptr, dims, strides, box, es, CU_TENSOR_MAP_INTERLEAVE_NONE, CU_TENSOR_MAP_SWIZZLE_128B, CU_TENSOR_MAP_L2_PROMOTION_L2_256B, CU_TENSOR_MAP_FLOAT_OOB_FILL_NONE);
}

#define G_LESS 0
static int g_dbg_mode = 0;

extern "C" void kernel_launch(void* const* d_in, const int* in_sizes, int n_in, void* d_out, int out_size) {
    const bf16* x = (const bf16*)d_in[0];
    const bf16* mem0 = (const bf16*)d_in[1];
    const bf16* Wq = (const bf16*)d_in[2];
    const bf16* Wk = (const bf16*)d_in[3];
    const bf16* Wv = (const bf16*)d_in[4];
    const bf16* Wo = (const bf16*)d_in[5];
    const bf16* Wg = (const bf16*)d_in[8];
    const bf16* Wu = (const bf16*)d_in[9];
    const bf16* Wd = (const bf16*)d_in[10];
    const bf16* cvec = (const bf16*)d_in[11];
    const bf16* wmod = (const bf16*)d_in[12];
    static PFN_encodeTiled fn = nullptr;
    static int nsm = 0;
    if (!fn) {
        cudaDriverEntryPointQueryResult qr;
        cudaGetDriverEntryPoint("cuTensorMapEncodeTiled", (void**)&fn, cudaEnableDefault, &qr);
        cudaFuncSetAttribute(r_kernel, cudaFuncAttributeMaxDynamicSharedMemorySize, rk::SMEM_BYTES);
        cudaFuncSetAttribute(r_kernel, cudaFuncAttributeNonPortableClusterSizeAllowed, 1);
        cudaFuncSetAttribute(g_kernel, cudaFuncAttributeMaxDynamicSharedMemorySize, gk::SMEM_BYTES);
        cudaDeviceGetAttribute(&nsm, cudaDevAttrMultiProcessorCount, 0);
    }
    void *ph, *po, *ph2, *pact, *pq, *pk, *pv;
    cudaGetSymbolAddress(&pq, g_q); cudaGetSymbolAddress(&pk, g_k); cudaGetSymbolAddress(&pv, g_v);
    cudaGetSymbolAddress(&ph, g_h); cudaGetSymbolAddress(&po, g_o); cudaGetSymbolAddress(&ph2, g_h2); cudaGetSymbolAddress(&pact, g_act);
    GParams P;
    make_map(fn, &P.tA_h, ph, 640, 2048, 64, 128);
    make_map(fn, &P.tA_o, po, 4096, 2048, 64, 128);
    make_map(fn, &P.tA_h2, ph2, 640, 2048, 64, 128);
    make_map(fn, &P.tA_act, pact, 1728, 2048, 64, 128);
    make_map(fn, &P.tB_q, Wq, 4096, 640, 64, 64);
    make_map(fn, &P.tB_k, Wk, 4096, 640, 64, 64);
    make_map(fn, &P.tB_v, Wv, 4096, 640, 64, 64);
    make_map(fn, &P.tB_o, Wo, 640, 4096, 64, 64);
    make_map(fn, &P.tB_g, Wg, 1728, 640, 64, 64);
    make_map(fn, &P.tB_u, Wu, 1728, 640, 64, 64);
    make_map(fn, &P.tB_d, Wd, 640, 1728, 64, 64);
    make_map(fn, &P.tS_q, pq, 4096, 2048, 64, 64);
    make_map(fn, &P.tS_k, pk, 4096, 2048, 64, 64);
    make_map(fn, &P.tS_v, pv, 4096, 2048, 64, 64);
    make_map(fn, &P.tS_act, pact, 1728, 2048, 64, 64);
    void *pkm, *pvm; cudaGetSymbolAddress(&pkm, g_km); cudaGetSymbolAddress(&pvm, g_vm);
    make_map(fn, &P.tS_o, po, 4096, 2048, 64, 64);
    make_map(fn, &P.tL_q, pq, 4096, 2048, 64, 128);
    make_map(fn, &P.tL_k, pk, 4096, 2048, 64, 128);
    make_map(fn, &P.tL_v, pv, 4096, 2048, 64, 128);
    make_map(fn, &P.tL_km, pkm, 4096, 512, 64, 32);
    make_map(fn, &P.tL_vm, pvm, 4096, 512, 64, 32);
    void* pacc; cudaGetSymbolAddress(&pacc, g_slab);
    make_map(fn, &P.tR_acc, pacc, 640, 2048, 32, 64, true);
    cudaStream_t st = cudaStreamPerThread;
    if (g_dbg_mode != 1) {
        cudaLaunchConfig_t cfg = {};
        cfg.gridDim = dim3(64); cfg.blockDim = dim3(256); cfg.dynamicSmemBytes = rk::SMEM_BYTES; cfg.stream = st;
        cudaLaunchAttribute at[1]; at[0].id = cudaLaunchAttributeClusterDimension; at[0].val.clusterDim.x = 16; at[0].val.clusterDim.y = 1; at[0].val.clusterDim.z = 1;
        cfg.attrs = at; cfg.numAttrs = 1;
        CUtensorMap tk, tv;
        make_map(fn, &tk, pk, 4096, 2048, 64, 32);
        make_map(fn, &tv, pv, 4096, 2048, 64, 32);
        cudaLaunchKernelEx(&cfg, r_kernel, tk, tv, mem0, Wq, Wk, Wv, Wo, 1);
    }
    {
        cudaLaunchConfig_t cfg = {};
        const int ng = g_dbg_mode == 1 ? nsm : nsm - G_LESS;
        cfg.gridDim = dim3(ng); cfg.blockDim = dim3(384); cfg.dynamicSmemBytes = gk::SMEM_BYTES; cfg.stream = st;
        cudaLaunchAttribute at[1]; at[0].id = cudaLaunchAttributeProgrammaticStreamSerialization; at[0].val.programmaticStreamSerializationAllowed = 1;
        cfg.attrs = at; cfg.numAttrs = g_dbg_mode == 1 ? 0 : 1;
        cudaLaunchKernelEx(&cfg, g_kernel, P, x, cvec, wmod, (bf16*)d_out, ng, g_dbg_mode == 1 ? 0 : 1);
    }
}
```

```cpp
#include <cuda_runtime.h>
#include <cuda_bf16.h>
#include <cuda.h>
#include <stdint.h>

typedef __nv_bfloat16 bf16;

__device__ __forceinline__ uint32_t smem_u32(const void* p) { return (uint32_t)__cvta_generic_to_shared(p); }
__device__ __forceinline__ uint32_t mapa_u32(uint32_t a, uint32_t r) { uint32_t o; asm volatile("mapa.shared::cluster.u32 %0, %1, %2;" : "=r"(o) : "r"(a), "r"(r)); return o; }
__device__ __forceinline__ void mbar_init(uint32_t bar, uint32_t cnt) { asm volatile("mbarrier.init.shared::cta.b64 [%0], %1;" :: "r"(bar), "r"(cnt) : "memory"); }
__device__ __forceinline__ void mbar_expect_tx(uint32_t bar, uint32_t bytes) { asm volatile("mbarrier.arrive.expect_tx.shared::cta.b64 _, [%0], %1;" :: "r"(bar), "r"(bytes) : "memory"); }
__device__ __forceinline__ void mbar_arrive(uint32_t bar) { asm volatile("mbarrier.arrive.shared::cta.b64 _, [%0];" :: "r"(bar) : "memory"); }
#define SPIN_LIMIT 400000
__device__ __forceinline__ bool mbar_try(uint32_t bar, uint32_t ph) {
    uint32_t ok;
    asm volatile("{ .reg .pred p; mbarrier.try_wait.parity.shared::cta.b64 p, [%1], %2; selp.u32 %0, 1, 0, p; }" : "=r"(ok) : "r"(bar), "r"(ph) : "memory");
    return ok;
}
__device__ __forceinline__ void mbar_wait(uint32_t bar, uint32_t ph) {
    if (mbar_try(bar, ph)) return;
#pragma unroll 1
    for (int lim = 0; lim < SPIN_LIMIT; lim++) if (mbar_try(bar, ph)) break;
}
__device__ __forceinline__ void mbar_wait_cluster(uint32_t bar, uint32_t ph) {
    uint32_t ok = 0; int lim = 0;
    while (true) {
        asm volatile("{ .reg .pred p; mbarrier.try_wait.parity.acquire.cluster.shared::cta.b64 p, [%1], %2; selp.u32 %0, 1, 0, p; }" : "=r"(ok) : "r"(bar), "r"(ph) : "memory");
        if (ok) break;
        if (++lim > SPIN_LIMIT) break;
    }
}
__device__ __forceinline__ void st_async_v4(uint32_t addr, uint32_t a, uint32_t b, uint32_t c, uint32_t d, uint32_t bar) {
    asm volatile("st.async.weak.shared::cluster.mbarrier::complete_tx::bytes.v4.b32 [%0], {%1,%2,%3,%4}, [%5];" :: "r"(addr), "r"(a), "r"(b), "r"(c), "r"(d), "r"(bar) : "memory");
}
__device__ __forceinline__ void ldsm_x4(uint32_t* r, uint32_t addr) {
    asm volatile("ldmatrix.sync.aligned.m8n8.x4.shared.b16 {%0,%1,%2,%3}, [%4];" : "=r"(r[0]), "=r"(r[1]), "=r"(r[2]), "=r"(r[3]) : "r"(addr) : "memory");
}
__device__ __forceinline__ void ldsm_x4_t(uint32_t* r, uint32_t addr) {
    asm volatile("ldmatrix.sync.aligned.m8n8.x4.trans.shared.b16 {%0,%1,%2,%3}, [%4];" : "=r"(r[0]), "=r"(r[1]), "=r"(r[2]), "=r"(r[3]) : "r"(addr) : "memory");
}
__device__ __forceinline__ void mma16816(float* d, const uint32_t* a, uint32_t b0, uint32_t b1) {
    asm volatile("mma.sync.aligned.m16n8k16.row.col.f32.bf16.bf16.f32 {%0,%1,%2,%3}, {%4,%5,%6,%7}, {%8,%9}, {%0,%1,%2,%3};"
        : "+f"(d[0]), "+f"(d[1]), "+f"(d[2]), "+f"(d[3]) : "r"(a[0]), "r"(a[1]), "r"(a[2]), "r"(a[3]), "r"(b0), "r"(b1));
}
__device__ __forceinline__ uint32_t pack_bf16(float lo, float hi) {
    uint32_t r; asm("cvt.rn.bf16x2.f32 %0, %1, %2;" : "=r"(r) : "f"(hi), "f"(lo)); return r;
}
__device__ __forceinline__ float bf16r(float x) { return __bfloat162float(__float2bfloat16_rn(x)); }
__device__ __forceinline__ uint4 lds128(uint32_t a) { uint4 v; asm volatile("ld.shared.v4.u32 {%0,%1,%2,%3}, [%4];" : "=r"(v.x), "=r"(v.y), "=r"(v.z), "=r"(v.w) : "r"(a) : "memory"); return v; }
__device__ __forceinline__ void sts128(uint32_t a, uint4 v) { asm volatile("st.shared.v4.u32 [%0], {%1,%2,%3,%4};" :: "r"(a), "r"(v.x), "r"(v.y), "r"(v.z), "r"(v.w) : "memory"); }
__device__ __forceinline__ void sts32(uint32_t a, uint32_t v) { asm volatile("st.shared.u32 [%0], %1;" :: "r"(a), "r"(v) : "memory"); }
__device__ __forceinline__ void sts64(uint32_t a, uint32_t x, uint32_t y) { asm volatile("st.shared.v2.u32 [%0], {%1,%2};" :: "r"(a), "r"(x), "r"(y) : "memory"); }
__device__ __forceinline__ void sts16(uint32_t a, uint16_t v) { asm volatile("st.shared.u16 [%0], %1;" :: "r"(a), "h"(v) : "memory"); }
__device__ __forceinline__ uint2 lds64(uint32_t a) { uint2 v; asm volatile("ld.shared.v2.u32 {%0,%1}, [%2];" : "=r"(v.x), "=r"(v.y) : "r"(a) : "memory"); return v; }
__device__ __forceinline__ void cp_async16(uint32_t dst, const void* src) { asm volatile("cp.async.cg.shared.global [%0], [%1], 16;" :: "r"(dst), "l"(src) : "memory"); }
__device__ __forceinline__ void cp_async_wait_all() { asm volatile("cp.async.wait_all;" ::: "memory"); }
__device__ __forceinline__ void bar_sync(int id, int n) { asm volatile("bar.sync %0, %1;" :: "r"(id), "r"(n) : "memory"); }
__device__ __forceinline__ uint4 ld_relaxed_v4(const void* p) {
    uint4 v; asm volatile("ld.relaxed.gpu.global.v4.u32 {%0,%1,%2,%3}, [%4];" : "=r"(v.x), "=r"(v.y), "=r"(v.z), "=r"(v.w) : "l"(p) : "memory"); return v;
}
__device__ __forceinline__ void st_relaxed_v4(void* p, uint4 v) {
    asm volatile("st.relaxed.gpu.global.v4.u32 [%0], {%1,%2,%3,%4};" :: "l"(p), "r"(v.x), "r"(v.y), "r"(v.z), "r"(v.w) : "memory");
}
__device__ __forceinline__ uint32_t ld_acquire(const uint32_t* p) { uint32_t v; asm volatile("ld.acquire.gpu.global.u32 %0, [%1];" : "=r"(v) : "l"(p) : "memory"); return v; }
__device__ __forceinline__ uint32_t ld_relaxed(const uint32_t* p) { uint32_t v; asm volatile("ld.relaxed.gpu.global.u32 %0, [%1];" : "=r"(v) : "l"(p) : "memory"); return v; }
__device__ __forceinline__ void st_release(uint32_t* p, uint32_t v) { asm volatile("st.release.gpu.global.u32 [%0], %1;" :: "l"(p), "r"(v) : "memory"); }
__device__ __forceinline__ void cluster_sync_all() {
    asm volatile("barrier.cluster.arrive.release.aligned;" ::: "memory");
    asm volatile("barrier.cluster.wait.acquire.aligned;" ::: "memory");
}

__device__ bf16 g_k[2048 * 4096];
__device__ bf16 g_v[2048 * 4096];
__device__ bf16 g_km[64 * 8 * 4096];
__device__ bf16 g_vm[64 * 8 * 4096];
__device__ uint4 g_gx[2][4][16][80];
__device__ uint32_t g_kvflag[16 * 64];
__device__ uint32_t g_epoch;
struct GState {
    uint32_t done, c_mod_a, c_mod_all, unused0;
    uint32_t pad0[28];
    uint32_t ready[3], lq_claim, exh[4];
    uint32_t pad1[24];
    uint32_t cnt[96 * 8];
    uint32_t f_h[16 * 32];
    uint32_t d_at[16 * 32];
    uint32_t c_at[16 * 32];
    uint32_t c_wo[16 * 32];
    uint32_t f_h2[16 * 32];
    uint32_t c_act[16 * 32];
    uint32_t c_f2[16 * 32];
};
__device__ GState g_st;
namespace gk {
enum { T_MOD, T_L1, T_KV, T_Q, T_AT, T_WO, T_L2, T_F1, T_F2, T_FIN, T_SKIP, T_END };
#define FINE_RB 14
__host__ __device__ __forceinline__ bool fine(int rb) { return rb >= FINE_RB; }
#define WO_FINE 16
#define WO_COARSE 8
__host__ __device__ __forceinline__ int wo_split(int rb) { return fine(rb) ? WO_FINE : WO_COARSE; }
__host__ __device__ __forceinline__ int f2_split(int rb) { return fine(rb) ? 9 : 3; }
__host__ __device__ __forceinline__ int n_nt(int rb) { return fine(rb) ? 5 : 3; }
__host__ __device__ __forceinline__ int n_f1(int rb) { return fine(rb) ? 27 : 14; }
__host__ __device__ __forceinline__ int group_size(int ty, int rb) {
    switch (ty) {
        case T_AT: return 32;
        case T_WO: return n_nt(rb) * wo_split(rb);
        case T_F1: return n_f1(rb);
        case T_F2: return n_nt(rb) * f2_split(rb);
        default: return 16;
    }
}
}
__device__ __forceinline__ uint32_t atom_add_acqrel(uint32_t* p, uint32_t v) {
    uint32_t o; asm volatile("atom.acq_rel.gpu.global.add.u32 %0, [%1], %2;" : "=r"(o) : "l"(p), "r"(v) : "memory"); return o;
}
__device__ __forceinline__ void red_release_inc(uint32_t* p) { asm volatile("red.release.gpu.global.add.u32 [%0], 1;" :: "l"(p) : "memory"); }
__device__ __forceinline__ void publish_group(int ty, int rb, uint32_t) {
    const int gi = (ty - gk::T_AT) * 16 + rb;
    asm volatile("red.release.gpu.global.or.b32 [%0], %1;" :: "l"(&g_st.ready[gi >> 5]), "r"(1u << (gi & 31)) : "memory");
}
#define RT(i)

#define POLL_DELAY 300
#define MEMSH 1
namespace rk {
constexpr int MEM_STRIDE = 1296;
constexpr int T_STRIDE = 272;
constexpr int OFF_W = 0;
constexpr int OFF_KX = 163840;
constexpr int OFF_VX = OFF_KX + 8192;
constexpr int OFF_MEM = OFF_VX + 8192;
constexpr int OFF_Q = OFF_MEM + 10240;
constexpr int OFF_KM = OFF_Q + 8 * T_STRIDE;
constexpr int OFF_VM = OFF_KM + 8 * T_STRIDE;
constexpr int OFF_O = OFF_VM + 8 * T_STRIDE;
constexpr int OFF_SC = OFF_O + 8 * T_STRIDE;
constexpr int OFF_RED = OFF_SC + 8 * 56 * 4;
constexpr int OFF_RS = OFF_RED + 6144;
constexpr int OFF_ST = OFF_RS + 8 * 80 * 16;
constexpr int OFF_BAR = OFF_ST + 640;
constexpr int OFF_TL = OFF_BAR + 128;
constexpr int SMEM_BYTES = OFF_TL + 512;

__device__ __forceinline__ uint32_t ldg_nc(const void* p) { uint32_t v; asm volatile("ld.global.nc.u32 %0, [%1];" : "=r"(v) : "l"(p)); return v; }
__device__ __forceinline__ void load_raw(uint32_t* a, const bf16* __restrict__ W, int ld, int ka, int kb, int cb, int g, int t) {
    const bf16* p = W + (uint32_t)((ka + 2 * t) * ld + cb + 2 * g);
    const bf16* q = W + (uint32_t)((kb + 2 * t) * ld + cb + 2 * g);
    a[0] = ldg_nc(p); a[1] = ldg_nc(p + ld); a[2] = ldg_nc(q); a[3] = ldg_nc(q + ld);
}
__device__ __forceinline__ void fix_frag(uint32_t* a) {
    const uint32_t w0 = a[0], w1 = a[1], w2 = a[2], w3 = a[3];
    a[0] = __byte_perm(w0, w1, 0x5410); a[1] = __byte_perm(w0, w1, 0x7632);
    a[2] = __byte_perm(w2, w3, 0x5410); a[3] = __byte_perm(w2, w3, 0x7632);
}
__device__ __forceinline__ int chunk_src(int d, int kh, int n) { return (d - 8 * kh - n / 5) & 15; }
__device__ __forceinline__ int chunk_col(int d, int kh, int n) { const int s = chunk_src(d, kh, n); return 320 * (s & 1) + 40 * (s >> 1) + 8 * (n % 5); }
}

#define RSTEP 20
#define TL(i)
#define TG(i)

__device__ __forceinline__ void tma_load_2d(uint32_t dst, const CUtensorMap* map, int c0, int c1, uint32_t bar) {
    asm volatile("cp.async.bulk.tensor.2d.shared::cluster.global.mbarrier::complete_tx::bytes [%0], [%1, {%3, %4}], [%2];"
        :: "r"(dst), "l"(map), "r"(bar), "r"(c0), "r"(c1) : "memory");
}
__device__ __forceinline__ uint32_t movmatrix_t(uint32_t a) { uint32_t d; asm volatile("movmatrix.sync.aligned.m8n8.trans.b16 %0, %1;" : "=r"(d) : "r"(a)); return d; }
__device__ __forceinline__ void stg128(void* p, uint4 v) { asm volatile("st.global.v4.u32 [%0], {%1,%2,%3,%4};" :: "l"(p), "r"(v.x), "r"(v.y), "r"(v.z), "r"(v.w) : "memory"); }

__global__ void __launch_bounds__(256, 1)
r_kernel(const __grid_constant__ CUtensorMap tmK, const __grid_constant__ CUtensorMap tmV, const bf16* __restrict__ mem0, const bf16* __restrict__ Wq, const bf16* __restrict__ Wk, const bf16* __restrict__ Wv, const bf16* __restrict__ Wo, int wait_kv)
{
    using namespace rk;
    extern __shared__ __align__(1024) uint8_t smem[];
    const uint32_t sb = smem_u32(smem);
    const int tid = threadIdx.x, warp = tid >> 5, lane = tid & 31, g = lane >> 2, t = lane & 3;
    uint32_t rank, cid;
    asm volatile("mov.u32 %0, %%cluster_ctarank;" : "=r"(rank));
    asm volatile("mov.u32 %0, %%clusterid.x;" : "=r"(cid));
    const int hh = rank >> 1, j = rank & 1, h = cid * 8 + hh;
    const int kh = warp & 1, mb = warp >> 1;
    const uint32_t b_mem = sb + OFF_BAR, b_qkv = b_mem + 64, b_rs = b_mem + 72, b_kv = b_mem + 80;

    RT(64);
    asm volatile("griddepcontrol.launch_dependents;");
    const uint32_t epoch = ld_relaxed(&g_epoch);

    if (tid == 0) {
        for (int i = 0; i < 8; i++) mbar_init(b_mem + 8 * i, 1);
        mbar_init(b_qkv, 9); mbar_init(b_rs, 1); mbar_init(b_kv, 1);
        asm volatile("fence.mbarrier_init.release.cluster;" ::: "memory");
    }
    const uint32_t wsm = sb + OFF_W + (warp < 4 ? warp * 22528 : 4 * 22528 + (warp - 4) * 18432) + lane * 16;
    {
        const size_t co = (size_t)h * 128 + 64 * j;
        for (int i = tid; i < 640; i += 256) {
            asm volatile("prefetch.global.L2 [%0];" :: "l"(Wv + (size_t)i * 4096 + co));
            asm volatile("prefetch.global.L2 [%0];" :: "l"(Wo + ((size_t)h * 128 + i / 5) * 640 + 320 * j + (i % 5) * 64));
            asm volatile("prefetch.global.L2 [%0];" :: "l"(Wq + (size_t)i * 4096 + co));
            asm volatile("prefetch.global.L2 [%0];" :: "l"(Wk + (size_t)i * 4096 + co));
        }
    }
    uint32_t wq[20][4], wk[20][4];
    {
        const int cb = h * 128 + 64 * j + 16 * mb;
#pragma unroll
        for (int i = 0; i < 20; i++) load_raw(wq[i], Wv, 4096, chunk_col(rank, kh, 2 * i), chunk_col(rank, kh, 2 * i + 1), cb, g, t);
        const bf16* Woh = Wo + (size_t)h * 128 * 640;
        const int c3 = 320 * j + 16 * warp;
#pragma unroll
        for (int i = 0; i < 16; i++) load_raw(wk[i], Woh, 640, (i & 7) * 16, (i & 7) * 16 + 8, c3 + 128 * (i >> 3), g, t);
#pragma unroll
        for (int i = 0; i < 20; i++) { fix_frag(wq[i]); sts128(wsm + i * 512, make_uint4(wq[i][0], wq[i][1], wq[i][2], wq[i][3])); }
        if (warp < 4) {
#pragma unroll
            for (int i = 0; i < 8; i++) load_raw(wq[i], Woh, 640, i * 16, i * 16 + 8, c3 + 256, g, t);
        }
#pragma unroll
        for (int i = 0; i < 16; i++) { fix_frag(wk[i]); sts128(wsm + (20 + i) * 512, make_uint4(wk[i][0], wk[i][1], wk[i][2], wk[i][3])); }
#pragma unroll
        for (int i = 0; i < 20; i++) load_raw(wk[i], Wk, 4096, chunk_col(rank, kh, 2 * i), chunk_col(rank, kh, 2 * i + 1), cb, g, t);
        if (warp < 4) {
#pragma unroll
            for (int i = 0; i < 8; i++) { fix_frag(wq[i]); sts128(wsm + (36 + i) * 512, make_uint4(wq[i][0], wq[i][1], wq[i][2], wq[i][3])); }
        }
#pragma unroll
        for (int i = 0; i < 20; i++) load_raw(wq[i], Wq, 4096, chunk_col(rank, kh, 2 * i), chunk_col(rank, kh, 2 * i + 1), cb, g, t);
#pragma unroll
        for (int i = 0; i < 20; i++) { fix_frag(wk[i]); fix_frag(wq[i]); }
    }
    for (int i = tid; i < 640; i += 256) {
        int row = i / 80, c = i % 80;
        uint4 v = __ldg((const uint4*)(mem0 + row * 640 + c * 8));
        const int jj = c / 40, h5 = (c % 40) / 5;
        sts128(sb + OFF_MEM + (((int)rank - (2 * h5 + jj)) & 15) * 640 + row * 80 + (c % 5) * 16, v);
    }
    auto prefetch_kv = [&](int s) {
        if ((wait_kv & 1) && (s & 3) == 0) {
            const uint32_t* fk = &g_kvflag[(s >> 2) * 64 + h];
            int lim = 0;
            while (ld_acquire(fk) != epoch + 1) { if (++lim > SPIN_LIMIT) break; }
            while (ld_acquire(fk + 32) != epoch + 1) { if (++lim > SPIN_LIMIT) break; }
            asm volatile("fence.proxy.async.global;" ::: "memory");
        }
        mbar_expect_tx(b_kv, 16384);
        tma_load_2d(sb + OFF_KX, &tmK, h * 128, s * 32, b_kv);
        tma_load_2d(sb + OFF_KX + 4096, &tmK, h * 128 + 64, s * 32, b_kv);
        tma_load_2d(sb + OFF_VX, &tmV, h * 128, s * 32, b_kv);
        tma_load_2d(sb + OFF_VX + 4096, &tmV, h * 128 + 64, s * 32, b_kv);
    };
    __syncthreads();
    RT(65);
    __syncthreads();
    cluster_sync_all();

    const float scale = 0.08838834764831845f;
#define LAUNDER() int tid_ = threadIdx.x; asm volatile("" : "+r"(tid_)); const int warp = tid_ >> 5, lane = tid_ & 31, g = lane >> 2, t = lane & 3; (void)g; (void)t; (void)warp;
#define WSM() (sb + OFF_W + (warp < 4 ? warp * 22528 : 4 * 22528 + (warp - 4) * 18432) + lane * 16)

#pragma unroll 1
    for (int s = 0; s < 64; s++) {
        const uint32_t ph = s & 1;
        RT(s);
        {
            LAUNDER();
            TL(0);
            const int kh = warp & 1, mb = warp >> 1;
            const uint32_t wsm = WSM();
            const uint32_t mb0 = sb + OFF_MEM + kh * 5120 + (lane & 7) * 80 + (lane >> 3) * 16;
            const uint32_t mb1 = mb0 + ((lane >> 3) >= 1 ? 560 : 0), mb2 = mb0 + ((lane >> 3) >= 2 ? 560 : 0), mb3 = mb0 + ((lane >> 3) >= 3 ? 560 : 0);
            auto baddr = [&](int it) {
                const int r5 = (4 * it) % 5, c = ((4 * it) / 5) * 640 + r5 * 16;
                return (r5 <= 1 ? mb0 : (r5 == 4 ? mb1 : (r5 == 3 ? mb2 : mb3))) + c;
            };
            uint4 va[6];
            va[0] = lds128(wsm); va[1] = lds128(wsm + 512); va[2] = lds128(wsm + 1024); va[3] = lds128(wsm + 1536);
            if (s > 0) mbar_wait(b_mem, ph ^ 1);
            TL(1); TG(15);
            float aq0[4] = {0, 0, 0, 0}, aq1[4] = {0, 0, 0, 0}, ak0[4] = {0, 0, 0, 0}, ak1[4] = {0, 0, 0, 0}, av0[4] = {0, 0, 0, 0}, av1[4] = {0, 0, 0, 0};
            uint32_t b[3][4];
            ldsm_x4(b[0], baddr(0)); ldsm_x4(b[1], baddr(1));
            if (tid_ == 0) {
                mbar_expect_tx(b_qkv, 3072);
                if (s < 63) mbar_expect_tx(b_rs, 10240);
            }
#pragma unroll
            for (int i = 0; i < 10; i++) {
                if (i + 2 < 10) {
                    const int it = i + 2, sl = ((4 * it + 3) / 5) >> MEMSH, slp = ((4 * (it - 1) + 3) / 5) >> MEMSH;
                    if (sl != slp && s > 0) mbar_wait(b_mem + 8 * sl, ph ^ 1);
                    ldsm_x4(b[(i + 2) % 3], baddr(i + 2));
                    va[(2 * i + 4) % 6] = lds128(wsm + (2 * i + 4) * 512); va[(2 * i + 5) % 6] = lds128(wsm + (2 * i + 5) * 512);
                }
                const uint32_t* bb = b[i % 3];
                mma16816(aq0, wq[2 * i], bb[0], bb[1]); mma16816(ak0, wk[2 * i], bb[0], bb[1]); mma16816(av0, (uint32_t*)&va[(2 * i) % 6], bb[0], bb[1]);
                mma16816(aq1, wq[2 * i + 1], bb[2], bb[3]); mma16816(ak1, wk[2 * i + 1], bb[2], bb[3]); mma16816(av1, (uint32_t*)&va[(2 * i + 1) % 6], bb[2], bb[3]);
            }
            float snd[4], fin[4];
#pragma unroll
            for (int i = 0; i < 4; i++) { float q = aq0[i] + aq1[i], k = ak0[i] + ak1[i]; snd[i] = kh ? q : k; fin[i] = kh ? k : q; av0[i] += av1[i]; }
            sts128(sb + OFF_RED + tid_ * 16, make_uint4(__float_as_uint(snd[0]), __float_as_uint(snd[1]), __float_as_uint(snd[2]), __float_as_uint(snd[3])));
            sts64(sb + OFF_RED + 4096 + tid_ * 8, __float_as_uint(kh ? av0[0] : av0[1]), __float_as_uint(kh ? av0[2] : av0[3]));
            bar_sync(1 + mb, 64);
            uint4 r = lds128(sb + OFF_RED + (tid_ ^ 32) * 16);
            uint2 r2 = lds64(sb + OFF_RED + 4096 + (tid_ ^ 32) * 8);
            fin[0] += __uint_as_float(r.x); fin[1] += __uint_as_float(r.y); fin[2] += __uint_as_float(r.z); fin[3] += __uint_as_float(r.w);
            float f0 = (kh ? av0[1] : av0[0]) + __uint_as_float(r2.x), f1 = (kh ? av0[3] : av0[2]) + __uint_as_float(r2.y);
            TL(2);
            const uint32_t cofs = (64 * j + 16 * mb) * 2;
            const uint32_t buf = sb + (kh ? OFF_KM : OFF_Q) + cofs;
            sts32(buf + (2 * t) * T_STRIDE + g * 4, pack_bf16(fin[0], fin[2]));
            sts32(buf + (2 * t + 1) * T_STRIDE + g * 4, pack_bf16(fin[1], fin[3]));
            sts32(sb + OFF_VM + cofs + (2 * t + kh) * T_STRIDE + g * 4, pack_bf16(f0, f1));
            __syncwarp();
            if (lane < 24) {
                const uint32_t peer_off = mapa_u32(sb, rank ^ 1) - sb;
                const int row = lane < 16 ? (lane >> 1) : 2 * ((lane - 16) >> 1) + kh;
                const uint32_t a = (lane < 16 ? buf : sb + OFF_VM + cofs) + row * T_STRIDE + (lane & 1) * 16;
                uint4 v = lds128(a);
                st_async_v4(a + peer_off, v.x, v.y, v.z, v.w, b_qkv + peer_off);
                if ((kh || lane >= 16) && !(wait_kv & 8)) {
                    bf16* dst = (lane < 16 ? g_km : g_vm) + ((uint32_t)(s * 8 + row) * 4096u + h * 128 + 64 * j + 16 * mb + (lane & 1) * 8);
                    stg128(dst, v);
                }
            }
            if (lane == 0) mbar_arrive(b_qkv);
            if (s == 0 && tid_ == 224) prefetch_kv(0);
            TL(3);
        }
        if (s == 63) {
            __syncthreads();
            if (threadIdx.x == 0 && (wait_kv & 1)) red_release_inc(&g_st.d_at[15 * 32]);
            break;
        }
        uint4 wa[8];
        {
            LAUNDER();
            const uint32_t wsm = WSM();
            if (!(wait_kv & 2) || s == 0) mbar_wait(b_kv, ph);
            if (warp >= 4 && warp < 7) {
                const int kw = warp - 4;
                uint32_t ka[8][4];
                if (kw < 2) {
                    const uint32_t kaddr = sb + OFF_KX + (16 * kw + (lane & 15)) * 128;
#pragma unroll
                    for (int i = 0; i < 8; i++) ldsm_x4(ka[i], kaddr + (i >> 2) * 4096 + ((((2 * i + (lane >> 4)) & 7) ^ (lane & 7)) << 4));
                    mbar_wait(b_qkv, ph);
                } else {
                    mbar_wait(b_qkv, ph);
                    const uint32_t kaddr = sb + OFF_KM + (lane & 7) * T_STRIDE + (lane >> 4) * 16;
#pragma unroll
                    for (int i = 0; i < 8; i++) ldsm_x4(ka[i], kaddr + i * 32);
                }
                TL(5);
                const uint32_t qa = sb + OFF_Q + (lane & 7) * T_STRIDE + (lane >> 3) * 16;
                uint32_t qb[4][4];
#pragma unroll
                for (int i = 0; i < 4; i++) ldsm_x4(qb[i], qa + i * 64);
                float s0[4] = {0, 0, 0, 0}, s1[4] = {0, 0, 0, 0}, s2[4] = {0, 0, 0, 0}, s3[4] = {0, 0, 0, 0};
                mma16816(s0, ka[0], qb[0][0], qb[0][1]); mma16816(s1, ka[1], qb[0][2], qb[0][3]);
                mma16816(s2, ka[2], qb[1][0], qb[1][1]); mma16816(s3, ka[3], qb[1][2], qb[1][3]);
                mma16816(s0, ka[4], qb[2][0], qb[2][1]); mma16816(s1, ka[5], qb[2][2], qb[2][3]);
                mma16816(s2, ka[6], qb[3][0], qb[3][1]); mma16816(s3, ka[7], qb[3][2], qb[3][3]);
                const uint32_t sc = sb + OFF_SC + (16 * kw + g) * 4 + (2 * t) * 224;
                sts32(sc, __float_as_uint(bf16r(bf16r((s0[0] + s1[0]) + (s2[0] + s3[0])) * scale)));
                sts32(sc + 224, __float_as_uint(bf16r(bf16r((s0[1] + s1[1]) + (s2[1] + s3[1])) * scale)));
                if (kw < 2) {
                    sts32(sc + 32, __float_as_uint(bf16r(bf16r((s0[2] + s1[2]) + (s2[2] + s3[2])) * scale)));
                    sts32(sc + 32 + 224, __float_as_uint(bf16r(bf16r((s0[3] + s1[3]) + (s2[3] + s3[3])) * scale)));
                }
                asm volatile("bar.arrive 6, 224;" ::: "memory");
                TL(4);
#pragma unroll
                for (int i = 0; i < 8; i++) wa[i] = lds128(wsm + (20 + i) * 512);
            } else {
#pragma unroll
                for (int i = 0; i < 8; i++) wa[i] = lds128(wsm + (20 + i) * 512);
                if (warp < 4) {
                    mbar_wait(b_qkv, ph);
                    uint32_t a0[2][4], a1[2][4], a2[2][4];
#pragma unroll
                    for (int u = 0; u < 2; u++) {
                        const int et = warp + 4 * u;
                        const uint32_t vx = sb + OFF_VX + u * 4096 + ((lane >> 4) * 8 + (lane & 7)) * 128 + ((((2 * warp + ((lane >> 3) & 1)) & 7) ^ (lane & 7)) << 4);
                        ldsm_x4_t(a0[u], vx); ldsm_x4_t(a1[u], vx + 16 * 128);
                        ldsm_x4_t(a2[u], sb + OFF_VM + (lane & 7) * T_STRIDE + (16 * et + ((lane >> 3) & 1) * 8) * 2);
                    }
                    bar_sync(6, 224);
                    TL(6);
                    float x[10];
#pragma unroll
                    for (int i = 0; i < 5; i++) { uint2 v = lds64(sb + OFF_SC + g * 224 + (8 * i + 2 * t) * 4); x[2 * i] = __uint_as_float(v.x); x[2 * i + 1] = __uint_as_float(v.y); }
                    float m = fmaxf(fmaxf(fmaxf(x[0], x[1]), fmaxf(x[2], x[3])), fmaxf(fmaxf(x[4], x[5]), fmaxf(x[6], x[7])));
                    m = fmaxf(m, fmaxf(x[8], x[9]));
                    m = fmaxf(m, __shfl_xor_sync(0xffffffff, m, 1)); m = fmaxf(m, __shfl_xor_sync(0xffffffff, m, 2));
                    float sum0 = 0, sum1 = 0;
#pragma unroll
                    for (int i = 0; i < 5; i++) { x[2 * i] = __expf(x[2 * i] - m); sum0 += x[2 * i]; x[2 * i + 1] = __expf(x[2 * i + 1] - m); sum1 += x[2 * i + 1]; }
                    float sum = sum0 + sum1;
                    sum += __shfl_xor_sync(0xffffffff, sum, 1); sum += __shfl_xor_sync(0xffffffff, sum, 2);
                    float inv = __fdividef(1.0f, sum);
                    if (inv == 123.f) TL(14);
                    TL(4);
                    uint32_t pb[5];
#pragma unroll
                    for (int i = 0; i < 5; i++) pb[i] = pack_bf16(x[2 * i] * inv, x[2 * i + 1] * inv);
#pragma unroll
                    for (int u = 0; u < 2; u++) {
                        float o0[4] = {0, 0, 0, 0}, o1[4] = {0, 0, 0, 0}, o2[4] = {0, 0, 0, 0};
                        mma16816(o0, a0[u], pb[0], pb[1]); mma16816(o1, a1[u], pb[2], pb[3]); mma16816(o2, a2[u], pb[4], 0u);
                        const uint32_t lo = movmatrix_t(pack_bf16((o0[0] + o1[0]) + o2[0], (o0[1] + o1[1]) + o2[1]));
                        const uint32_t hi = movmatrix_t(pack_bf16((o0[2] + o1[2]) + o2[2], (o0[3] + o1[3]) + o2[3]));
                        const uint32_t oa = sb + OFF_O + g * T_STRIDE + (16 * (warp + 4 * u) + 2 * t) * 2;
                        sts32(oa, lo); sts32(oa + 16, hi);
                    }
                    TL(5);
                } else {
                    if (lane < (8 >> MEMSH)) mbar_expect_tx(b_mem + 8 * lane, 1280 << MEMSH);
                }
            }
        }
        __syncthreads();
        {
            LAUNDER();
            TL(7);
            const uint32_t wsm = WSM();
            uint32_t ob[16];
            const uint32_t oa = sb + OFF_O + (lane & 7) * T_STRIDE + (lane >> 3) * 16;
#pragma unroll
            for (int i = 0; i < 4; i++) ldsm_x4(ob + 4 * i, oa + i * 64);
            const uint32_t rs_base = OFF_RS + hh * 1280 + t * 16;
            const int ntile = warp < 4 ? 3 : 2;
#pragma unroll 1
            for (int tl = 0; tl < ntile; tl++) {
                float d0[4] = {0, 0, 0, 0}, d1[4] = {0, 0, 0, 0}, d2[4] = {0, 0, 0, 0}, d3[4] = {0, 0, 0, 0};
                const bool more = tl + 1 < ntile;
                const uint32_t nx = wsm + (28 + 8 * tl) * 512;
                mma16816(d0, (uint32_t*)&wa[0], ob[0], ob[1]);   if (more) wa[0] = lds128(nx);
                mma16816(d1, (uint32_t*)&wa[1], ob[2], ob[3]);   if (more) wa[1] = lds128(nx + 512);
                mma16816(d2, (uint32_t*)&wa[2], ob[4], ob[5]);   if (more) wa[2] = lds128(nx + 1024);
                mma16816(d3, (uint32_t*)&wa[3], ob[6], ob[7]);   if (more) wa[3] = lds128(nx + 1536);
                mma16816(d0, (uint32_t*)&wa[4], ob[8], ob[9]);   if (more) wa[4] = lds128(nx + 2048);
                mma16816(d1, (uint32_t*)&wa[5], ob[10], ob[11]); if (more) wa[5] = lds128(nx + 2560);
                mma16816(d2, (uint32_t*)&wa[6], ob[12], ob[13]); if (more) wa[6] = lds128(nx + 3072);
                mma16816(d3, (uint32_t*)&wa[7], ob[14], ob[15]); if (more) wa[7] = lds128(nx + 3584);
                const int col = 16 * (warp + 8 * tl) + 2 * g; const int own = col / 40; const int cp = (col - own * 40) >> 1;
                const uint32_t dbase = mapa_u32(sb, 2 * own + j);
                st_async_v4(dbase + rs_base + cp * 64, __float_as_uint((d0[0] + d1[0]) + (d2[0] + d3[0])), __float_as_uint((d0[1] + d1[1]) + (d2[1] + d3[1])),
                            __float_as_uint((d0[2] + d1[2]) + (d2[2] + d3[2])), __float_as_uint((d0[3] + d1[3]) + (d2[3] + d3[3])), dbase + OFF_BAR + 72);
            }
            TL(8);
        }
        {
            LAUNDER();
            if (warp >= 5) {
                const int x = tid_ - 160;
                const int ot = x < 80 ? x : 79;
                const uint32_t gs = epoch * 64 + s; const uint32_t tag = (gs + 1) & 15u; const int slot = gs & 1;
                uint4* gp = &g_gx[slot][0][rank][ot];
                mbar_wait(b_rs, ph);
                TL(9); TG(12);
                uint4 u[8];
#pragma unroll
                for (int q = 0; q < 8; q++) u[q] = lds128(sb + OFF_RS + q * 1280 + ot * 16);
                float4 a;
                a.x = ((__uint_as_float(u[0].x) + __uint_as_float(u[1].x)) + (__uint_as_float(u[2].x) + __uint_as_float(u[3].x))) + ((__uint_as_float(u[4].x) + __uint_as_float(u[5].x)) + (__uint_as_float(u[6].x) + __uint_as_float(u[7].x)));
                a.y = ((__uint_as_float(u[0].y) + __uint_as_float(u[1].y)) + (__uint_as_float(u[2].y) + __uint_as_float(u[3].y))) + ((__uint_as_float(u[4].y) + __uint_as_float(u[5].y)) + (__uint_as_float(u[6].y) + __uint_as_float(u[7].y)));
                a.z = ((__uint_as_float(u[0].z) + __uint_as_float(u[1].z)) + (__uint_as_float(u[2].z) + __uint_as_float(u[3].z))) + ((__uint_as_float(u[4].z) + __uint_as_float(u[5].z)) + (__uint_as_float(u[6].z) + __uint_as_float(u[7].z)));
                a.w = ((__uint_as_float(u[0].w) + __uint_as_float(u[1].w)) + (__uint_as_float(u[2].w) + __uint_as_float(u[3].w))) + ((__uint_as_float(u[4].w) + __uint_as_float(u[5].w)) + (__uint_as_float(u[6].w) + __uint_as_float(u[7].w)));
                uint4 mine = make_uint4((__float_as_uint(a.x) & ~15u) | tag, (__float_as_uint(a.y) & ~15u) | tag, (__float_as_uint(a.z) & ~15u) | tag, (__float_as_uint(a.w) & ~15u) | tag);
                if (x < 80) st_relaxed_v4(gp + cid * 1280, mine);
                { uint32_t c0, c1; asm volatile("mov.u32 %0, %%clock;" : "=r"(c0) :: "memory"); do { asm volatile("mov.u32 %0, %%clock;" : "=r"(c1) :: "memory"); } while (c1 - c0 < POLL_DELAY); }
                uint4 v[3];
                const uint4* rp0 = gp + (cid ^ 1) * 1280; const uint4* rp1 = gp + (cid ^ 2) * 1280; const uint4* rp2 = gp + (cid ^ 3) * 1280;
                int lim = 0;
                while (true) {
                    v[0] = ld_relaxed_v4(rp0); v[1] = ld_relaxed_v4(rp1); v[2] = ld_relaxed_v4(rp2);
                    uint32_t bad = 0;
#pragma unroll
                    for (int c = 0; c < 3; c++) bad |= (v[c].x ^ tag) | (v[c].y ^ tag) | (v[c].z ^ tag) | (v[c].w ^ tag);
                    if ((bad & 15u) == 0) break;
                    if (++lim > SPIN_LIMIT) break;
                }
                float f0 = (__uint_as_float(mine.x) + __uint_as_float(v[0].x)) + (__uint_as_float(v[1].x) + __uint_as_float(v[2].x));
                float f1 = (__uint_as_float(mine.y) + __uint_as_float(v[0].y)) + (__uint_as_float(v[1].y) + __uint_as_float(v[2].y));
                float f2 = (__uint_as_float(mine.z) + __uint_as_float(v[0].z)) + (__uint_as_float(v[1].z) + __uint_as_float(v[2].z));
                float f3 = (__uint_as_float(mine.w) + __uint_as_float(v[0].w)) + (__uint_as_float(v[1].w) + __uint_as_float(v[2].w));
                const int cp = ot >> 2, tt = ot & 3;
                sts32(sb + OFF_ST + (2 * tt) * 80 + cp * 4, pack_bf16(f0, f2));
                sts32(sb + OFF_ST + (2 * tt + 1) * 80 + cp * 4, pack_bf16(f1, f3));
                TL(10); TG(13);
                bar_sync(5, 128);
                if (x < 80) {
                    const int c = x % 40, d0 = x / 40;
                    uint4 w = lds128(sb + OFF_ST + c * 16);
                    const uint32_t off = OFF_MEM + d0 * 5120 + c * 16;
#pragma unroll
                    for (int i = 0; i < 8; i++) {
                        const uint32_t rb = mapa_u32(sb, (d0 * 8 + i + rank) & 15);
                        st_async_v4(rb + off + i * 640, w.x, w.y, w.z, w.w, rb + OFF_BAR + 8 * (i >> MEMSH));
                    }
                }
            } else if (warp == 4) {
                if (lane == 0 && (s & 3) == 3 && (wait_kv & 1)) red_release_inc(&g_st.d_at[(s >> 2) * 32]);
                __syncwarp();
            } else if (warp == 3) {
                bar_sync(5, 128);
                if (lane == 0 && s < 62 && !(wait_kv & 2)) prefetch_kv(s + 1);
                __syncwarp();
            }
            TL(11);
        }
    }
    cluster_sync_all();
}

__device__ float g_mod[3840];
__device__ bf16 g_h[2048 * 640];
__device__ bf16 g_q[2048 * 4096];
__device__ bf16 g_o[2048 * 4096];
__device__ bf16 g_x1[2048 * 640];
__device__ bf16 g_h2[2048 * 640];
__device__ bf16 g_act[2048 * 1728];
__device__ float g_slab[2048 * 640];

namespace gk {
constexpr int STAGES = 4;
constexpr int STAGE_BYTES = 49152;
constexpr int OFF_SCR = STAGES * STAGE_BYTES;
constexpr int OFF_BAR = OFF_SCR + 32768;
constexpr int SMEM_BYTES = OFF_BAR + 256 + 2048;
#define PRECLAIM_RB 15
#define LOW_LEAD 3
constexpr int N_MOD = 60, N_L1 = 256, N_KV = 32, N_Q = 16;
constexpr int I_L1 = N_MOD, I_W = I_L1 + N_L1;
constexpr int N_LOW = I_W + 16 * (N_KV + N_Q) + 32;
constexpr int NFINE = 16 - FINE_RB;
constexpr int N_HIGH = 16 * (32 + 16 + 16) + (16 - NFINE) * (3 * WO_COARSE + 14 + 9) + NFINE * (5 * WO_FINE + 27 + 45);
struct Item { int type, rb, nt, ks; };
__host__ __device__ inline Item decode_low(int t) {
    Item it; it.rb = 0; it.nt = 0; it.ks = 0;
    if (t < I_L1) { it.type = T_MOD; it.nt = t; return it; }
    if (t < I_L1 + 16) { it.type = T_L1; it.rb = 0; it.nt = t - I_L1; return it; }
    if (t < I_L1 + 80) { it.type = T_KV; it.rb = 0; it.nt = t - I_L1 - 16; it.ks = 1; return it; }
    if (t < I_W + 64) { it.type = T_L1; it.rb = (t - I_L1 - 64) >> 4; it.nt = (t - I_L1 - 64) & 15; return it; }
    t -= I_W;
    if (t < 96) { it.type = T_KV; it.rb = 1; it.nt = t - 64; return it; }
    t -= 96;
    if (t < 14 * 48) { const int w = t / 48; t -= w * 48; if (t < 16) { it.type = T_Q; it.rb = w; it.nt = t; } else { it.type = T_KV; it.rb = w + 2; it.nt = t - 16; } return it; }
    t -= 14 * 48;
    it.type = T_Q; it.rb = 14 + (t >> 4); it.nt = t & 15; return it;
}
__device__ __forceinline__ bool is_wide(const Item& it) {
    if (it.type == T_KV || it.type == T_Q) return it.ks == 0;
    if (it.type == T_F1) return !fine(it.rb);
    if (it.type == T_WO || it.type == T_F2) return !fine(it.rb) && it.nt < 2;
    return false;
}
__device__ __forceinline__ int red_col(const Item& it) { return fine(it.rb) ? it.nt * 128 : it.nt * 256; }
__device__ __forceinline__ int pack_item(const Item& it) { return it.type | (it.rb << 4) | (it.nt << 8) | (it.ks << 16); }
__device__ __forceinline__ Item unpack_item(int v) { Item it; it.type = v & 15; it.rb = (v >> 4) & 15; it.nt = (v >> 8) & 255; it.ks = (v >> 16) & 255; return it; }
}

struct GParams {
    CUtensorMap tA_h, tA_o, tA_h2, tA_act, tB_q, tB_k, tB_v, tB_o, tB_g, tB_u, tB_d, tS_q, tS_k, tS_v, tS_act, tS_o, tL_q, tL_k, tL_v, tL_km, tL_vm, tR_acc;
};

__device__ __forceinline__ void wait_ge(const uint32_t* p, uint32_t target) {
    int lim = 0;
    while ((int32_t)(ld_acquire(p) - target) < 0) { __nanosleep(64); if (++lim > SPIN_LIMIT) break; }
}
__device__ __forceinline__ void red_add_relaxed(uint32_t* p, uint32_t v) { asm volatile("red.relaxed.gpu.global.add.u32 [%0], %1;" :: "l"(p), "r"(v) : "memory"); }
__device__ __forceinline__ void st_relaxed_u32(uint32_t* p, uint32_t v) { asm volatile("st.relaxed.gpu.global.u32 [%0], %1;" :: "l"(p), "r"(v) : "memory"); }
__device__ __forceinline__ void red_add_release(uint32_t* p, uint32_t v) { asm volatile("red.release.gpu.global.add.u32 [%0], %1;" :: "l"(p), "r"(v) : "memory"); }

__device__ __forceinline__ void wgmma_fence() { asm volatile("wgmma.fence.sync.aligned;" ::: "memory"); }
__device__ __forceinline__ void wgmma_commit() { asm volatile("wgmma.commit_group.sync.aligned;" ::: "memory"); }
template<int N> __device__ __forceinline__ void wgmma_wait() { asm volatile("wgmma.wait_group.sync.aligned %0;" :: "n"(N) : "memory"); }

template<int N> __device__ __forceinline__ void fence_acc(float* d) {
#pragma unroll
    for (int i = 0; i < N; i++) asm volatile("" : "+f"(d[i]) :: "memory");
}
#define ACC8(b) "+f"(d[b]), "+f"(d[b+1]), "+f"(d[b+2]), "+f"(d[b+3]), "+f"(d[b+4]), "+f"(d[b+5]), "+f"(d[b+6]), "+f"(d[b+7])
#define ACC32(b) ACC8(b), ACC8(b+8), ACC8(b+16), ACC8(b+24)
__device__ __forceinline__ void wgmma_n128(float* d, uint64_t da, uint64_t db, int scale_d) {
    asm volatile("{ .reg .pred p; setp.ne.b32 p, %66, 0;\n"
        "wgmma.mma_async.sync.aligned.m64n128k16.f32.bf16.bf16 {%0,%1,%2,%3,%4,%5,%6,%7,%8,%9,%10,%11,%12,%13,%14,%15,%16,%17,%18,%19,%20,%21,%22,%23,%24,%25,%26,%27,%28,%29,%30,%31,"
        "%32,%33,%34,%35,%36,%37,%38,%39,%40,%41,%42,%43,%44,%45,%46,%47,%48,%49,%50,%51,%52,%53,%54,%55,%56,%57,%58,%59,%60,%61,%62,%63}, %64, %65, p, 1, 1, 0, 1; }"
        : ACC32(0), ACC32(32) : "l"(da), "l"(db), "r"(scale_d));
}
__device__ __forceinline__ void wgmma_n256(float* d, uint64_t da, uint64_t db, int scale_d) {
    asm volatile("{ .reg .pred p; setp.ne.b32 p, %130, 0;\n"
        "wgmma.mma_async.sync.aligned.m64n256k16.f32.bf16.bf16 {%0,%1,%2,%3,%4,%5,%6,%7,%8,%9,%10,%11,%12,%13,%14,%15,%16,%17,%18,%19,%20,%21,%22,%23,%24,%25,%26,%27,%28,%29,%30,%31,"
        "%32,%33,%34,%35,%36,%37,%38,%39,%40,%41,%42,%43,%44,%45,%46,%47,%48,%49,%50,%51,%52,%53,%54,%55,%56,%57,%58,%59,%60,%61,%62,%63,"
        "%64,%65,%66,%67,%68,%69,%70,%71,%72,%73,%74,%75,%76,%77,%78,%79,%80,%81,%82,%83,%84,%85,%86,%87,%88,%89,%90,%91,%92,%93,%94,%95,"
        "%96,%97,%98,%99,%100,%101,%102,%103,%104,%105,%106,%107,%108,%109,%110,%111,%112,%113,%114,%115,%116,%117,%118,%119,%120,%121,%122,%123,%124,%125,%126,%127}, %128, %129, p, 1, 1, 0, 1; }"
        : ACC32(0), ACC32(32), ACC32(64), ACC32(96) : "l"(da), "l"(db), "r"(scale_d));
}
__device__ __forceinline__ uint64_t make_desc(uint32_t addr, uint32_t lbo, uint32_t sbo) {
    return (uint64_t)((addr & 0x3FFFF) >> 4) | ((uint64_t)(lbo >> 4) << 16) | ((uint64_t)(sbo >> 4) << 32) | ((uint64_t)1 << 62);
}

__device__ __forceinline__ float div_fix(float a, float b, float rb) { float q = a * rb; float r = fmaf(-q, b, a); return fmaf(r, rb, q); }
__device__ __forceinline__ void row_item(int mode, uint32_t sx, uint32_t sa, uint32_t sp, uint32_t bar_empty, float* __restrict__ acc, bf16* __restrict__ yout, bf16* __restrict__ out, int lane) {
    float x[20];
#pragma unroll
    for (int i = 0; i < 5; i++) {
        const uint2 v = lds64(sx + i * 256 + lane * 8);
        x[4 * i] = __uint_as_float(v.x << 16); x[4 * i + 1] = __uint_as_float(v.x & 0xffff0000u);
        x[4 * i + 2] = __uint_as_float(v.y << 16); x[4 * i + 3] = __uint_as_float(v.y & 0xffff0000u);
    }
    if (mode) {
#pragma unroll
        for (int i = 0; i < 5; i++) {
            const uint4 a = lds128(sa + i * 512 + lane * 16), gt = lds128(sp + i * 512 + lane * 16);
            x[4 * i] = bf16r(x[4 * i] + bf16r(__uint_as_float(gt.x) * bf16r(__uint_as_float(a.x)))); x[4 * i + 1] = bf16r(x[4 * i + 1] + bf16r(__uint_as_float(gt.y) * bf16r(__uint_as_float(a.y))));
            x[4 * i + 2] = bf16r(x[4 * i + 2] + bf16r(__uint_as_float(gt.z) * bf16r(__uint_as_float(a.z)))); x[4 * i + 3] = bf16r(x[4 * i + 3] + bf16r(__uint_as_float(gt.w) * bf16r(__uint_as_float(a.w))));
            *(uint2*)(yout + i * 128 + lane * 4) = make_uint2(pack_bf16(x[4 * i], x[4 * i + 1]), pack_bf16(x[4 * i + 2], x[4 * i + 3]));
            *(float4*)(acc + i * 128 + lane * 4) = make_float4(0.f, 0.f, 0.f, 0.f);
        }
        sp += 2560;
    }
    if (mode != 2) {
        float s = 0;
#pragma unroll
        for (int i = 0; i < 20; i++) s += x[i];
#pragma unroll
        for (int o = 16; o; o >>= 1) s += __shfl_xor_sync(0xffffffff, s, o);
        const float mean = s * (1.0f / 640.0f);
        float q = 0;
#pragma unroll
        for (int i = 0; i < 20; i++) { float d = x[i] - mean; q += d * d; }
#pragma unroll
        for (int o = 16; o; o >>= 1) q += __shfl_xor_sync(0xffffffff, q, o);
        const float m16 = bf16r(mean);
        const float sd = bf16r(sqrtf(bf16r(bf16r(q * (1.0f / 640.0f)) + 1e-5f)));
        const float rs = __frcp_rn(sd);
#pragma unroll
        for (int i = 0; i < 5; i++) {
            const uint4 sh = lds128(sp + i * 512 + lane * 16), sc = lds128(sp + 2560 + i * 512 + lane * 16);
            float y0 = bf16r(bf16r(div_fix(bf16r(x[4 * i] - m16), sd, rs)) * bf16r(1.0f + __uint_as_float(sc.x))) + __uint_as_float(sh.x);
            float y1 = bf16r(bf16r(div_fix(bf16r(x[4 * i + 1] - m16), sd, rs)) * bf16r(1.0f + __uint_as_float(sc.y))) + __uint_as_float(sh.y);
            float y2 = bf16r(bf16r(div_fix(bf16r(x[4 * i + 2] - m16), sd, rs)) * bf16r(1.0f + __uint_as_float(sc.z))) + __uint_as_float(sh.z);
            float y3 = bf16r(bf16r(div_fix(bf16r(x[4 * i + 3] - m16), sd, rs)) * bf16r(1.0f + __uint_as_float(sc.w))) + __uint_as_float(sh.w);
            *(uint2*)(out + i * 128 + lane * 4) = make_uint2(pack_bf16(y0, y1), pack_bf16(y2, y3));
        }
    }
    __syncwarp();
    if (lane == 0) mbar_arrive(bar_empty);
}

__device__ __forceinline__ float gelu_tanh(float x) {
    float u2 = x * fmaf(x * x, 2.0f * 0.7978845608028654f * 0.044715f * 1.4426950408889634f, 2.0f * 0.7978845608028654f * 1.4426950408889634f);
    float e; asm("ex2.approx.ftz.f32 %0, %1;" : "=f"(e) : "f"(-u2));
    return __fdividef(x, 1.0f + e);
}
__device__ __forceinline__ uint4 ldg128(const void* p) { uint4 v; asm volatile("ld.global.v4.u32 {%0,%1,%2,%3}, [%4];" : "=r"(v.x), "=r"(v.y), "=r"(v.z), "=r"(v.w) : "l"(p) : "memory"); return v; }
__device__ __forceinline__ float4 ldcg_f4(const float* p) { float4 v; asm volatile("ld.global.cg.v4.f32 {%0,%1,%2,%3}, [%4];" : "=f"(v.x), "=f"(v.y), "=f"(v.z), "=f"(v.w) : "l"(p) : "memory"); return v; }
__device__ __forceinline__ uint4 ldcg128(const void* p) { uint4 v; asm volatile("ld.global.cg.v4.u32 {%0,%1,%2,%3}, [%4];" : "=r"(v.x), "=r"(v.y), "=r"(v.z), "=r"(v.w) : "l"(p) : "memory"); return v; }

__device__ __forceinline__ void attn_scores(uint32_t sq, uint32_t sk, uint32_t skm, int sg, int mt, int lane, uint32_t (&p)[6][2]) {
    const int g = lane >> 2, t = lane & 3, l7 = lane & 7;
    float s[5][4];
#pragma unroll
    for (int kt = 0; kt < 5; kt++) s[kt][0] = s[kt][1] = s[kt][2] = s[kt][3] = 0.f;
    const uint32_t qrow = sq + (sg * 32 + mt * 16 + (lane & 15)) * 128;
    const uint32_t krow = sk + (sg * 32 + l7) * 128, kmrow = skm + (sg * 8 + l7) * 128;
#pragma unroll
    for (int c = 0; c < 4; c++) {
        uint32_t a0[4], a1[4];
        ldsm_x4(a0, qrow + (c >> 1) * 16384 + ((((4 * c + (lane >> 4)) & 7) ^ l7) << 4));
        ldsm_x4(a1, qrow + (c >> 1) * 16384 + ((((4 * c + 2 + (lane >> 4)) & 7) ^ l7) << 4));
        const uint32_t sw = (((4 * c + (lane >> 3)) & 7) ^ l7) << 4;
#pragma unroll
        for (int kt = 0; kt < 5; kt++) {
            uint32_t b[4];
            ldsm_x4(b, kt == 0 ? kmrow + (c >> 1) * 4096 + sw : krow + (kt - 1) * 1024 + (c >> 1) * 16384 + sw);
            mma16816(s[kt], a0, b[0], b[1]); mma16816(s[kt], a1, b[2], b[3]);
        }
    }
    const float scale = 0.08838834764831845f;
    const int r0 = mt * 16 + g, r1 = r0 + 8;
    float m0 = -INFINITY, m1 = -INFINITY;
#pragma unroll
    for (int kt = 0; kt < 5; kt++) {
#pragma unroll
        for (int i = 0; i < 4; i++) {
            float v = bf16r(bf16r(s[kt][i]) * scale);
            if (kt > 0) { int key = (kt - 1) * 8 + 2 * t + (i & 1); if (key > (i < 2 ? r0 : r1)) v = -1.0e9f; }
            s[kt][i] = v;
            if (i < 2) m0 = fmaxf(m0, v); else m1 = fmaxf(m1, v);
        }
    }
    m0 = fmaxf(m0, __shfl_xor_sync(0xffffffff, m0, 1)); m0 = fmaxf(m0, __shfl_xor_sync(0xffffffff, m0, 2));
    m1 = fmaxf(m1, __shfl_xor_sync(0xffffffff, m1, 1)); m1 = fmaxf(m1, __shfl_xor_sync(0xffffffff, m1, 2));
    float l0 = 0, l1 = 0;
#pragma unroll
    for (int kt = 0; kt < 5; kt++) {
        s[kt][0] = __expf(s[kt][0] - m0); s[kt][1] = __expf(s[kt][1] - m0); l0 += s[kt][0] + s[kt][1];
        s[kt][2] = __expf(s[kt][2] - m1); s[kt][3] = __expf(s[kt][3] - m1); l1 += s[kt][2] + s[kt][3];
    }
    l0 += __shfl_xor_sync(0xffffffff, l0, 1); l0 += __shfl_xor_sync(0xffffffff, l0, 2);
    l1 += __shfl_xor_sync(0xffffffff, l1, 1); l1 += __shfl_xor_sync(0xffffffff, l1, 2);
    const float i0 = __fdividef(1.0f, l0), i1 = __fdividef(1.0f, l1);
#pragma unroll
    for (int kt = 0; kt < 5; kt++) { p[kt][0] = pack_bf16(s[kt][0] * i0, s[kt][1] * i0); p[kt][1] = pack_bf16(s[kt][2] * i1, s[kt][3] * i1); }
    p[5][0] = p[5][1] = 0;
}
__device__ __forceinline__ void attn_pv(uint32_t sv, uint32_t svm, int sg, int lane, const uint32_t (&p)[6][2], float* d) {
    const int l7 = lane & 7, hi = (lane >> 3) & 1, ec = lane >> 4;
    const uint32_t r0 = hi ? sv + (sg * 32 + l7) * 128 : svm + (sg * 8 + l7) * 128;
    const uint32_t sub0 = hi ? 16384 : 4096;
    const uint32_t r1 = sv + (sg * 32 + 8 + hi * 8 + l7) * 128;
    const uint32_t r2 = sv + (sg * 32 + 24 + l7) * 128;
#pragma unroll
    for (int i = 0; i < 8; i++) {
        const uint32_t sw = (((2 * i + ec) & 7) ^ l7) << 4;
        uint32_t b0[4], b1[4], b2[4];
        ldsm_x4_t(b0, r0 + (i >> 2) * sub0 + sw); ldsm_x4_t(b1, r1 + (i >> 2) * 16384 + sw); ldsm_x4_t(b2, r2 + (i >> 2) * 16384 + sw);
        float* o0 = d + 8 * i; float* o1 = o0 + 4;
        o0[0] = o0[1] = o0[2] = o0[3] = o1[0] = o1[1] = o1[2] = o1[3] = 0.f;
        { uint32_t a[4] = {p[0][0], p[0][1], p[1][0], p[1][1]}; mma16816(o0, a, b0[0], b0[1]); mma16816(o1, a, b0[2], b0[3]); }
        { uint32_t a[4] = {p[2][0], p[2][1], p[3][0], p[3][1]}; mma16816(o0, a, b1[0], b1[1]); mma16816(o1, a, b1[2], b1[3]); }
        { uint32_t a[4] = {p[4][0], p[4][1], p[5][0], p[5][1]}; mma16816(o0, a, b2[0], b2[1]); mma16816(o1, a, b2[2], b2[3]); }
    }
}
__device__ __forceinline__ void bulk_load(uint32_t dst, const void* src, uint32_t bytes, uint32_t bar) {
    asm volatile("cp.async.bulk.shared::cluster.global.mbarrier::complete_tx::bytes [%0], [%1], %2, [%3];" :: "r"(dst), "l"(src), "r"(bytes), "r"(bar) : "memory");
}

__device__ __forceinline__ void stsm_x4(uint32_t addr, uint32_t a, uint32_t b, uint32_t c, uint32_t d) {
    asm volatile("stmatrix.sync.aligned.m8n8.x4.shared.b16 [%0], {%1,%2,%3,%4};" :: "r"(addr), "r"(a), "r"(b), "r"(c), "r"(d) : "memory");
}
__device__ __forceinline__ void tma_reduce_2d(const CUtensorMap* map, uint32_t src, int c0, int c1) {
    asm volatile("cp.reduce.async.bulk.tensor.2d.global.shared::cta.add.tile.bulk_group [%0, {%2, %3}], [%1];" :: "l"(map), "r"(src), "r"(c0), "r"(c1) : "memory");
}
__device__ __forceinline__ void tma_store_2d(const CUtensorMap* map, uint32_t src, int c0, int c1) {
    asm volatile("cp.async.bulk.tensor.2d.global.shared::cta.bulk_group [%0, {%2, %3}], [%1];" :: "l"(map), "r"(src), "r"(c0), "r"(c1) : "memory");
}

__global__ void __launch_bounds__(384, 1)
g_kernel(const __grid_constant__ GParams P, const bf16* __restrict__ x, const bf16* __restrict__ cvec, const bf16* __restrict__ w_mod, bf16* __restrict__ out, int nctas, int wait_r)
{
    using namespace gk;
    extern __shared__ __align__(1024) uint8_t smem[];
    const uint32_t sb = smem_u32(smem);
    const int tid = threadIdx.x, warp = tid >> 5, lane = tid & 31;
    const uint32_t b_full = sb + OFF_BAR, b_empty = b_full + 8 * STAGES, b_wfull = b_empty + 8 * STAGES, b_wempty = b_wfull + 16;
    const uint32_t b_cdone = b_wempty + 16, b_sfree = b_cdone + 16;
    volatile int* wslot = (volatile int*)(smem + OFF_BAR + 192);
    const uint32_t epoch = ld_relaxed(&g_epoch);
    const uint32_t e1 = epoch + 1;
    if (tid == 0) {
        wslot[4] = 0;
        for (int i = 0; i < STAGES; i++) { mbar_init(b_full + 8 * i, 1); mbar_init(b_empty + 8 * i, 8); }
        for (int i = 0; i < 2; i++) { mbar_init(b_wfull + 8 * i, 1); mbar_init(b_wempty + 8 * i, 9); mbar_init(b_cdone + 8 * i, 4); mbar_init(b_sfree + 8 * i, 1); }
        asm volatile("fence.mbarrier_init.release.cluster;" ::: "memory");
    }
    __syncthreads();

    if (warp < 4) {
        asm volatile("setmaxnreg.dec.sync.aligned.u32 40;");
        if (warp == 0 && lane == 0) {
            uint32_t stage = 0, sph = 1, wi = 0, wph = 1;
            bool low_left = true;
            uint32_t lx0 = 0, lx1 = 0, lx2 = 0;
            int lim = 0, issued = 0, nat = 0;
            volatile int* fin_cnt = wslot + 4;
            while (true) {
                Item it; it.type = T_END; it.rb = it.nt = it.ks = 0;
                int tk = 0; (void)tk;
                while (true) {
                    uint4 rd = ld_relaxed_v4(&g_st.ready[0]); const uint4 ex = ld_relaxed_v4(&g_st.exh[0]);
                    const uint32_t dat = nat < 16 ? ld_relaxed(&g_st.d_at[nat * 32]) : 0;
                    if (nat < 16 && dat == e1 * ((wait_r ? 112u : 48u) + (nat == 0 ? 32u : 0u))) { if (!(rd.x >> nat & 1)) publish_group(T_AT, nat, e1); nat++; }
                    { const int na = __popc(rd.x & 0xffffu); if (na > nat) nat = na; }
                    rd.x |= (1u << nat) - 1;
                    lx0 |= ex.x; lx1 |= ex.y; lx2 |= ex.z;
                    uint32_t a0 = rd.x & ~lx0, a1 = rd.y & ~lx1, a2 = rd.z & ~lx2;
                    bool got = false;
                    if ((a0 | a1 | a2) && (rd.x >> (FINE_RB - 1) & 1) && *fin_cnt != issued) {
                        int l2 = 0; while (*fin_cnt != issued && ++l2 < SPIN_LIMIT) { }
                        continue;
                    }
                    while (a0 | a1 | a2) {
                        const int gi = a0 ? __ffs(a0) - 1 : (a1 ? 32 + __ffs(a1) - 1 : 64 + __ffs(a2) - 1);
                        const int ty = T_AT + (gi >> 4), rb = gi & 15, n = group_size(ty, rb);
                        const int i = (int)atomicAdd(&g_st.cnt[gi * 8], 1u);
                        const uint32_t bit = 1u << (gi & 31);
                        if (i >= n - 1) {
                            if (gi < 32) { lx0 |= bit; a0 &= ~bit; } else if (gi < 64) { lx1 |= bit; a1 &= ~bit; } else { lx2 |= bit; a2 &= ~bit; }
                            if (i == n - 1) asm volatile("red.relaxed.gpu.global.or.b32 [%0], %1;" :: "l"(&g_st.exh[gi >> 5]), "r"(bit) : "memory");
                        }
                        if (i < n) {
                            it.type = ty; it.rb = rb; it.nt = i;
                            if (ty == T_WO || ty == T_F2) { const int nn = n_nt(rb); it.ks = i / nn; it.nt = i - it.ks * nn; }
                            asm volatile("fence.acq_rel.gpu;" ::: "memory");
                            got = true; break;
                        }
                    }
                    if (got) {
                        break;
                    }
                    if (low_left && (int)rd.w < I_W + 96 + (nat + LOW_LEAD) * 48) {
                        const int lt = (int)atomicAdd(&g_st.lq_claim, 1u);
                        if (lt < N_LOW) {
                            it = decode_low(lt);
                            if (it.type == T_L1) wait_ge(&g_st.c_mod_a, e1 * 20);
                            else if (it.type != T_MOD) wait_ge(&g_st.f_h[it.rb * 32], e1 * 16);
                            break;
                        }
                        low_left = false;
                    }
                    if ((lx0 & lx1 & lx2) == 0xffffffffu) break;
                    if (!low_left && nat >= PRECLAIM_RB) {
                        const uint32_t rdw[3] = {rd.x, rd.y, rd.z}, lxw[3] = {lx0, lx1, lx2};
                        int gsel = -1;
#pragma unroll
                        for (int rb = 15; rb >= PRECLAIM_RB; rb--) {
#pragma unroll
                            for (int k = 5; k >= 0; k--) {
                                const int gi = k * 16 + rb;
                                const bool rdy = rdw[gi >> 5] >> (gi & 31) & 1, exq = lxw[gi >> 5] >> (gi & 31) & 1;
                                const bool pre = k == 0 ? (nat == rb) : (rdw[(gi - 16) >> 5] >> ((gi - 16) & 31) & 1);
                                if (!rdy && !exq && pre) gsel = gi;
                            }
                        }
                        if (gsel >= 0) {
                            const int gi = gsel, ty = T_AT + (gi >> 4), rb = gi & 15, n = group_size(ty, rb);
                            const int i = (int)atomicAdd(&g_st.cnt[gi * 8], 1u);
                            const uint32_t bit = 1u << (gi & 31);
                            if (i >= n - 1) {
                                if (gi < 32) lx0 |= bit; else if (gi < 64) lx1 |= bit; else lx2 |= bit;
                                if (i == n - 1) asm volatile("red.relaxed.gpu.global.or.b32 [%0], %1;" :: "l"(&g_st.exh[gi >> 5]), "r"(bit) : "memory");
                            }
                            if (i < n) {
                                it.type = ty; it.rb = rb; it.nt = i;
                                if (ty == T_WO || ty == T_F2) { const int nn = n_nt(rb); it.ks = i / nn; it.nt = i - it.ks * nn; }
                                const uint32_t* dp = (ty == T_AT ? g_st.d_at : ty == T_WO ? g_st.c_at : ty == T_L2 ? g_st.c_wo : ty == T_F1 ? g_st.f_h2 : ty == T_F2 ? g_st.c_act : g_st.c_f2) + rb * 32;
                                const uint32_t dt = e1 * (ty == T_AT ? (wait_r ? 112u : 48u) : (uint32_t)group_size(ty - 1, rb));
                                int l3 = 0;
                                while ((int32_t)(ld_acquire(dp) - dt) < 0) { if (++l3 > SPIN_LIMIT) break; }
                                break;
                            }
                            continue;
                        }
                    }
                    __nanosleep(40);
                    if (++lim > SPIN_LIMIT) break;
                }
                issued++;
                if (it.type == T_L2) wait_ge(&g_st.c_mod_all, e1 * 60);
                asm volatile("fence.proxy.async.global;" ::: "memory");
                mbar_wait(b_wempty + 8 * wi, wph);
                wslot[wi] = pack_item(it);
                mbar_arrive(b_wfull + 8 * wi);
                if (++wi == 2) { wi = 0; wph ^= 1; }
                if (it.type == T_END) break;
                int nkb = 0, kb0 = 0;
                const CUtensorMap *mA = nullptr, *mB0 = nullptr, *mB1 = nullptr; int n0 = 0, n1 = 0, nbox = 4;
                switch (it.type) {
                    case T_KV: nkb = 10; mA = &P.tA_h;
                        if (it.ks) { mB0 = mB1 = (it.nt < 32) ? &P.tB_k : &P.tB_v; n0 = (it.nt & 31) * 128; n1 = n0 + 64; nbox = 2; }
                        else { mB0 = mB1 = (it.nt < 16) ? &P.tB_k : &P.tB_v; n0 = (it.nt & 15) * 256; n1 = n0 + 128; }
                        break;
                    case T_Q: nkb = 10; mA = &P.tA_h; mB0 = mB1 = &P.tB_q; n0 = it.nt * 256; n1 = n0 + 128; break;
                    case T_F1: nkb = 10; mA = &P.tA_h2; mB0 = &P.tB_g; mB1 = &P.tB_u; if (fine(it.rb)) { n0 = n1 = it.nt * 64; nbox = 2; } else n0 = n1 = it.nt * 128; break;
                    case T_WO: nkb = 64 / wo_split(it.rb); kb0 = it.ks * nkb; mA = &P.tA_o; mB0 = mB1 = &P.tB_o; n0 = red_col(it); if (is_wide(it)) n1 = n0 + 128; else { n1 = n0 + 64; nbox = 2; } break;
                    case T_F2: nkb = 27 / f2_split(it.rb); kb0 = it.ks * nkb; mA = &P.tA_act; mB0 = mB1 = &P.tB_d; n0 = red_col(it); if (is_wide(it)) n1 = n0 + 128; else { n1 = n0 + 64; nbox = 2; } break;
                    default: break;
                }
                if (it.type == T_AT) {
#pragma unroll 1
                    for (int i = 0; i < 3; i++) {
                        mbar_wait(b_empty + 8 * stage, sph);
                        const uint32_t st = sb + stage * STAGE_BYTES, bar = b_full + 8 * stage;
                        mbar_expect_tx(bar, i ? 40960 : 32768);
                        const CUtensorMap* m = i == 0 ? &P.tL_q : (i == 1 ? &P.tL_k : &P.tL_v);
                        tma_load_2d(st + 16384, m, it.nt * 128, it.rb * 128, bar);
                        tma_load_2d(st + 32768, m, it.nt * 128 + 64, it.rb * 128, bar);
                        if (i) {
                            const CUtensorMap* mm = i == 1 ? &P.tL_km : &P.tL_vm;
                            tma_load_2d(st, mm, it.nt * 128, it.rb * 32, bar);
                            tma_load_2d(st + 4096, mm, it.nt * 128 + 64, it.rb * 32, bar);
                        }
                        if (++stage == STAGES) { stage = 0; sph ^= 1; }
                    }
                } else if (it.type == T_L1 || it.type == T_L2 || it.type == T_FIN) {
                    const int mode = it.type == T_L1 ? 0 : (it.type == T_L2 ? 1 : 2);
                    const uint32_t pbytes = mode == 0 ? 5120 : (mode == 1 ? 7680 : 2560);
                    const float* psrc = g_mod + (mode == 0 ? 0 : (mode == 1 ? 2 * 640 : 5 * 640));
                    {
                        mbar_wait(b_empty + 8 * stage, sph);
                        const uint32_t st = sb + stage * STAGE_BYTES, bar = b_full + 8 * stage;
                        const size_t ro = ((size_t)it.rb * 128 + it.nt * 8) * 640;
                        mbar_expect_tx(bar, 10240 + (mode ? 20480 : 0) + pbytes);
                        bulk_load(st, (mode == 2 ? g_x1 : x) + ro, 10240, bar);
                        if (mode) bulk_load(st + 10240, g_slab + ro, 20480, bar);
                        bulk_load(st + 30720, psrc, pbytes, bar);
                        if (++stage == STAGES) { stage = 0; sph ^= 1; }
                    }
                }
                for (int kb = 0; kb < nkb; kb++) {
                    mbar_wait(b_empty + 8 * stage, sph);
                    const uint32_t st = sb + stage * STAGE_BYTES, bar = b_full + 8 * stage;
                    mbar_expect_tx(bar, 16384 + nbox * 8192);
                    const int k = (kb0 + kb) * 64;
                    tma_load_2d(st, mA, k, it.rb * 128, bar);
                    tma_load_2d(st + 16384, mB0, n0, k, bar);
                    if (nbox == 4) {
                        tma_load_2d(st + 16384 + 8192, mB0, n0 + 64, k, bar);
                        tma_load_2d(st + 16384 + 16384, mB1, n1, k, bar);
                        tma_load_2d(st + 16384 + 24576, mB1, n1 + 64, k, bar);
                    } else {
                        tma_load_2d(st + 16384 + 8192, mB1, n1, k, bar);
                    }
                    if (++stage == STAGES) { stage = 0; sph ^= 1; }
                }
            }
        } else if (warp == 1 && lane == 0) {
            uint32_t wi = 0, wph = 0, cph = 0;
            while (true) {
                mbar_wait(b_wfull + 8 * wi, wph);
                const Item it = unpack_item(wslot[wi]);
                mbar_arrive(b_wempty + 8 * wi);
                if (++wi == 2) { wi = 0; wph ^= 1; }
                if (it.type == T_END) break;
                const bool red = it.type == T_WO || it.type == T_F2;
                const bool tma = it.type == T_KV || it.type == T_Q || it.type == T_F1 || it.type == T_AT || red;
                const bool narrow = it.type == T_F1 && fine(it.rb);
                const bool kvn = it.type == T_KV && it.ks;
                const int rounds = red ? (is_wide(it) ? 4 : 2) : (((it.type == T_KV || it.type == T_Q) && !kvn) ? 2 : 1);
                const CUtensorMap* mS = it.type == T_F1 ? &P.tS_act : (it.type == T_AT ? &P.tS_o : (it.type == T_Q ? &P.tS_q : (it.nt < (kvn ? 32 : 16) ? &P.tS_k : &P.tS_v)));
                const int gcol = red ? red_col(it) : (narrow ? it.nt * 64 : (rounds == 1 ? (it.nt & 31) * 128 : (it.nt & 15) * 256));
                for (int rnd = 0; rnd < rounds; rnd++) {
                    for (int wg = 0; wg < 2; wg++) {
                        mbar_wait(b_cdone + 8 * wg, cph);
                        const uint32_t stg = sb + OFF_SCR + wg * 16384;
                        const int grow = it.rb * 128 + wg * 64;
                        if (red) {
                            tma_reduce_2d(&P.tR_acc, stg, gcol + rnd * 64, grow);
                            tma_reduce_2d(&P.tR_acc, stg + 8192, gcol + rnd * 64 + 32, grow);
                        } else if (tma) {
                            tma_store_2d(mS, stg, gcol + rnd * 128, grow);
                            if (!narrow) tma_store_2d(mS, stg + 8192, gcol + rnd * 128 + 64, grow);
                        }
                        if (tma) asm volatile("cp.async.bulk.commit_group;" ::: "memory");
                    }
                    cph ^= 1;
                    if (tma) asm volatile("cp.async.bulk.wait_group.read 0;" ::: "memory");
                    mbar_arrive(b_sfree); mbar_arrive(b_sfree + 8);
                }
                if (tma) { asm volatile("cp.async.bulk.wait_group 0;" ::: "memory"); asm volatile("fence.proxy.async.global;" ::: "memory"); }
                if (it.type <= T_KV) asm volatile("fence.acq_rel.gpu;" ::: "memory");
                uint32_t* cnt = nullptr; uint32_t tgt = 0; int nxt = -1;
                switch (it.type) {
                    case T_KV: if (kvn) st_relaxed_u32(&g_kvflag[it.nt], e1);
                        else { st_relaxed_u32(&g_kvflag[it.rb * 64 + it.nt * 2], e1); st_relaxed_u32(&g_kvflag[it.rb * 64 + it.nt * 2 + 1], e1); }
                    case T_Q: red_release_inc(&g_st.d_at[it.rb * 32]); break;
                    case T_MOD: if (it.nt < 20) red_add_relaxed(&g_st.c_mod_a, 1); red_add_relaxed(&g_st.c_mod_all, 1); break;
                    case T_L1: red_add_relaxed(&g_st.f_h[it.rb * 32], 1); break;
                    case T_AT: cnt = &g_st.c_at[it.rb * 32]; tgt = 32; nxt = T_WO; break;
                    case T_WO: cnt = &g_st.c_wo[it.rb * 32]; tgt = group_size(T_WO, it.rb); nxt = T_L2; break;
                    case T_L2: cnt = &g_st.f_h2[it.rb * 32]; tgt = 16; nxt = T_F1; break;
                    case T_F1: cnt = &g_st.c_act[it.rb * 32]; tgt = group_size(T_F1, it.rb); nxt = T_F2; break;
                    case T_F2: cnt = &g_st.c_f2[it.rb * 32]; tgt = group_size(T_F2, it.rb); nxt = T_FIN; break;
                    default: break;
                }
                if (cnt) { if (atom_add_acqrel(cnt, 1) + 1 == e1 * tgt) publish_group(nxt, it.rb, e1); }
            }
            uint32_t old = atom_add_acqrel(&g_st.done, 1);
            if (old + 1 == e1 * (uint32_t)nctas) {
                for (int i = 0; i < 96; i++) g_st.cnt[i * 8] = 0;
                for (int i = 0; i < 3; i++) { g_st.ready[i] = 0; g_st.exh[i] = 0; }
                g_st.lq_claim = 0;
                st_release(&g_epoch, e1);
            }
        }
    } else {
        asm volatile("setmaxnreg.inc.sync.aligned.u32 232;");
        const int ct = tid - 128, cw = warp - 4, wg = cw >> 2;
        const int g = lane >> 2, t = lane & 3;
        uint32_t stage = 0, sph = 0, wi = 0, wph = 0, fph = 1; int ndone = 0;
        while (true) {
            if (ct == 0) wslot[4] = ndone;
            ndone++;
            mbar_wait(b_wfull + 8 * wi, wph);
            const Item it = unpack_item(wslot[wi]);
            __syncwarp();
            if (lane == 0) mbar_arrive(b_wempty + 8 * wi);
            if (++wi == 2) { wi = 0; wph ^= 1; }
            if (it.type == T_END) break;
            const bool narrow = (it.type == T_F1 && fine(it.rb)) || (it.type == T_KV && it.ks);
            if (is_wide(it)) {
                const bool red = it.type == T_WO || it.type == T_F2;
                const int nkb = it.type == T_WO ? 64 / wo_split(it.rb) : (it.type == T_F2 ? 27 / f2_split(it.rb) : 10);
                float d[128];
#pragma unroll
                for (int i = 0; i < 128; i++) d[i] = 0.f;
                for (int kb = 0; kb < nkb; kb++) {
                    mbar_wait(b_full + 8 * stage, sph);
                    const uint32_t st = sb + stage * STAGE_BYTES;
                    const uint64_t da = make_desc(st + wg * 8192, 16, 1024), db = make_desc(st + 16384, 8192, 1024);
                    wgmma_fence();
#pragma unroll
                    for (int k = 0; k < 4; k++) wgmma_n256(d, da + k * 2, db + k * 128, 1);
                    wgmma_commit();
                    wgmma_wait<1>();
                    if (kb > 0 && lane == 0) mbar_arrive(b_empty + 8 * ((stage + STAGES - 1) % STAGES));
                    if (++stage == STAGES) { stage = 0; sph ^= 1; }
                }
                wgmma_wait<0>();
                fence_acc<128>(d);
                if (lane == 0) mbar_arrive(b_empty + 8 * ((stage + STAGES - 1) % STAGES));
                if (red) {
                    const uint32_t sbase = sb + OFF_SCR + wg * 16384 + ((cw & 3) * 16 + g) * 128 + (t & 1) * 8;
#pragma unroll
                    for (int rnd = 0; rnd < 4; rnd++) {
                        mbar_wait(b_sfree + 8 * wg, fph); fph ^= 1;
#pragma unroll
                        for (int i = 0; i < 8; i++) {
                            const float* dd = d + rnd * 32 + i * 4;
                            const uint32_t a = sbase + (i >> 2) * 8192 + ((((2 * i + (t >> 1)) & 7) ^ (g & 7)) << 4);
                            sts64(a, __float_as_uint(dd[0]), __float_as_uint(dd[1]));
                            sts64(a + 1024, __float_as_uint(dd[2]), __float_as_uint(dd[3]));
                        }
                        asm volatile("fence.proxy.async.shared::cta;" ::: "memory");
                        __syncwarp();
                        if (lane == 0) mbar_arrive(b_cdone + 8 * wg);
                    }
                    continue;
                }
                const uint32_t sbase = sb + OFF_SCR + wg * 16384 + ((cw & 3) * 16 + ((lane >> 3) & 1) * 8 + (lane & 7)) * 128;
                const int sx = lane & 7, hi = lane >> 4;
                if (it.type == T_F1) {
#pragma unroll
                    for (int i = 0; i < 64; i++) d[i] = bf16r(gelu_tanh(bf16r(d[i]))) * bf16r(d[64 + i]);
                }
#pragma unroll
                for (int rnd = 0; rnd < 2; rnd++) {
                    if (rnd == 1 && it.type == T_F1) break;
                    mbar_wait(b_sfree + 8 * wg, fph); fph ^= 1;
#pragma unroll
                    for (int i = 0; i < 8; i++) {
                        const float* dd = d + rnd * 64 + i * 8;
                        const int chunk = (2 * i + hi) & 7;
                        stsm_x4(sbase + (i >> 2) * 8192 + ((chunk ^ sx) << 4), pack_bf16(dd[0], dd[1]), pack_bf16(dd[2], dd[3]), pack_bf16(dd[4], dd[5]), pack_bf16(dd[6], dd[7]));
                    }
                    asm volatile("fence.proxy.async.shared::cta;" ::: "memory");
                    __syncwarp();
                    if (lane == 0) mbar_arrive(b_cdone + 8 * wg);
                }
                continue;
            } else if (narrow) {
                float d[64];
#pragma unroll
                for (int i = 0; i < 64; i++) d[i] = 0.f;
                const int nkb = 10;
                for (int kb = 0; kb < nkb; kb++) {
                    mbar_wait(b_full + 8 * stage, sph);
                    const uint32_t st = sb + stage * STAGE_BYTES;
                    const uint64_t da = make_desc(st + wg * 8192, 16, 1024), db = make_desc(st + 16384, 8192, 1024);
                    wgmma_fence();
#pragma unroll
                    for (int k = 0; k < 4; k++) wgmma_n128(d, da + k * 2, db + k * 128, 1);
                    wgmma_commit();
                    wgmma_wait<1>();
                    if (kb > 0 && lane == 0) mbar_arrive(b_empty + 8 * ((stage + STAGES - 1) % STAGES));
                    if (++stage == STAGES) { stage = 0; sph ^= 1; }
                }
                wgmma_wait<0>();
                fence_acc<64>(d);
                if (lane == 0) mbar_arrive(b_empty + 8 * ((stage + STAGES - 1) % STAGES));
                {
                    const uint32_t sbase = sb + OFF_SCR + wg * 16384 + ((cw & 3) * 16 + ((lane >> 3) & 1) * 8 + (lane & 7)) * 128;
                    const bool f1 = it.type == T_F1;
                    if (f1) {
#pragma unroll
                        for (int i = 0; i < 32; i++) d[i] = bf16r(gelu_tanh(bf16r(d[i]))) * bf16r(d[32 + i]);
                    }
                    mbar_wait(b_sfree + 8 * wg, fph); fph ^= 1;
#pragma unroll
                    for (int i = 0; i < 8; i++) {
                        if (i >= 4 && f1) break;
                        const float* dd = d + i * 8;
                        const int chunk = (2 * i + (lane >> 4)) & 7;
                        stsm_x4(sbase + (i >> 2) * 8192 + ((chunk ^ (lane & 7)) << 4), pack_bf16(dd[0], dd[1]), pack_bf16(dd[2], dd[3]), pack_bf16(dd[4], dd[5]), pack_bf16(dd[6], dd[7]));
                    }
                    asm volatile("fence.proxy.async.shared::cta;" ::: "memory");
                }
            } else if (it.type == T_WO || it.type == T_F2) {
                float d[64];
#pragma unroll
                for (int i = 0; i < 64; i++) d[i] = 0.f;
                const int nkb = it.type == T_WO ? 64 / wo_split(it.rb) : 27 / f2_split(it.rb);
                for (int kb = 0; kb < nkb; kb++) {
                    mbar_wait(b_full + 8 * stage, sph);
                    const uint32_t st = sb + stage * STAGE_BYTES;
                    const uint64_t da = make_desc(st + wg * 8192, 16, 1024), db = make_desc(st + 16384, 8192, 1024);
                    wgmma_fence();
#pragma unroll
                    for (int k = 0; k < 4; k++) wgmma_n128(d, da + k * 2, db + k * 128, 1);
                    wgmma_commit();
                    wgmma_wait<1>();
                    if (kb > 0 && lane == 0) mbar_arrive(b_empty + 8 * ((stage + STAGES - 1) % STAGES));
                    if (++stage == STAGES) { stage = 0; sph ^= 1; }
                }
                wgmma_wait<0>();
                fence_acc<64>(d);
                if (lane == 0) mbar_arrive(b_empty + 8 * ((stage + STAGES - 1) % STAGES));
                {
                    const int r0 = (cw & 3) * 16 + g;
                    const uint32_t sbase = sb + OFF_SCR + wg * 16384 + r0 * 128 + (t & 1) * 8;
#pragma unroll
                    for (int rnd = 0; rnd < 2; rnd++) {
                        mbar_wait(b_sfree + 8 * wg, fph); fph ^= 1;
#pragma unroll
                        for (int i = 0; i < 8; i++) {
                            const float* dd = d + rnd * 32 + i * 4;
                            const uint32_t a = sbase + (i >> 2) * 8192 + ((((2 * i + (t >> 1)) & 7) ^ (g & 7)) << 4);
                            sts64(a, __float_as_uint(dd[0]), __float_as_uint(dd[1]));
                            sts64(a + 1024, __float_as_uint(dd[2]), __float_as_uint(dd[3]));
                        }
                        asm volatile("fence.proxy.async.shared::cta;" ::: "memory");
                        if (rnd == 0) { __syncwarp(); if (lane == 0) mbar_arrive(b_cdone + 8 * wg); }
                    }
                }
            } else if (it.type == T_AT) {
                uint32_t p[6][2];
                float d[64];
                const uint32_t s0 = stage, s1 = (stage + 1) % STAGES, s2 = (stage + 2) % STAGES;
                mbar_wait(b_full + 8 * s0, sph);
                mbar_wait(b_full + 8 * s1, s1 < s0 ? sph ^ 1 : sph);
                attn_scores(sb + s0 * STAGE_BYTES + 16384, sb + s1 * STAGE_BYTES + 16384, sb + s1 * STAGE_BYTES, cw >> 1, cw & 1, lane, p);
                __syncwarp();
                if (lane == 0) { mbar_arrive(b_empty + 8 * s0); mbar_arrive(b_empty + 8 * s1); }
                mbar_wait(b_full + 8 * s2, s2 < s0 ? sph ^ 1 : sph);
                attn_pv(sb + s2 * STAGE_BYTES + 16384, sb + s2 * STAGE_BYTES, cw >> 1, lane, p, d);
                __syncwarp();
                if (lane == 0) mbar_arrive(b_empty + 8 * s2);
                stage += 3; if (stage >= STAGES) { stage -= STAGES; sph ^= 1; }
                const uint32_t sbase = sb + OFF_SCR + wg * 16384 + ((cw & 3) * 16 + ((lane >> 3) & 1) * 8 + (lane & 7)) * 128;
                mbar_wait(b_sfree + 8 * wg, fph); fph ^= 1;
#pragma unroll
                for (int i = 0; i < 8; i++) {
                    const float* dd = d + i * 8;
                    const int chunk = (2 * i + (lane >> 4)) & 7;
                    stsm_x4(sbase + (i >> 2) * 8192 + ((chunk ^ (lane & 7)) << 4), pack_bf16(dd[0], dd[1]), pack_bf16(dd[2], dd[3]), pack_bf16(dd[4], dd[5]), pack_bf16(dd[6], dd[7]));
                }
                asm volatile("fence.proxy.async.shared::cta;" ::: "memory");
            } else if (it.type == T_L1 || it.type == T_L2 || it.type == T_FIN) {
                const int mode = it.type == T_L1 ? 0 : (it.type == T_L2 ? 1 : 2);
                {
                    const size_t ro = ((size_t)it.rb * 128 + it.nt * 8 + cw) * 640;
                    const uint32_t st = sb + stage * STAGE_BYTES;
                    mbar_wait(b_full + 8 * stage, sph);
                    row_item(mode, st + cw * 1280, st + 10240 + cw * 2560, st + 30720, b_empty + 8 * stage, g_slab + ro, (mode == 2 ? out : g_x1) + ro, (mode ? g_h2 : g_h) + ro, lane);
                    if (++stage == STAGES) { stage = 0; sph ^= 1; }
                }
            } else if (it.type == T_MOD) {
                const int kg = ct >> 3, c8 = ct & 7;
                float acc[8] = {0, 0, 0, 0, 0, 0, 0, 0};
                const bf16* wp = w_mod + (size_t)kg * 20 * 3840 + it.nt * 64 + c8 * 8;
                {
                    uint4 w[20]; float sl[20];
#pragma unroll
                    for (int i = 0; i < 20; i++) { w[i] = __ldg((const uint4*)(wp + (size_t)i * 3840)); sl[i] = __bfloat162float(cvec[kg * 20 + i]); }
#pragma unroll
                    for (int i = 0; i < 20; i++) {
                        const float s = bf16r(__fdividef(sl[i], 1.0f + __expf(-sl[i])));
                        acc[0] += s * __uint_as_float(w[i].x << 16); acc[1] += s * __uint_as_float(w[i].x & 0xffff0000u);
                        acc[2] += s * __uint_as_float(w[i].y << 16); acc[3] += s * __uint_as_float(w[i].y & 0xffff0000u);
                        acc[4] += s * __uint_as_float(w[i].z << 16); acc[5] += s * __uint_as_float(w[i].z & 0xffff0000u);
                        acc[6] += s * __uint_as_float(w[i].w << 16); acc[7] += s * __uint_as_float(w[i].w & 0xffff0000u);
                    }
                }
#pragma unroll
                for (int i = 0; i < 8; i++) { acc[i] += __shfl_xor_sync(0xffffffff, acc[i], 8); acc[i] += __shfl_xor_sync(0xffffffff, acc[i], 16); }
                float* scr = (float*)(smem + OFF_BAR + 256);
                bar_sync(3, 256);
                if (lane < 8) {
#pragma unroll
                    for (int i = 0; i < 8; i++) scr[cw * 64 + lane * 8 + i] = acc[i];
                }
                bar_sync(3, 256);
                if (ct < 64) {
                    float sum = 0;
#pragma unroll
                    for (int i = 0; i < 8; i++) sum += scr[i * 64 + ct];
                    g_mod[it.nt * 64 + ct] = bf16r(sum);
                }
            }
            if (it.type == T_MOD || it.type == T_L1 || it.type == T_L2 || it.type == T_FIN) { mbar_wait(b_sfree + 8 * wg, fph); fph ^= 1; }
            __syncwarp();
            if (lane == 0) mbar_arrive(b_cdone + 8 * wg);
        }
    }
}

typedef CUresult (*PFN_encodeTiled)(CUtensorMap*, CUtensorMapDataType, cuuint32_t, void*, const cuuint64_t*, const cuuint64_t*, const cuuint32_t*, const cuuint32_t*, CUtensorMapInterleave, CUtensorMapSwizzle, CUtensorMapL2promotion, CUtensorMapFloatOOBfill);

static void make_map(PFN_encodeTiled fn, CUtensorMap* m, const void* ptr, uint64_t inner, uint64_t outer, uint32_t box_inner, uint32_t box_outer, bool f32 = false) {
    cuuint64_t dims[2] = {inner, outer};
    cuuint64_t strides[1] = {inner * (f32 ? 4 : 2)};
    cuuint32_t box[2] = {box_inner, box_outer};
    cuuint32_t es[2] = {1, 1};
    fn(m, f32 ? CU_TENSOR_MAP_DATA_TYPE_FLOAT32 : CU_TENSOR_MAP_DATA_TYPE_BFLOAT16, 2, (void*)ptr, dims, strides, box, es, CU_TENSOR_MAP_INTERLEAVE_NONE, CU_TENSOR_MAP_SWIZZLE_128B, CU_TENSOR_MAP_L2_PROMOTION_L2_256B, CU_TENSOR_MAP_FLOAT_OOB_FILL_NONE);
}

#define G_LESS 0
static int g_dbg_mode = 0;

extern "C" void kernel_launch(void* const* d_in, const int* in_sizes, int n_in, void* d_out, int out_size) {
    const bf16* x = (const bf16*)d_in[0];
    const bf16* mem0 = (const bf16*)d_in[1];
    const bf16* Wq = (const bf16*)d_in[2];
    const bf16* Wk = (const bf16*)d_in[3];
    const bf16* Wv = (const bf16*)d_in[4];
    const bf16* Wo = (const bf16*)d_in[5];
    const bf16* Wg = (const bf16*)d_in[8];
    const bf16* Wu = (const bf16*)d_in[9];
    const bf16* Wd = (const bf16*)d_in[10];
    const bf16* cvec = (const bf16*)d_in[11];
    const bf16* wmod = (const bf16*)d_in[12];
    static PFN_encodeTiled fn = nullptr;
    static int nsm = 0;
    if (!fn) {
        cudaDriverEntryPointQueryResult qr;
        cudaGetDriverEntryPoint("cuTensorMapEncodeTiled", (void**)&fn, cudaEnableDefault, &qr);
        cudaFuncSetAttribute(r_kernel, cudaFuncAttributeMaxDynamicSharedMemorySize, rk::SMEM_BYTES);
        cudaFuncSetAttribute(r_kernel, cudaFuncAttributeNonPortableClusterSizeAllowed, 1);
        cudaFuncSetAttribute(g_kernel, cudaFuncAttributeMaxDynamicSharedMemorySize, gk::SMEM_BYTES);
        cudaDeviceGetAttribute(&nsm, cudaDevAttrMultiProcessorCount, 0);
    }
    void *ph, *po, *ph2, *pact, *pq, *pk, *pv;
    cudaGetSymbolAddress(&pq, g_q); cudaGetSymbolAddress(&pk, g_k); cudaGetSymbolAddress(&pv, g_v);
    cudaGetSymbolAddress(&ph, g_h); cudaGetSymbolAddress(&po, g_o); cudaGetSymbolAddress(&ph2, g_h2); cudaGetSymbolAddress(&pact, g_act);
    GParams P;
    make_map(fn, &P.tA_h, ph, 640, 2048, 64, 128);
    make_map(fn, &P.tA_o, po, 4096, 2048, 64, 128);
    make_map(fn, &P.tA_h2, ph2, 640, 2048, 64, 128);
    make_map(fn, &P.tA_act, pact, 1728, 2048, 64, 128);
    make_map(fn, &P.tB_q, Wq, 4096, 640, 64, 64);
    make_map(fn, &P.tB_k, Wk, 4096, 640, 64, 64);
    make_map(fn, &P.tB_v, Wv, 4096, 640, 64, 64);
    make_map(fn, &P.tB_o, Wo, 640, 4096, 64, 64);
    make_map(fn, &P.tB_g, Wg, 1728, 640, 64, 64);
    make_map(fn, &P.tB_u, Wu, 1728, 640, 64, 64);
    make_map(fn, &P.tB_d, Wd, 640, 1728, 64, 64);
    make_map(fn, &P.tS_q, pq, 4096, 2048, 64, 64);
    make_map(fn, &P.tS_k, pk, 4096, 2048, 64, 64);
    make_map(fn, &P.tS_v, pv, 4096, 2048, 64, 64);
    make_map(fn, &P.tS_act, pact, 1728, 2048, 64, 64);
    void *pkm, *pvm; cudaGetSymbolAddress(&pkm, g_km); cudaGetSymbolAddress(&pvm, g_vm);
    make_map(fn, &P.tS_o, po, 4096, 2048, 64, 64);
    make_map(fn, &P.tL_q, pq, 4096, 2048, 64, 128);
    make_map(fn, &P.tL_k, pk, 4096, 2048, 64, 128);
    make_map(fn, &P.tL_v, pv, 4096, 2048, 64, 128);
    make_map(fn, &P.tL_km, pkm, 4096, 512, 64, 32);
    make_map(fn, &P.tL_vm, pvm, 4096, 512, 64, 32);
    void* pacc; cudaGetSymbolAddress(&pacc, g_slab);
    make_map(fn, &P.tR_acc, pacc, 640, 2048, 32, 64, true);
    cudaStream_t st = cudaStreamPerThread;
    if (g_dbg_mode != 1) {
        cudaLaunchConfig_t cfg = {};
        cfg.gridDim = dim3(64); cfg.blockDim = dim3(256); cfg.dynamicSmemBytes = rk::SMEM_BYTES; cfg.stream = st;
        cudaLaunchAttribute at[1]; at[0].id = cudaLaunchAttributeClusterDimension; at[0].val.clusterDim.x = 16; at[0].val.clusterDim.y = 1; at[0].val.clusterDim.z = 1;
        cfg.attrs = at; cfg.numAttrs = 1;
        CUtensorMap tk, tv;
        make_map(fn, &tk, pk, 4096, 2048, 64, 32);
        make_map(fn, &tv, pv, 4096, 2048, 64, 32);
        cudaLaunchKernelEx(&cfg, r_kernel, tk, tv, mem0, Wq, Wk, Wv, Wo, 1);
    }
    {
        cudaLaunchConfig_t cfg = {};
        const int ng = g_dbg_mode == 1 ? nsm : nsm - G_LESS;
        cfg.gridDim = dim3(ng); cfg.blockDim = dim3(384); cfg.dynamicSmemBytes = gk::SMEM_BYTES; cfg.stream = st;
        cudaLaunchAttribute at[1]; at[0].id = cudaLaunchAttributeProgrammaticStreamSerialization; at[0].val.programmaticStreamSerializationAllowed = 1;
        cfg.attrs = at; cfg.numAttrs = g_dbg_mode == 1 ? 0 : 1;
        cudaLaunchKernelEx(&cfg, g_kernel, P, x, cvec, wmod, (bf16*)d_out, ng, g_dbg_mode == 1 ? 0 : 1);
    }
}
```

```cpp
#include <cuda_runtime.h>
#include <cuda_bf16.h>
#include <cuda.h>
#include <stdint.h>

typedef __nv_bfloat16 bf16;

__device__ __forceinline__ uint32_t smem_u32(const void* p) { return (uint32_t)__cvta_generic_to_shared(p); }
__device__ __forceinline__ uint32_t mapa_u32(uint32_t a, uint32_t r) { uint32_t o; asm volatile("mapa.shared::cluster.u32 %0, %1, %2;" : "=r"(o) : "r"(a), "r"(r)); return o; }
__device__ __forceinline__ void mbar_init(uint32_t bar, uint32_t cnt) { asm volatile("mbarrier.init.shared::cta.b64 [%0], %1;" :: "r"(bar), "r"(cnt) : "memory"); }
__device__ __forceinline__ void mbar_expect_tx(uint32_t bar, uint32_t bytes) { asm volatile("mbarrier.arrive.expect_tx.shared::cta.b64 _, [%0], %1;" :: "r"(bar), "r"(bytes) : "memory"); }
__device__ __forceinline__ void mbar_arrive(uint32_t bar) { asm volatile("mbarrier.arrive.shared::cta.b64 _, [%0];" :: "r"(bar) : "memory"); }
#define SPIN_LIMIT 400000
__device__ __forceinline__ bool mbar_try(uint32_t bar, uint32_t ph) {
    uint32_t ok;
    asm volatile("{ .reg .pred p; mbarrier.try_wait.parity.shared::cta.b64 p, [%1], %2; selp.u32 %0, 1, 0, p; }" : "=r"(ok) : "r"(bar), "r"(ph) : "memory");
    return ok;
}
__device__ __forceinline__ void mbar_wait(uint32_t bar, uint32_t ph) {
    if (mbar_try(bar, ph)) return;
#pragma unroll 1
    for (int lim = 0; lim < SPIN_LIMIT; lim++) if (mbar_try(bar, ph)) break;
}
__device__ __forceinline__ void mbar_wait_cluster(uint32_t bar, uint32_t ph) {
    uint32_t ok = 0; int lim = 0;
    while (true) {
        asm volatile("{ .reg .pred p; mbarrier.try_wait.parity.acquire.cluster.shared::cta.b64 p, [%1], %2; selp.u32 %0, 1, 0, p; }" : "=r"(ok) : "r"(bar), "r"(ph) : "memory");
        if (ok) break;
        if (++lim > SPIN_LIMIT) break;
    }
}
__device__ __forceinline__ void st_async_v4(uint32_t addr, uint32_t a, uint32_t b, uint32_t c, uint32_t d, uint32_t bar) {
    asm volatile("st.async.weak.shared::cluster.mbarrier::complete_tx::bytes.v4.b32 [%0], {%1,%2,%3,%4}, [%5];" :: "r"(addr), "r"(a), "r"(b), "r"(c), "r"(d), "r"(bar) : "memory");
}
__device__ __forceinline__ void ldsm_x4(uint32_t* r, uint32_t addr) {
    asm volatile("ldmatrix.sync.aligned.m8n8.x4.shared.b16 {%0,%1,%2,%3}, [%4];" : "=r"(r[0]), "=r"(r[1]), "=r"(r[2]), "=r"(r[3]) : "r"(addr) : "memory");
}
__device__ __forceinline__ void ldsm_x4_t(uint32_t* r, uint32_t addr) {
    asm volatile("ldmatrix.sync.aligned.m8n8.x4.trans.shared.b16 {%0,%1,%2,%3}, [%4];" : "=r"(r[0]), "=r"(r[1]), "=r"(r[2]), "=r"(r[3]) : "r"(addr) : "memory");
}
__device__ __forceinline__ void mma16816(float* d, const uint32_t* a, uint32_t b0, uint32_t b1) {
    asm volatile("mma.sync.aligned.m16n8k16.row.col.f32.bf16.bf16.f32 {%0,%1,%2,%3}, {%4,%5,%6,%7}, {%8,%9}, {%0,%1,%2,%3};"
        : "+f"(d[0]), "+f"(d[1]), "+f"(d[2]), "+f"(d[3]) : "r"(a[0]), "r"(a[1]), "r"(a[2]), "r"(a[3]), "r"(b0), "r"(b1));
}
__device__ __forceinline__ uint32_t pack_bf16(float lo, float hi) {
    uint32_t r; asm("cvt.rn.bf16x2.f32 %0, %1, %2;" : "=r"(r) : "f"(hi), "f"(lo)); return r;
}
__device__ __forceinline__ float bf16r(float x) { return __bfloat162float(__float2bfloat16_rn(x)); }
__device__ __forceinline__ uint4 lds128(uint32_t a) { uint4 v; asm volatile("ld.shared.v4.u32 {%0,%1,%2,%3}, [%4];" : "=r"(v.x), "=r"(v.y), "=r"(v.z), "=r"(v.w) : "r"(a) : "memory"); return v; }
__device__ __forceinline__ void sts128(uint32_t a, uint4 v) { asm volatile("st.shared.v4.u32 [%0], {%1,%2,%3,%4};" :: "r"(a), "r"(v.x), "r"(v.y), "r"(v.z), "r"(v.w) : "memory"); }
__device__ __forceinline__ void sts32(uint32_t a, uint32_t v) { asm volatile("st.shared.u32 [%0], %1;" :: "r"(a), "r"(v) : "memory"); }
__device__ __forceinline__ void sts64(uint32_t a, uint32_t x, uint32_t y) { asm volatile("st.shared.v2.u32 [%0], {%1,%2};" :: "r"(a), "r"(x), "r"(y) : "memory"); }
__device__ __forceinline__ void sts16(uint32_t a, uint16_t v) { asm volatile("st.shared.u16 [%0], %1;" :: "r"(a), "h"(v) : "memory"); }
__device__ __forceinline__ uint2 lds64(uint32_t a) { uint2 v; asm volatile("ld.shared.v2.u32 {%0,%1}, [%2];" : "=r"(v.x), "=r"(v.y) : "r"(a) : "memory"); return v; }
__device__ __forceinline__ void cp_async16(uint32_t dst, const void* src) { asm volatile("cp.async.cg.shared.global [%0], [%1], 16;" :: "r"(dst), "l"(src) : "memory"); }
__device__ __forceinline__ void cp_async_wait_all() { asm volatile("cp.async.wait_all;" ::: "memory"); }
__device__ __forceinline__ void bar_sync(int id, int n) { asm volatile("bar.sync %0, %1;" :: "r"(id), "r"(n) : "memory"); }
__device__ __forceinline__ uint4 ld_relaxed_v4(const void* p) {
    uint4 v; asm volatile("ld.relaxed.gpu.global.v4.u32 {%0,%1,%2,%3}, [%4];" : "=r"(v.x), "=r"(v.y), "=r"(v.z), "=r"(v.w) : "l"(p) : "memory"); return v;
}
__device__ __forceinline__ void st_relaxed_v4(void* p, uint4 v) {
    asm volatile("st.relaxed.gpu.global.v4.u32 [%0], {%1,%2,%3,%4};" :: "l"(p), "r"(v.x), "r"(v.y), "r"(v.z), "r"(v.w) : "memory");
}
__device__ __forceinline__ uint32_t ld_acquire(const uint32_t* p) { uint32_t v; asm volatile("ld.acquire.gpu.global.u32 %0, [%1];" : "=r"(v) : "l"(p) : "memory"); return v; }
__device__ __forceinline__ uint32_t ld_relaxed(const uint32_t* p) { uint32_t v; asm volatile("ld.relaxed.gpu.global.u32 %0, [%1];" : "=r"(v) : "l"(p) : "memory"); return v; }
__device__ __forceinline__ void st_release(uint32_t* p, uint32_t v) { asm volatile("st.release.gpu.global.u32 [%0], %1;" :: "l"(p), "r"(v) : "memory"); }
__device__ __forceinline__ void cluster_sync_all() {
    asm volatile("barrier.cluster.arrive.release.aligned;" ::: "memory");
    asm volatile("barrier.cluster.wait.acquire.aligned;" ::: "memory");
}

__device__ bf16 g_k[2048 * 4096];
__device__ bf16 g_v[2048 * 4096];
__device__ bf16 g_km[64 * 8 * 4096];
__device__ bf16 g_vm[64 * 8 * 4096];
__device__ uint4 g_gx[2][4][16][80];
__device__ uint32_t g_kvflag[16 * 64];
__device__ uint32_t g_epoch;
struct GState {
    uint32_t done, c_mod_a, c_mod_all, unused0;
    uint32_t pad0[28];
    uint32_t ready[3], lq_claim, exh[4];
    uint32_t pad1[24];
    uint32_t cnt[96 * 8];
    uint32_t f_h[16 * 32];
    uint32_t d_at[16 * 32];
    uint32_t c_at[16 * 32];
    uint32_t c_wo[16 * 32];
    uint32_t f_h2[16 * 32];
    uint32_t c_act[16 * 32];
    uint32_t c_f2[16 * 32];
};
__device__ GState g_st;
namespace gk {
enum { T_MOD, T_L1, T_KV, T_Q, T_AT, T_WO, T_L2, T_F1, T_F2, T_FIN, T_SKIP, T_END };
#define FINE_RB 13
__host__ __device__ __forceinline__ bool fine(int rb) { return rb >= FINE_RB; }
#define WO_FINE 16
#define WO_COARSE 8
__host__ __device__ __forceinline__ int wo_split(int rb) { return fine(rb) ? WO_FINE : WO_COARSE; }
__host__ __device__ __forceinline__ int f2_split(int rb) { return fine(rb) ? 9 : 3; }
__host__ __device__ __forceinline__ int n_nt(int rb) { return fine(rb) ? 5 : 3; }
__host__ __device__ __forceinline__ int n_f1(int rb) { return fine(rb) ? 27 : 14; }
__host__ __device__ __forceinline__ int group_size(int ty, int rb) {
    switch (ty) {
        case T_AT: return 32;
        case T_WO: return n_nt(rb) * wo_split(rb);
        case T_F1: return n_f1(rb);
        case T_F2: return n_nt(rb) * f2_split(rb);
        default: return 16;
    }
}
}
__device__ __forceinline__ uint32_t atom_add_acqrel(uint32_t* p, uint32_t v) {
    uint32_t o; asm volatile("atom.acq_rel.gpu.global.add.u32 %0, [%1], %2;" : "=r"(o) : "l"(p), "r"(v) : "memory"); return o;
}
__device__ __forceinline__ void red_release_inc(uint32_t* p) { asm volatile("red.release.gpu.global.add.u32 [%0], 1;" :: "l"(p) : "memory"); }
__device__ __forceinline__ void publish_group(int ty, int rb, uint32_t) {
    const int gi = (ty - gk::T_AT) * 16 + rb;
    asm volatile("red.release.gpu.global.or.b32 [%0], %1;" :: "l"(&g_st.ready[gi >> 5]), "r"(1u << (gi & 31)) : "memory");
}
#define RT(i)

#define POLL_DELAY 300
#define MEMSH 1
namespace rk {
constexpr int MEM_STRIDE = 1296;
constexpr int T_STRIDE = 272;
constexpr int OFF_W = 0;
constexpr int OFF_KX = 163840;
constexpr int OFF_VX = OFF_KX + 8192;
constexpr int OFF_MEM = OFF_VX + 8192;
constexpr int OFF_Q = OFF_MEM + 10240;
constexpr int OFF_KM = OFF_Q + 8 * T_STRIDE;
constexpr int OFF_VM = OFF_KM + 8 * T_STRIDE;
constexpr int OFF_O = OFF_VM + 8 * T_STRIDE;
constexpr int OFF_SC = OFF_O + 8 * T_STRIDE;
constexpr int OFF_RED = OFF_SC + 8 * 56 * 4;
constexpr int OFF_RS = OFF_RED + 6144;
constexpr int OFF_ST = OFF_RS + 8 * 80 * 16;
constexpr int OFF_BAR = OFF_ST + 640;
constexpr int OFF_TL = OFF_BAR + 128;
constexpr int SMEM_BYTES = OFF_TL + 512;

__device__ __forceinline__ uint32_t ldg_nc(const void* p) { uint32_t v; asm volatile("ld.global.nc.u32 %0, [%1];" : "=r"(v) : "l"(p)); return v; }
__device__ __forceinline__ void load_raw(uint32_t* a, const bf16* __restrict__ W, int ld, int ka, int kb, int cb, int g, int t) {
    const bf16* p = W + (uint32_t)((ka + 2 * t) * ld + cb + 2 * g);
    const bf16* q = W + (uint32_t)((kb + 2 * t) * ld + cb + 2 * g);
    a[0] = ldg_nc(p); a[1] = ldg_nc(p + ld); a[2] = ldg_nc(q); a[3] = ldg_nc(q + ld);
}
__device__ __forceinline__ void fix_frag(uint32_t* a) {
    const uint32_t w0 = a[0], w1 = a[1], w2 = a[2], w3 = a[3];
    a[0] = __byte_perm(w0, w1, 0x5410); a[1] = __byte_perm(w0, w1, 0x7632);
    a[2] = __byte_perm(w2, w3, 0x5410); a[3] = __byte_perm(w2, w3, 0x7632);
}
__device__ __forceinline__ int chunk_src(int d, int kh, int n) { return (d - 8 * kh - n / 5) & 15; }
__device__ __forceinline__ int chunk_col(int d, int kh, int n) { const int s = chunk_src(d, kh, n); return 320 * (s & 1) + 40 * (s >> 1) + 8 * (n % 5); }
}

#define RSTEP 20
#define TL(i)
#define TG(i)

__device__ __forceinline__ void tma_load_2d(uint32_t dst, const CUtensorMap* map, int c0, int c1, uint32_t bar) {
    asm volatile("cp.async.bulk.tensor.2d.shared::cluster.global.mbarrier::complete_tx::bytes [%0], [%1, {%3, %4}], [%2];"
        :: "r"(dst), "l"(map), "r"(bar), "r"(c0), "r"(c1) : "memory");
}
__device__ __forceinline__ uint32_t movmatrix_t(uint32_t a) { uint32_t d; asm volatile("movmatrix.sync.aligned.m8n8.trans.b16 %0, %1;" : "=r"(d) : "r"(a)); return d; }
__device__ __forceinline__ void stg128(void* p, uint4 v) { asm volatile("st.global.v4.u32 [%0], {%1,%2,%3,%4};" :: "l"(p), "r"(v.x), "r"(v.y), "r"(v.z), "r"(v.w) : "memory"); }

__global__ void __launch_bounds__(256, 1)
r_kernel(const __grid_constant__ CUtensorMap tmK, const __grid_constant__ CUtensorMap tmV, const bf16* __restrict__ mem0, const bf16* __restrict__ Wq, const bf16* __restrict__ Wk, const bf16* __restrict__ Wv, const bf16* __restrict__ Wo, int wait_kv)
{
    using namespace rk;
    extern __shared__ __align__(1024) uint8_t smem[];
    const uint32_t sb = smem_u32(smem);
    const int tid = threadIdx.x, warp = tid >> 5, lane = tid & 31, g = lane >> 2, t = lane & 3;
    uint32_t rank, cid;
    asm volatile("mov.u32 %0, %%cluster_ctarank;" : "=r"(rank));
    asm volatile("mov.u32 %0, %%clusterid.x;" : "=r"(cid));
    const int hh = rank >> 1, j = rank & 1, h = cid * 8 + hh;
    const int kh = warp & 1, mb = warp >> 1;
    const uint32_t b_mem = sb + OFF_BAR, b_qkv = b_mem + 64, b_rs = b_mem + 72, b_kv = b_mem + 80;

    RT(64);
    asm volatile("griddepcontrol.launch_dependents;");
    const uint32_t epoch = ld_relaxed(&g_epoch);

    if (tid == 0) {
        for (int i = 0; i < 8; i++) mbar_init(b_mem + 8 * i, 1);
        mbar_init(b_qkv, 9); mbar_init(b_rs, 1); mbar_init(b_kv, 1);
        asm volatile("fence.mbarrier_init.release.cluster;" ::: "memory");
    }
    const uint32_t wsm = sb + OFF_W + (warp < 4 ? warp * 22528 : 4 * 22528 + (warp - 4) * 18432) + lane * 16;
    {
        const size_t co = (size_t)h * 128 + 64 * j;
        for (int i = tid; i < 640; i += 256) {
            asm volatile("prefetch.global.L2 [%0];" :: "l"(Wv + (size_t)i * 4096 + co));
            asm volatile("prefetch.global.L2 [%0];" :: "l"(Wo + ((size_t)h * 128 + i / 5) * 640 + 320 * j + (i % 5) * 64));
            asm volatile("prefetch.global.L2 [%0];" :: "l"(Wq + (size_t)i * 4096 + co));
            asm volatile("prefetch.global.L2 [%0];" :: "l"(Wk + (size_t)i * 4096 + co));
        }
    }
    uint32_t wq[20][4], wk[20][4];
    {
        const int cb = h * 128 + 64 * j + 16 * mb;
#pragma unroll
        for (int i = 0; i < 20; i++) load_raw(wq[i], Wv, 4096, chunk_col(rank, kh, 2 * i), chunk_col(rank, kh, 2 * i + 1), cb, g, t);
        const bf16* Woh = Wo + (size_t)h * 128 * 640;
        const int c3 = 320 * j + 16 * warp;
#pragma unroll
        for (int i = 0; i < 16; i++) load_raw(wk[i], Woh, 640, (i & 7) * 16, (i & 7) * 16 + 8, c3 + 128 * (i >> 3), g, t);
#pragma unroll
        for (int i = 0; i < 20; i++) { fix_frag(wq[i]); sts128(wsm + i * 512, make_uint4(wq[i][0], wq[i][1], wq[i][2], wq[i][3])); }
        if (warp < 4) {
#pragma unroll
            for (int i = 0; i < 8; i++) load_raw(wq[i], Woh, 640, i * 16, i * 16 + 8, c3 + 256, g, t);
        }
#pragma unroll
        for (int i = 0; i < 16; i++) { fix_frag(wk[i]); sts128(wsm + (20 + i) * 512, make_uint4(wk[i][0], wk[i][1], wk[i][2], wk[i][3])); }
#pragma unroll
        for (int i = 0; i < 20; i++) load_raw(wk[i], Wk, 4096, chunk_col(rank, kh, 2 * i), chunk_col(rank, kh, 2 * i + 1), cb, g, t);
        if (warp < 4) {
#pragma unroll
            for (int i = 0; i < 8; i++) { fix_frag(wq[i]); sts128(wsm + (36 + i) * 512, make_uint4(wq[i][0], wq[i][1], wq[i][2], wq[i][3])); }
        }
#pragma unroll
        for (int i = 0; i < 20; i++) load_raw(wq[i], Wq, 4096, chunk_col(rank, kh, 2 * i), chunk_col(rank, kh, 2 * i + 1), cb, g, t);
#pragma unroll
        for (int i = 0; i < 20; i++) { fix_frag(wk[i]); fix_frag(wq[i]); }
    }
    for (int i = tid; i < 640; i += 256) {
        int row = i / 80, c = i % 80;
        uint4 v = __ldg((const uint4*)(mem0 + row * 640 + c * 8));
        const int jj = c / 40, h5 = (c % 40) / 5;
        sts128(sb + OFF_MEM + (((int)rank - (2 * h5 + jj)) & 15) * 640 + row * 80 + (c % 5) * 16, v);
    }
    auto prefetch_kv = [&](int s) {
        if ((wait_kv & 1) && (s & 3) == 0) {
            const uint32_t* fk = &g_kvflag[(s >> 2) * 64 + h];
            int lim = 0;
            while (ld_acquire(fk) != epoch + 1) { if (++lim > SPIN_LIMIT) break; }
            while (ld_acquire(fk + 32) != epoch + 1) { if (++lim > SPIN_LIMIT) break; }
            asm volatile("fence.proxy.async.global;" ::: "memory");
        }
        mbar_expect_tx(b_kv, 16384);
        tma_load_2d(sb + OFF_KX, &tmK, h * 128, s * 32, b_kv);
        tma_load_2d(sb + OFF_KX + 4096, &tmK, h * 128 + 64, s * 32, b_kv);
        tma_load_2d(sb + OFF_VX, &tmV, h * 128, s * 32, b_kv);
        tma_load_2d(sb + OFF_VX + 4096, &tmV, h * 128 + 64, s * 32, b_kv);
    };
    __syncthreads();
    RT(65);
    __syncthreads();
    cluster_sync_all();

    const float scale = 0.08838834764831845f;
#define LAUNDER() int tid_ = threadIdx.x; asm volatile("" : "+r"(tid_)); const int warp = tid_ >> 5, lane = tid_ & 31, g = lane >> 2, t = lane & 3; (void)g; (void)t; (void)warp;
#define WSM() (sb + OFF_W + (warp < 4 ? warp * 22528 : 4 * 22528 + (warp - 4) * 18432) + lane * 16)

#pragma unroll 1
    for (int s = 0; s < 64; s++) {
        const uint32_t ph = s & 1;
        RT(s);
        {
            LAUNDER();
            TL(0);
            const int kh = warp & 1, mb = warp >> 1;
            const uint32_t wsm = WSM();
            const uint32_t mb0 = sb + OFF_MEM + kh * 5120 + (lane & 7) * 80 + (lane >> 3) * 16;
            const uint32_t mb1 = mb0 + ((lane >> 3) >= 1 ? 560 : 0), mb2 = mb0 + ((lane >> 3) >= 2 ? 560 : 0), mb3 = mb0 + ((lane >> 3) >= 3 ? 560 : 0);
            auto baddr = [&](int it) {
                const int r5 = (4 * it) % 5, c = ((4 * it) / 5) * 640 + r5 * 16;
                return (r5 <= 1 ? mb0 : (r5 == 4 ? mb1 : (r5 == 3 ? mb2 : mb3))) + c;
            };
            uint4 va[6];
            va[0] = lds128(wsm); va[1] = lds128(wsm + 512); va[2] = lds128(wsm + 1024); va[3] = lds128(wsm + 1536);
            if (s > 0) mbar_wait(b_mem, ph ^ 1);
            TL(1); TG(15);
            float aq0[4] = {0, 0, 0, 0}, aq1[4] = {0, 0, 0, 0}, ak0[4] = {0, 0, 0, 0}, ak1[4] = {0, 0, 0, 0}, av0[4] = {0, 0, 0, 0}, av1[4] = {0, 0, 0, 0};
            uint32_t b[3][4];
            ldsm_x4(b[0], baddr(0)); ldsm_x4(b[1], baddr(1));
            if (tid_ == 0) {
                mbar_expect_tx(b_qkv, 3072);
                if (s < 63) mbar_expect_tx(b_rs, 10240);
            }
#pragma unroll
            for (int i = 0; i < 10; i++) {
                if (i + 2 < 10) {
                    const int it = i + 2, sl = ((4 * it + 3) / 5) >> MEMSH, slp = ((4 * (it - 1) + 3) / 5) >> MEMSH;
                    if (sl != slp && s > 0) mbar_wait(b_mem + 8 * sl, ph ^ 1);
                    ldsm_x4(b[(i + 2) % 3], baddr(i + 2));
                    va[(2 * i + 4) % 6] = lds128(wsm + (2 * i + 4) * 512); va[(2 * i + 5) % 6] = lds128(wsm + (2 * i + 5) * 512);
                }
                const uint32_t* bb = b[i % 3];
                mma16816(aq0, wq[2 * i], bb[0], bb[1]); mma16816(ak0, wk[2 * i], bb[0], bb[1]); mma16816(av0, (uint32_t*)&va[(2 * i) % 6], bb[0], bb[1]);
                mma16816(aq1, wq[2 * i + 1], bb[2], bb[3]); mma16816(ak1, wk[2 * i + 1], bb[2], bb[3]); mma16816(av1, (uint32_t*)&va[(2 * i + 1) % 6], bb[2], bb[3]);
            }
            float snd[4], fin[4];
#pragma unroll
            for (int i = 0; i < 4; i++) { float q = aq0[i] + aq1[i], k = ak0[i] + ak1[i]; snd[i] = kh ? q : k; fin[i] = kh ? k : q; av0[i] += av1[i]; }
            sts128(sb + OFF_RED + tid_ * 16, make_uint4(__float_as_uint(snd[0]), __float_as_uint(snd[1]), __float_as_uint(snd[2]), __float_as_uint(snd[3])));
            sts64(sb + OFF_RED + 4096 + tid_ * 8, __float_as_uint(kh ? av0[0] : av0[1]), __float_as_uint(kh ? av0[2] : av0[3]));
            bar_sync(1 + mb, 64);
            uint4 r = lds128(sb + OFF_RED + (tid_ ^ 32) * 16);
            uint2 r2 = lds64(sb + OFF_RED + 4096 + (tid_ ^ 32) * 8);
            fin[0] += __uint_as_float(r.x); fin[1] += __uint_as_float(r.y); fin[2] += __uint_as_float(r.z); fin[3] += __uint_as_float(r.w);
            float f0 = (kh ? av0[1] : av0[0]) + __uint_as_float(r2.x), f1 = (kh ? av0[3] : av0[2]) + __uint_as_float(r2.y);
            TL(2);
            const uint32_t cofs = (64 * j + 16 * mb) * 2;
            const uint32_t buf = sb + (kh ? OFF_KM : OFF_Q) + cofs;
            sts32(buf + (2 * t) * T_STRIDE + g * 4, pack_bf16(fin[0], fin[2]));
            sts32(buf + (2 * t + 1) * T_STRIDE + g * 4, pack_bf16(fin[1], fin[3]));
            sts32(sb + OFF_VM + cofs + (2 * t + kh) * T_STRIDE + g * 4, pack_bf16(f0, f1));
            __syncwarp();
            if (lane < 24) {
                const uint32_t peer_off = mapa_u32(sb, rank ^ 1) - sb;
                const int row = lane < 16 ? (lane >> 1) : 2 * ((lane - 16) >> 1) + kh;
                const uint32_t a = (lane < 16 ? buf : sb + OFF_VM + cofs) + row * T_STRIDE + (lane & 1) * 16;
                uint4 v = lds128(a);
                st_async_v4(a + peer_off, v.x, v.y, v.z, v.w, b_qkv + peer_off);
                if ((kh || lane >= 16) && !(wait_kv & 8)) {
                    bf16* dst = (lane < 16 ? g_km : g_vm) + ((uint32_t)(s * 8 + row) * 4096u + h * 128 + 64 * j + 16 * mb + (lane & 1) * 8);
                    stg128(dst, v);
                }
            }
            if (lane == 0) mbar_arrive(b_qkv);
            if (s == 0 && tid_ == 224) prefetch_kv(0);
            TL(3);
        }
        if (s == 63) {
            __syncthreads();
            if (threadIdx.x == 0 && (wait_kv & 1)) red_release_inc(&g_st.d_at[15 * 32]);
            break;
        }
        uint4 wa[8];
        {
            LAUNDER();
            const uint32_t wsm = WSM();
            if (!(wait_kv & 2) || s == 0) mbar_wait(b_kv, ph);
            if (warp >= 4 && warp < 7) {
                const int kw = warp - 4;
                uint32_t ka[8][4];
                if (kw < 2) {
                    const uint32_t kaddr = sb + OFF_KX + (16 * kw + (lane & 15)) * 128;
#pragma unroll
                    for (int i = 0; i < 8; i++) ldsm_x4(ka[i], kaddr + (i >> 2) * 4096 + ((((2 * i + (lane >> 4)) & 7) ^ (lane & 7)) << 4));
                    mbar_wait(b_qkv, ph);
                } else {
                    mbar_wait(b_qkv, ph);
                    const uint32_t kaddr = sb + OFF_KM + (lane & 7) * T_STRIDE + (lane >> 4) * 16;
#pragma unroll
                    for (int i = 0; i < 8; i++) ldsm_x4(ka[i], kaddr + i * 32);
                }
                TL(5);
                const uint32_t qa = sb + OFF_Q + (lane & 7) * T_STRIDE + (lane >> 3) * 16;
                uint32_t qb[4][4];
#pragma unroll
                for (int i = 0; i < 4; i++) ldsm_x4(qb[i], qa + i * 64);
                float s0[4] = {0, 0, 0, 0}, s1[4] = {0, 0, 0, 0}, s2[4] = {0, 0, 0, 0}, s3[4] = {0, 0, 0, 0};
                mma16816(s0, ka[0], qb[0][0], qb[0][1]); mma16816(s1, ka[1], qb[0][2], qb[0][3]);
                mma16816(s2, ka[2], qb[1][0], qb[1][1]); mma16816(s3, ka[3], qb[1][2], qb[1][3]);
                mma16816(s0, ka[4], qb[2][0], qb[2][1]); mma16816(s1, ka[5], qb[2][2], qb[2][3]);
                mma16816(s2, ka[6], qb[3][0], qb[3][1]); mma16816(s3, ka[7], qb[3][2], qb[3][3]);
                const uint32_t sc = sb + OFF_SC + (16 * kw + g) * 4 + (2 * t) * 224;
                sts32(sc, __float_as_uint(bf16r(bf16r((s0[0] + s1[0]) + (s2[0] + s3[0])) * scale)));
                sts32(sc + 224, __float_as_uint(bf16r(bf16r((s0[1] + s1[1]) + (s2[1] + s3[1])) * scale)));
                if (kw < 2) {
                    sts32(sc + 32, __float_as_uint(bf16r(bf16r((s0[2] + s1[2]) + (s2[2] + s3[2])) * scale)));
                    sts32(sc + 32 + 224, __float_as_uint(bf16r(bf16r((s0[3] + s1[3]) + (s2[3] + s3[3])) * scale)));
                }
                asm volatile("bar.arrive 6, 224;" ::: "memory");
                TL(4);
#pragma unroll
                for (int i = 0; i < 8; i++) wa[i] = lds128(wsm + (20 + i) * 512);
            } else {
#pragma unroll
                for (int i = 0; i < 8; i++) wa[i] = lds128(wsm + (20 + i) * 512);
                if (warp < 4) {
                    mbar_wait(b_qkv, ph);
                    uint32_t a0[2][4], a1[2][4], a2[2][4];
#pragma unroll
                    for (int u = 0; u < 2; u++) {
                        const int et = warp + 4 * u;
                        const uint32_t vx = sb + OFF_VX + u * 4096 + ((lane >> 4) * 8 + (lane & 7)) * 128 + ((((2 * warp + ((lane >> 3) & 1)) & 7) ^ (lane & 7)) << 4);
                        ldsm_x4_t(a0[u], vx); ldsm_x4_t(a1[u], vx + 16 * 128);
                        ldsm_x4_t(a2[u], sb + OFF_VM + (lane & 7) * T_STRIDE + (16 * et + ((lane >> 3) & 1) * 8) * 2);
                    }
                    bar_sync(6, 224);
                    TL(6);
                    float x[10];
#pragma unroll
                    for (int i = 0; i < 5; i++) { uint2 v = lds64(sb + OFF_SC + g * 224 + (8 * i + 2 * t) * 4); x[2 * i] = __uint_as_float(v.x); x[2 * i + 1] = __uint_as_float(v.y); }
                    float m = fmaxf(fmaxf(fmaxf(x[0], x[1]), fmaxf(x[2], x[3])), fmaxf(fmaxf(x[4], x[5]), fmaxf(x[6], x[7])));
                    m = fmaxf(m, fmaxf(x[8], x[9]));
                    m = fmaxf(m, __shfl_xor_sync(0xffffffff, m, 1)); m = fmaxf(m, __shfl_xor_sync(0xffffffff, m, 2));
                    float sum0 = 0, sum1 = 0;
#pragma unroll
                    for (int i = 0; i < 5; i++) { x[2 * i] = __expf(x[2 * i] - m); sum0 += x[2 * i]; x[2 * i + 1] = __expf(x[2 * i + 1] - m); sum1 += x[2 * i + 1]; }
                    float sum = sum0 + sum1;
                    sum += __shfl_xor_sync(0xffffffff, sum, 1); sum += __shfl_xor_sync(0xffffffff, sum, 2);
                    float inv = __fdividef(1.0f, sum);
                    if (inv == 123.f) TL(14);
                    TL(4);
                    uint32_t pb[5];
#pragma unroll
                    for (int i = 0; i < 5; i++) pb[i] = pack_bf16(x[2 * i] * inv, x[2 * i + 1] * inv);
#pragma unroll
                    for (int u = 0; u < 2; u++) {
                        float o0[4] = {0, 0, 0, 0}, o1[4] = {0, 0, 0, 0}, o2[4] = {0, 0, 0, 0};
                        mma16816(o0, a0[u], pb[0], pb[1]); mma16816(o1, a1[u], pb[2], pb[3]); mma16816(o2, a2[u], pb[4], 0u);
                        const uint32_t lo = movmatrix_t(pack_bf16((o0[0] + o1[0]) + o2[0], (o0[1] + o1[1]) + o2[1]));
                        const uint32_t hi = movmatrix_t(pack_bf16((o0[2] + o1[2]) + o2[2], (o0[3] + o1[3]) + o2[3]));
                        const uint32_t oa = sb + OFF_O + g * T_STRIDE + (16 * (warp + 4 * u) + 2 * t) * 2;
                        sts32(oa, lo); sts32(oa + 16, hi);
                    }
                    TL(5);
                } else {
                    if (lane < (8 >> MEMSH)) mbar_expect_tx(b_mem + 8 * lane, 1280 << MEMSH);
                }
            }
        }
        __syncthreads();
        {
            LAUNDER();
            TL(7);
            const uint32_t wsm = WSM();
            uint32_t ob[16];
            const uint32_t oa = sb + OFF_O + (lane & 7) * T_STRIDE + (lane >> 3) * 16;
#pragma unroll
            for (int i = 0; i < 4; i++) ldsm_x4(ob + 4 * i, oa + i * 64);
            const uint32_t rs_base = OFF_RS + hh * 1280 + t * 16;
            const int ntile = warp < 4 ? 3 : 2;
#pragma unroll 1
            for (int tl = 0; tl < ntile; tl++) {
                float d0[4] = {0, 0, 0, 0}, d1[4] = {0, 0, 0, 0}, d2[4] = {0, 0, 0, 0}, d3[4] = {0, 0, 0, 0};
                const bool more = tl + 1 < ntile;
                const uint32_t nx = wsm + (28 + 8 * tl) * 512;
                mma16816(d0, (uint32_t*)&wa[0], ob[0], ob[1]);   if (more) wa[0] = lds128(nx);
                mma16816(d1, (uint32_t*)&wa[1], ob[2], ob[3]);   if (more) wa[1] = lds128(nx + 512);
                mma16816(d2, (uint32_t*)&wa[2], ob[4], ob[5]);   if (more) wa[2] = lds128(nx + 1024);
                mma16816(d3, (uint32_t*)&wa[3], ob[6], ob[7]);   if (more) wa[3] = lds128(nx + 1536);
                mma16816(d0, (uint32_t*)&wa[4], ob[8], ob[9]);   if (more) wa[4] = lds128(nx + 2048);
                mma16816(d1, (uint32_t*)&wa[5], ob[10], ob[11]); if (more) wa[5] = lds128(nx + 2560);
                mma16816(d2, (uint32_t*)&wa[6], ob[12], ob[13]); if (more) wa[6] = lds128(nx + 3072);
                mma16816(d3, (uint32_t*)&wa[7], ob[14], ob[15]); if (more) wa[7] = lds128(nx + 3584);
                const int col = 16 * (warp + 8 * tl) + 2 * g; const int own = col / 40; const int cp = (col - own * 40) >> 1;
                const uint32_t dbase = mapa_u32(sb, 2 * own + j);
                st_async_v4(dbase + rs_base + cp * 64, __float_as_uint((d0[0] + d1[0]) + (d2[0] + d3[0])), __float_as_uint((d0[1] + d1[1]) + (d2[1] + d3[1])),
                            __float_as_uint((d0[2] + d1[2]) + (d2[2] + d3[2])), __float_as_uint((d0[3] + d1[3]) + (d2[3] + d3[3])), dbase + OFF_BAR + 72);
            }
            TL(8);
        }
        {
            LAUNDER();
            if (warp >= 5) {
                const int x = tid_ - 160;
                const int ot = x < 80 ? x : 79;
                const uint32_t gs = epoch * 64 + s; const uint32_t tag = (gs + 1) & 15u; const int slot = gs & 1;
                uint4* gp = &g_gx[slot][0][rank][ot];
                mbar_wait(b_rs, ph);
                TL(9); TG(12);
                uint4 u[8];
#pragma unroll
                for (int q = 0; q < 8; q++) u[q] = lds128(sb + OFF_RS + q * 1280 + ot * 16);
                float4 a;
                a.x = ((__uint_as_float(u[0].x) + __uint_as_float(u[1].x)) + (__uint_as_float(u[2].x) + __uint_as_float(u[3].x))) + ((__uint_as_float(u[4].x) + __uint_as_float(u[5].x)) + (__uint_as_float(u[6].x) + __uint_as_float(u[7].x)));
                a.y = ((__uint_as_float(u[0].y) + __uint_as_float(u[1].y)) + (__uint_as_float(u[2].y) + __uint_as_float(u[3].y))) + ((__uint_as_float(u[4].y) + __uint_as_float(u[5].y)) + (__uint_as_float(u[6].y) + __uint_as_float(u[7].y)));
                a.z = ((__uint_as_float(u[0].z) + __uint_as_float(u[1].z)) + (__uint_as_float(u[2].z) + __uint_as_float(u[3].z))) + ((__uint_as_float(u[4].z) + __uint_as_float(u[5].z)) + (__uint_as_float(u[6].z) + __uint_as_float(u[7].z)));
                a.w = ((__uint_as_float(u[0].w) + __uint_as_float(u[1].w)) + (__uint_as_float(u[2].w) + __uint_as_float(u[3].w))) + ((__uint_as_float(u[4].w) + __uint_as_float(u[5].w)) + (__uint_as_float(u[6].w) + __uint_as_float(u[7].w)));
                uint4 mine = make_uint4((__float_as_uint(a.x) & ~15u) | tag, (__float_as_uint(a.y) & ~15u) | tag, (__float_as_uint(a.z) & ~15u) | tag, (__float_as_uint(a.w) & ~15u) | tag);
                if (x < 80) st_relaxed_v4(gp + cid * 1280, mine);
                { uint32_t c0, c1; asm volatile("mov.u32 %0, %%clock;" : "=r"(c0) :: "memory"); do { asm volatile("mov.u32 %0, %%clock;" : "=r"(c1) :: "memory"); } while (c1 - c0 < POLL_DELAY); }
                uint4 v[3];
                const uint4* rp0 = gp + (cid ^ 1) * 1280; const uint4* rp1 = gp + (cid ^ 2) * 1280; const uint4* rp2 = gp + (cid ^ 3) * 1280;
                int lim = 0;
                while (true) {
                    v[0] = ld_relaxed_v4(rp0); v[1] = ld_relaxed_v4(rp1); v[2] = ld_relaxed_v4(rp2);
                    uint32_t bad = 0;
#pragma unroll
                    for (int c = 0; c < 3; c++) bad |= (v[c].x ^ tag) | (v[c].y ^ tag) | (v[c].z ^ tag) | (v[c].w ^ tag);
                    if ((bad & 15u) == 0) break;
                    if (++lim > SPIN_LIMIT) break;
                }
                float f0 = (__uint_as_float(mine.x) + __uint_as_float(v[0].x)) + (__uint_as_float(v[1].x) + __uint_as_float(v[2].x));
                float f1 = (__uint_as_float(mine.y) + __uint_as_float(v[0].y)) + (__uint_as_float(v[1].y) + __uint_as_float(v[2].y));
                float f2 = (__uint_as_float(mine.z) + __uint_as_float(v[0].z)) + (__uint_as_float(v[1].z) + __uint_as_float(v[2].z));
                float f3 = (__uint_as_float(mine.w) + __uint_as_float(v[0].w)) + (__uint_as_float(v[1].w) + __uint_as_float(v[2].w));
                const int cp = ot >> 2, tt = ot & 3;
                sts32(sb + OFF_ST + (2 * tt) * 80 + cp * 4, pack_bf16(f0, f2));
                sts32(sb + OFF_ST + (2 * tt + 1) * 80 + cp * 4, pack_bf16(f1, f3));
                TL(10); TG(13);
                bar_sync(5, 128);
                if (x < 80) {
                    const int c = x % 40, d0 = x / 40;
                    uint4 w = lds128(sb + OFF_ST + c * 16);
                    const uint32_t off = OFF_MEM + d0 * 5120 + c * 16;
#pragma unroll
                    for (int i = 0; i < 8; i++) {
                        const uint32_t rb = mapa_u32(sb, (d0 * 8 + i + rank) & 15);
                        st_async_v4(rb + off + i * 640, w.x, w.y, w.z, w.w, rb + OFF_BAR + 8 * (i >> MEMSH));
                    }
                }
            } else if (warp == 4) {
                if (lane == 0 && (s & 3) == 3 && (wait_kv & 1)) red_release_inc(&g_st.d_at[(s >> 2) * 32]);
                __syncwarp();
            } else if (warp == 3) {
                bar_sync(5, 128);
                if (lane == 0 && s < 62 && !(wait_kv & 2)) prefetch_kv(s + 1);
                __syncwarp();
            }
            TL(11);
        }
    }
    cluster_sync_all();
}

__device__ float g_mod[3840];
__device__ bf16 g_h[2048 * 640];
__device__ bf16 g_q[2048 * 4096];
__device__ bf16 g_o[2048 * 4096];
__device__ bf16 g_x1[2048 * 640];
__device__ bf16 g_h2[2048 * 640];
__device__ bf16 g_act[2048 * 1728];
__device__ float g_slab[2048 * 640];

namespace gk {
constexpr int STAGES = 4;
constexpr int STAGE_BYTES = 49152;
constexpr int OFF_SCR = STAGES * STAGE_BYTES;
constexpr int OFF_BAR = OFF_SCR + 32768;
constexpr int SMEM_BYTES = OFF_BAR + 256 + 2048;
#define PRECLAIM_MOD 2
#define PRECLAIM_RB 15
#define LOW_LEAD 3
constexpr int N_MOD = 60, N_L1 = 256, N_KV = 32, N_Q = 16;
constexpr int I_L1 = N_MOD, I_W = I_L1 + N_L1;
constexpr int N_LOW = I_W + 16 * (N_KV + N_Q) + 32;
constexpr int NFINE = 16 - FINE_RB;
constexpr int N_HIGH = 16 * (32 + 16 + 16) + (16 - NFINE) * (3 * WO_COARSE + 14 + 9) + NFINE * (5 * WO_FINE + 27 + 45);
struct Item { int type, rb, nt, ks; };
__host__ __device__ inline Item decode_low(int t) {
    Item it; it.rb = 0; it.nt = 0; it.ks = 0;
    if (t < I_L1) { it.type = T_MOD; it.nt = t; return it; }
    if (t < I_L1 + 16) { it.type = T_L1; it.rb = 0; it.nt = t - I_L1; return it; }
    if (t < I_L1 + 80) { it.type = T_KV; it.rb = 0; it.nt = t - I_L1 - 16; it.ks = 1; return it; }
    if (t < I_L1 + 112) { it.type = T_L1; it.rb = (t - I_L1 - 64) >> 4; it.nt = (t - I_L1 - 64) & 15; return it; }
    if (t < I_L1 + 144) { it.type = T_KV; it.rb = 1; it.nt = t - I_L1 - 112; return it; }
    if (t < I_W + 96) { it.type = T_L1; it.rb = (t - I_L1 - 96) >> 4; it.nt = (t - I_L1 - 96) & 15; return it; }
    t -= I_W + 96;
    if (t < 14 * 48) { const int w = t / 48; t -= w * 48; if (t < 16) { it.type = T_Q; it.rb = w; it.nt = t; } else { it.type = T_KV; it.rb = w + 2; it.nt = t - 16; } return it; }
    t -= 14 * 48;
    it.type = T_Q; it.rb = 14 + (t >> 4); it.nt = t & 15; return it;
}
__device__ __forceinline__ bool is_wide(const Item& it) {
    if (it.type == T_KV || it.type == T_Q) return it.ks == 0;
    if (it.type == T_F1) return !fine(it.rb);
    if (it.type == T_WO || it.type == T_F2) return !fine(it.rb) && it.nt < 2;
    return false;
}
__device__ __forceinline__ int red_col(const Item& it) { return fine(it.rb) ? it.nt * 128 : it.nt * 256; }
__device__ __forceinline__ int pack_item(const Item& it) { return it.type | (it.rb << 4) | (it.nt << 8) | (it.ks << 16); }
__device__ __forceinline__ Item unpack_item(int v) { Item it; it.type = v & 15; it.rb = (v >> 4) & 15; it.nt = (v >> 8) & 255; it.ks = (v >> 16) & 255; return it; }
}

struct GParams {
    CUtensorMap tA_h, tA_o, tA_h2, tA_act, tB_q, tB_k, tB_v, tB_o, tB_g, tB_u, tB_d, tS_q, tS_k, tS_v, tS_act, tS_o, tL_q, tL_k, tL_v, tL_km, tL_vm, tR_acc;
};

__device__ __forceinline__ void wait_ge(const uint32_t* p, uint32_t target) {
    int lim = 0;
    while ((int32_t)(ld_acquire(p) - target) < 0) { __nanosleep(64); if (++lim > SPIN_LIMIT) break; }
}
__device__ __forceinline__ void red_add_relaxed(uint32_t* p, uint32_t v) { asm volatile("red.relaxed.gpu.global.add.u32 [%0], %1;" :: "l"(p), "r"(v) : "memory"); }
__device__ __forceinline__ void st_relaxed_u32(uint32_t* p, uint32_t v) { asm volatile("st.relaxed.gpu.global.u32 [%0], %1;" :: "l"(p), "r"(v) : "memory"); }
__device__ __forceinline__ void red_add_release(uint32_t* p, uint32_t v) { asm volatile("red.release.gpu.global.add.u32 [%0], %1;" :: "l"(p), "r"(v) : "memory"); }

__device__ __forceinline__ void wgmma_fence() { asm volatile("wgmma.fence.sync.aligned;" ::: "memory"); }
__device__ __forceinline__ void wgmma_commit() { asm volatile("wgmma.commit_group.sync.aligned;" ::: "memory"); }
template<int N> __device__ __forceinline__ void wgmma_wait() { asm volatile("wgmma.wait_group.sync.aligned %0;" :: "n"(N) : "memory"); }

template<int N> __device__ __forceinline__ void fence_acc(float* d) {
#pragma unroll
    for (int i = 0; i < N; i++) asm volatile("" : "+f"(d[i]) :: "memory");
}
#define ACC8(b) "+f"(d[b]), "+f"(d[b+1]), "+f"(d[b+2]), "+f"(d[b+3]), "+f"(d[b+4]), "+f"(d[b+5]), "+f"(d[b+6]), "+f"(d[b+7])
#define ACC32(b) ACC8(b), ACC8(b+8), ACC8(b+16), ACC8(b+24)
__device__ __forceinline__ void wgmma_n128(float* d, uint64_t da, uint64_t db, int scale_d) {
    asm volatile("{ .reg .pred p; setp.ne.b32 p, %66, 0;\n"
        "wgmma.mma_async.sync.aligned.m64n128k16.f32.bf16.bf16 {%0,%1,%2,%3,%4,%5,%6,%7,%8,%9,%10,%11,%12,%13,%14,%15,%16,%17,%18,%19,%20,%21,%22,%23,%24,%25,%26,%27,%28,%29,%30,%31,"
        "%32,%33,%34,%35,%36,%37,%38,%39,%40,%41,%42,%43,%44,%45,%46,%47,%48,%49,%50,%51,%52,%53,%54,%55,%56,%57,%58,%59,%60,%61,%62,%63}, %64, %65, p, 1, 1, 0, 1; }"
        : ACC32(0), ACC32(32) : "l"(da), "l"(db), "r"(scale_d));
}
__device__ __forceinline__ void wgmma_n256(float* d, uint64_t da, uint64_t db, int scale_d) {
    asm volatile("{ .reg .pred p; setp.ne.b32 p, %130, 0;\n"
        "wgmma.mma_async.sync.aligned.m64n256k16.f32.bf16.bf16 {%0,%1,%2,%3,%4,%5,%6,%7,%8,%9,%10,%11,%12,%13,%14,%15,%16,%17,%18,%19,%20,%21,%22,%23,%24,%25,%26,%27,%28,%29,%30,%31,"
        "%32,%33,%34,%35,%36,%37,%38,%39,%40,%41,%42,%43,%44,%45,%46,%47,%48,%49,%50,%51,%52,%53,%54,%55,%56,%57,%58,%59,%60,%61,%62,%63,"
        "%64,%65,%66,%67,%68,%69,%70,%71,%72,%73,%74,%75,%76,%77,%78,%79,%80,%81,%82,%83,%84,%85,%86,%87,%88,%89,%90,%91,%92,%93,%94,%95,"
        "%96,%97,%98,%99,%100,%101,%102,%103,%104,%105,%106,%107,%108,%109,%110,%111,%112,%113,%114,%115,%116,%117,%118,%119,%120,%121,%122,%123,%124,%125,%126,%127}, %128, %129, p, 1, 1, 0, 1; }"
        : ACC32(0), ACC32(32), ACC32(64), ACC32(96) : "l"(da), "l"(db), "r"(scale_d));
}
__device__ __forceinline__ uint64_t make_desc(uint32_t addr, uint32_t lbo, uint32_t sbo) {
    return (uint64_t)((addr & 0x3FFFF) >> 4) | ((uint64_t)(lbo >> 4) << 16) | ((uint64_t)(sbo >> 4) << 32) | ((uint64_t)1 << 62);
}

__device__ __forceinline__ float div_fix(float a, float b, float rb) { float q = a * rb; float r = fmaf(-q, b, a); return fmaf(r, rb, q); }
__device__ __forceinline__ void row_item(int mode, uint32_t sx, uint32_t sa, uint32_t sp, uint32_t bar_empty, float* __restrict__ acc, bf16* __restrict__ yout, bf16* __restrict__ out, int lane) {
    float x[20];
#pragma unroll
    for (int i = 0; i < 5; i++) {
        const uint2 v = lds64(sx + i * 256 + lane * 8);
        x[4 * i] = __uint_as_float(v.x << 16); x[4 * i + 1] = __uint_as_float(v.x & 0xffff0000u);
        x[4 * i + 2] = __uint_as_float(v.y << 16); x[4 * i + 3] = __uint_as_float(v.y & 0xffff0000u);
    }
    if (mode) {
#pragma unroll
        for (int i = 0; i < 5; i++) {
            const uint4 a = lds128(sa + i * 512 + lane * 16), gt = lds128(sp + i * 512 + lane * 16);
            x[4 * i] = bf16r(x[4 * i] + bf16r(__uint_as_float(gt.x) * bf16r(__uint_as_float(a.x)))); x[4 * i + 1] = bf16r(x[4 * i + 1] + bf16r(__uint_as_float(gt.y) * bf16r(__uint_as_float(a.y))));
            x[4 * i + 2] = bf16r(x[4 * i + 2] + bf16r(__uint_as_float(gt.z) * bf16r(__uint_as_float(a.z)))); x[4 * i + 3] = bf16r(x[4 * i + 3] + bf16r(__uint_as_float(gt.w) * bf16r(__uint_as_float(a.w))));
            *(uint2*)(yout + i * 128 + lane * 4) = make_uint2(pack_bf16(x[4 * i], x[4 * i + 1]), pack_bf16(x[4 * i + 2], x[4 * i + 3]));
            *(float4*)(acc + i * 128 + lane * 4) = make_float4(0.f, 0.f, 0.f, 0.f);
        }
        sp += 2560;
    }
    if (mode != 2) {
        float s = 0;
#pragma unroll
        for (int i = 0; i < 20; i++) s += x[i];
#pragma unroll
        for (int o = 16; o; o >>= 1) s += __shfl_xor_sync(0xffffffff, s, o);
        const float mean = s * (1.0f / 640.0f);
        float q = 0;
#pragma unroll
        for (int i = 0; i < 20; i++) { float d = x[i] - mean; q += d * d; }
#pragma unroll
        for (int o = 16; o; o >>= 1) q += __shfl_xor_sync(0xffffffff, q, o);
        const float m16 = bf16r(mean);
        const float sd = bf16r(sqrtf(bf16r(bf16r(q * (1.0f / 640.0f)) + 1e-5f)));
        const float rs = __frcp_rn(sd);
#pragma unroll
        for (int i = 0; i < 5; i++) {
            const uint4 sh = lds128(sp + i * 512 + lane * 16), sc = lds128(sp + 2560 + i * 512 + lane * 16);
            float y0 = bf16r(bf16r(div_fix(bf16r(x[4 * i] - m16), sd, rs)) * bf16r(1.0f + __uint_as_float(sc.x))) + __uint_as_float(sh.x);
            float y1 = bf16r(bf16r(div_fix(bf16r(x[4 * i + 1] - m16), sd, rs)) * bf16r(1.0f + __uint_as_float(sc.y))) + __uint_as_float(sh.y);
            float y2 = bf16r(bf16r(div_fix(bf16r(x[4 * i + 2] - m16), sd, rs)) * bf16r(1.0f + __uint_as_float(sc.z))) + __uint_as_float(sh.z);
            float y3 = bf16r(bf16r(div_fix(bf16r(x[4 * i + 3] - m16), sd, rs)) * bf16r(1.0f + __uint_as_float(sc.w))) + __uint_as_float(sh.w);
            *(uint2*)(out + i * 128 + lane * 4) = make_uint2(pack_bf16(y0, y1), pack_bf16(y2, y3));
        }
    }
    __syncwarp();
    if (lane == 0) mbar_arrive(bar_empty);
}

__device__ __forceinline__ float gelu_tanh(float x) {
    float u2 = x * fmaf(x * x, 2.0f * 0.7978845608028654f * 0.044715f * 1.4426950408889634f, 2.0f * 0.7978845608028654f * 1.4426950408889634f);
    float e; asm("ex2.approx.ftz.f32 %0, %1;" : "=f"(e) : "f"(-u2));
    return __fdividef(x, 1.0f + e);
}
__device__ __forceinline__ uint4 ldg128(const void* p) { uint4 v; asm volatile("ld.global.v4.u32 {%0,%1,%2,%3}, [%4];" : "=r"(v.x), "=r"(v.y), "=r"(v.z), "=r"(v.w) : "l"(p) : "memory"); return v; }
__device__ __forceinline__ float4 ldcg_f4(const float* p) { float4 v; asm volatile("ld.global.cg.v4.f32 {%0,%1,%2,%3}, [%4];" : "=f"(v.x), "=f"(v.y), "=f"(v.z), "=f"(v.w) : "l"(p) : "memory"); return v; }
__device__ __forceinline__ uint4 ldcg128(const void* p) { uint4 v; asm volatile("ld.global.cg.v4.u32 {%0,%1,%2,%3}, [%4];" : "=r"(v.x), "=r"(v.y), "=r"(v.z), "=r"(v.w) : "l"(p) : "memory"); return v; }

__device__ __forceinline__ void attn_scores(uint32_t sq, uint32_t sk, uint32_t skm, int sg, int mt, int lane, uint32_t (&p)[6][2]) {
    const int g = lane >> 2, t = lane & 3, l7 = lane & 7;
    float s[5][4];
#pragma unroll
    for (int kt = 0; kt < 5; kt++) s[kt][0] = s[kt][1] = s[kt][2] = s[kt][3] = 0.f;
    const uint32_t qrow = sq + (sg * 32 + mt * 16 + (lane & 15)) * 128;
    const uint32_t krow = sk + (sg * 32 + l7) * 128, kmrow = skm + (sg * 8 + l7) * 128;
#pragma unroll
    for (int c = 0; c < 4; c++) {
        uint32_t a0[4], a1[4];
        ldsm_x4(a0, qrow + (c >> 1) * 16384 + ((((4 * c + (lane >> 4)) & 7) ^ l7) << 4));
        ldsm_x4(a1, qrow + (c >> 1) * 16384 + ((((4 * c + 2 + (lane >> 4)) & 7) ^ l7) << 4));
        const uint32_t sw = (((4 * c + (lane >> 3)) & 7) ^ l7) << 4;
#pragma unroll
        for (int kt = 0; kt < 5; kt++) {
            uint32_t b[4];
            ldsm_x4(b, kt == 0 ? kmrow + (c >> 1) * 4096 + sw : krow + (kt - 1) * 1024 + (c >> 1) * 16384 + sw);
            mma16816(s[kt], a0, b[0], b[1]); mma16816(s[kt], a1, b[2], b[3]);
        }
    }
    const float scale = 0.08838834764831845f;
    const int r0 = mt * 16 + g, r1 = r0 + 8;
    float m0 = -INFINITY, m1 = -INFINITY;
#pragma unroll
    for (int kt = 0; kt < 5; kt++) {
#pragma unroll
        for (int i = 0; i < 4; i++) {
            float v = bf16r(bf16r(s[kt][i]) * scale);
            if (kt > 0) { int key = (kt - 1) * 8 + 2 * t + (i & 1); if (key > (i < 2 ? r0 : r1)) v = -1.0e9f; }
            s[kt][i] = v;
            if (i < 2) m0 = fmaxf(m0, v); else m1 = fmaxf(m1, v);
        }
    }
    m0 = fmaxf(m0, __shfl_xor_sync(0xffffffff, m0, 1)); m0 = fmaxf(m0, __shfl_xor_sync(0xffffffff, m0, 2));
    m1 = fmaxf(m1, __shfl_xor_sync(0xffffffff, m1, 1)); m1 = fmaxf(m1, __shfl_xor_sync(0xffffffff, m1, 2));
    float l0 = 0, l1 = 0;
#pragma unroll
    for (int kt = 0; kt < 5; kt++) {
        s[kt][0] = __expf(s[kt][0] - m0); s[kt][1] = __expf(s[kt][1] - m0); l0 += s[kt][0] + s[kt][1];
        s[kt][2] = __expf(s[kt][2] - m1); s[kt][3] = __expf(s[kt][3] - m1); l1 += s[kt][2] + s[kt][3];
    }
    l0 += __shfl_xor_sync(0xffffffff, l0, 1); l0 += __shfl_xor_sync(0xffffffff, l0, 2);
    l1 += __shfl_xor_sync(0xffffffff, l1, 1); l1 += __shfl_xor_sync(0xffffffff, l1, 2);
    const float i0 = __fdividef(1.0f, l0), i1 = __fdividef(1.0f, l1);
#pragma unroll
    for (int kt = 0; kt < 5; kt++) { p[kt][0] = pack_bf16(s[kt][0] * i0, s[kt][1] * i0); p[kt][1] = pack_bf16(s[kt][2] * i1, s[kt][3] * i1); }
    p[5][0] = p[5][1] = 0;
}
__device__ __forceinline__ void attn_pv(uint32_t sv, uint32_t svm, int sg, int lane, const uint32_t (&p)[6][2], float* d) {
    const int l7 = lane & 7, hi = (lane >> 3) & 1, ec = lane >> 4;
    const uint32_t r0 = hi ? sv + (sg * 32 + l7) * 128 : svm + (sg * 8 + l7) * 128;
    const uint32_t sub0 = hi ? 16384 : 4096;
    const uint32_t r1 = sv + (sg * 32 + 8 + hi * 8 + l7) * 128;
    const uint32_t r2 = sv + (sg * 32 + 24 + l7) * 128;
#pragma unroll
    for (int i = 0; i < 8; i++) {
        const uint32_t sw = (((2 * i + ec) & 7) ^ l7) << 4;
        uint32_t b0[4], b1[4], b2[4];
        ldsm_x4_t(b0, r0 + (i >> 2) * sub0 + sw); ldsm_x4_t(b1, r1 + (i >> 2) * 16384 + sw); ldsm_x4_t(b2, r2 + (i >> 2) * 16384 + sw);
        float* o0 = d + 8 * i; float* o1 = o0 + 4;
        o0[0] = o0[1] = o0[2] = o0[3] = o1[0] = o1[1] = o1[2] = o1[3] = 0.f;
        { uint32_t a[4] = {p[0][0], p[0][1], p[1][0], p[1][1]}; mma16816(o0, a, b0[0], b0[1]); mma16816(o1, a, b0[2], b0[3]); }
        { uint32_t a[4] = {p[2][0], p[2][1], p[3][0], p[3][1]}; mma16816(o0, a, b1[0], b1[1]); mma16816(o1, a, b1[2], b1[3]); }
        { uint32_t a[4] = {p[4][0], p[4][1], p[5][0], p[5][1]}; mma16816(o0, a, b2[0], b2[1]); mma16816(o1, a, b2[2], b2[3]); }
    }
}
__device__ __forceinline__ void bulk_load(uint32_t dst, const void* src, uint32_t bytes, uint32_t bar) {
    asm volatile("cp.async.bulk.shared::cluster.global.mbarrier::complete_tx::bytes [%0], [%1], %2, [%3];" :: "r"(dst), "l"(src), "r"(bytes), "r"(bar) : "memory");
}

__device__ __forceinline__ void stsm_x4(uint32_t addr, uint32_t a, uint32_t b, uint32_t c, uint32_t d) {
    asm volatile("stmatrix.sync.aligned.m8n8.x4.shared.b16 [%0], {%1,%2,%3,%4};" :: "r"(addr), "r"(a), "r"(b), "r"(c), "r"(d) : "memory");
}
__device__ __forceinline__ void tma_reduce_2d(const CUtensorMap* map, uint32_t src, int c0, int c1) {
    asm volatile("cp.reduce.async.bulk.tensor.2d.global.shared::cta.add.tile.bulk_group [%0, {%2, %3}], [%1];" :: "l"(map), "r"(src), "r"(c0), "r"(c1) : "memory");
}
__device__ __forceinline__ void tma_store_2d(const CUtensorMap* map, uint32_t src, int c0, int c1) {
    asm volatile("cp.async.bulk.tensor.2d.global.shared::cta.bulk_group [%0, {%2, %3}], [%1];" :: "l"(map), "r"(src), "r"(c0), "r"(c1) : "memory");
}

__global__ void __launch_bounds__(384, 1)
g_kernel(const __grid_constant__ GParams P, const bf16* __restrict__ x, const bf16* __restrict__ cvec, const bf16* __restrict__ w_mod, bf16* __restrict__ out, int nctas, int wait_r)
{
    using namespace gk;
    extern __shared__ __align__(1024) uint8_t smem[];
    const uint32_t sb = smem_u32(smem);
    const int tid = threadIdx.x, warp = tid >> 5, lane = tid & 31;
    const uint32_t b_full = sb + OFF_BAR, b_empty = b_full + 8 * STAGES, b_wfull = b_empty + 8 * STAGES, b_wempty = b_wfull + 16;
    const uint32_t b_cdone = b_wempty + 16, b_sfree = b_cdone + 16;
    volatile int* wslot = (volatile int*)(smem + OFF_BAR + 192);
    const uint32_t epoch = ld_relaxed(&g_epoch);
    const uint32_t e1 = epoch + 1;
    if (tid == 0) {
        wslot[4] = 0;
        for (int i = 0; i < STAGES; i++) { mbar_init(b_full + 8 * i, 1); mbar_init(b_empty + 8 * i, 8); }
        for (int i = 0; i < 2; i++) { mbar_init(b_wfull + 8 * i, 1); mbar_init(b_wempty + 8 * i, 9); mbar_init(b_cdone + 8 * i, 4); mbar_init(b_sfree + 8 * i, 1); }
        asm volatile("fence.mbarrier_init.release.cluster;" ::: "memory");
    }
    __syncthreads();

    if (warp < 4) {
        asm volatile("setmaxnreg.dec.sync.aligned.u32 40;");
        if (warp == 0 && lane == 0) {
            uint32_t stage = 0, sph = 1, wi = 0, wph = 1;
            bool low_left = true;
            uint32_t lx0 = 0, lx1 = 0, lx2 = 0;
            int lim = 0, issued = 0, nat = 0;
            volatile int* fin_cnt = wslot + 4;
            while (true) {
                Item it; it.type = T_END; it.rb = it.nt = it.ks = 0;
                int tk = 0; (void)tk;
                while (true) {
                    uint4 rd = ld_relaxed_v4(&g_st.ready[0]); const uint4 ex = ld_relaxed_v4(&g_st.exh[0]);
                    const uint32_t dat = nat < 16 ? ld_relaxed(&g_st.d_at[nat * 32]) : 0;
                    if (nat < 16 && dat == e1 * ((wait_r ? 112u : 48u) + (nat == 0 ? 32u : 0u))) { if (!(rd.x >> nat & 1)) publish_group(T_AT, nat, e1); nat++; }
                    { const int na = __popc(rd.x & 0xffffu); if (na > nat) nat = na; }
                    rd.x |= (1u << nat) - 1;
                    lx0 |= ex.x; lx1 |= ex.y; lx2 |= ex.z;
                    uint32_t a0 = rd.x & ~lx0, a1 = rd.y & ~lx1, a2 = rd.z & ~lx2;
                    bool got = false;
                    if ((a0 | a1 | a2) && (rd.x >> (FINE_RB - 1) & 1) && *fin_cnt != issued) {
                        int l2 = 0; while (*fin_cnt != issued && ++l2 < SPIN_LIMIT) { }
                        continue;
                    }
                    while (a0 | a1 | a2) {
                        const int gi = a0 ? __ffs(a0) - 1 : (a1 ? 32 + __ffs(a1) - 1 : 64 + __ffs(a2) - 1);
                        const int ty = T_AT + (gi >> 4), rb = gi & 15, n = group_size(ty, rb);
                        const int i = (int)atomicAdd(&g_st.cnt[gi * 8], 1u);
                        const uint32_t bit = 1u << (gi & 31);
                        if (i >= n - 1) {
                            if (gi < 32) { lx0 |= bit; a0 &= ~bit; } else if (gi < 64) { lx1 |= bit; a1 &= ~bit; } else { lx2 |= bit; a2 &= ~bit; }
                            if (i == n - 1) asm volatile("red.relaxed.gpu.global.or.b32 [%0], %1;" :: "l"(&g_st.exh[gi >> 5]), "r"(bit) : "memory");
                        }
                        if (i < n) {
                            it.type = ty; it.rb = rb; it.nt = i;
                            if (ty == T_WO || ty == T_F2) { const int nn = n_nt(rb); it.ks = i / nn; it.nt = i - it.ks * nn; }
                            asm volatile("fence.acq_rel.gpu;" ::: "memory");
                            got = true; break;
                        }
                    }
                    if (got) {
                        break;
                    }
                    if (low_left && (int)rd.w < I_W + 96 + (nat + LOW_LEAD) * 48) {
                        const int lt = (int)atomicAdd(&g_st.lq_claim, 1u);
                        if (lt < N_LOW) {
                            it = decode_low(lt);
                            if (it.type == T_L1) wait_ge(&g_st.c_mod_a, e1 * 20);
                            else if (it.type != T_MOD) wait_ge(&g_st.f_h[it.rb * 32], e1 * 16);
                            break;
                        }
                        low_left = false;
                    }
                    if ((lx0 & lx1 & lx2) == 0xffffffffu) break;
                    if (!low_left && nat >= PRECLAIM_RB && (blockIdx.x % PRECLAIM_MOD) != 0) {
                        const uint32_t rdw[3] = {rd.x, rd.y, rd.z}, lxw[3] = {lx0, lx1, lx2};
                        int gsel = -1;
#pragma unroll
                        for (int rb = 15; rb >= PRECLAIM_RB; rb--) {
#pragma unroll
                            for (int k = 5; k >= 0; k--) {
                                const int gi = k * 16 + rb;
                                const bool rdy = rdw[gi >> 5] >> (gi & 31) & 1, exq = lxw[gi >> 5] >> (gi & 31) & 1;
                                const bool pre = k == 0 ? (nat == rb) : (rdw[(gi - 16) >> 5] >> ((gi - 16) & 31) & 1);
                                if (!rdy && !exq && pre) gsel = gi;
                            }
                        }
                        if (gsel >= 0) {
                            const int gi = gsel, ty = T_AT + (gi >> 4), rb = gi & 15, n = group_size(ty, rb);
                            const int i = (int)atomicAdd(&g_st.cnt[gi * 8], 1u);
                            const uint32_t bit = 1u << (gi & 31);
                            if (i >= n - 1) {
                                if (gi < 32) lx0 |= bit; else if (gi < 64) lx1 |= bit; else lx2 |= bit;
                                if (i == n - 1) asm volatile("red.relaxed.gpu.global.or.b32 [%0], %1;" :: "l"(&g_st.exh[gi >> 5]), "r"(bit) : "memory");
                            }
                            if (i < n) {
                                it.type = ty; it.rb = rb; it.nt = i;
                                if (ty == T_WO || ty == T_F2) { const int nn = n_nt(rb); it.ks = i / nn; it.nt = i - it.ks * nn; }
                                const uint32_t* dp = (ty == T_AT ? g_st.d_at : ty == T_WO ? g_st.c_at : ty == T_L2 ? g_st.c_wo : ty == T_F1 ? g_st.f_h2 : ty == T_F2 ? g_st.c_act : g_st.c_f2) + rb * 32;
                                const uint32_t dt = e1 * (ty == T_AT ? (wait_r ? 112u : 48u) : (uint32_t)group_size(ty - 1, rb));
                                int l3 = 0;
                                while ((int32_t)(ld_acquire(dp) - dt) < 0) { if (++l3 > SPIN_LIMIT) break; }
                                break;
                            }
                            continue;
                        }
                    }
                    __nanosleep(40);
                    if (++lim > SPIN_LIMIT) break;
                }
                issued++;
                if (it.type == T_L2) wait_ge(&g_st.c_mod_all, e1 * 60);
                asm volatile("fence.proxy.async.global;" ::: "memory");
                mbar_wait(b_wempty + 8 * wi, wph);
                wslot[wi] = pack_item(it);
                mbar_arrive(b_wfull + 8 * wi);
                if (++wi == 2) { wi = 0; wph ^= 1; }
                if (it.type == T_END) break;
                int nkb = 0, kb0 = 0;
                const CUtensorMap *mA = nullptr, *mB0 = nullptr, *mB1 = nullptr; int n0 = 0, n1 = 0, nbox = 4;
                switch (it.type) {
                    case T_KV: nkb = 10; mA = &P.tA_h;
                        if (it.ks) { mB0 = mB1 = (it.nt < 32) ? &P.tB_k : &P.tB_v; n0 = (it.nt & 31) * 128; n1 = n0 + 64; nbox = 2; }
                        else { mB0 = mB1 = (it.nt < 16) ? &P.tB_k : &P.tB_v; n0 = (it.nt & 15) * 256; n1 = n0 + 128; }
                        break;
                    case T_Q: nkb = 10; mA = &P.tA_h; mB0 = mB1 = &P.tB_q; n0 = it.nt * 256; n1 = n0 + 128; break;
                    case T_F1: nkb = 10; mA = &P.tA_h2; mB0 = &P.tB_g; mB1 = &P.tB_u; if (fine(it.rb)) { n0 = n1 = it.nt * 64; nbox = 2; } else n0 = n1 = it.nt * 128; break;
                    case T_WO: nkb = 64 / wo_split(it.rb); kb0 = it.ks * nkb; mA = &P.tA_o; mB0 = mB1 = &P.tB_o; n0 = red_col(it); if (is_wide(it)) n1 = n0 + 128; else { n1 = n0 + 64; nbox = 2; } break;
                    case T_F2: nkb = 27 / f2_split(it.rb); kb0 = it.ks * nkb; mA = &P.tA_act; mB0 = mB1 = &P.tB_d; n0 = red_col(it); if (is_wide(it)) n1 = n0 + 128; else { n1 = n0 + 64; nbox = 2; } break;
                    default: break;
                }
                if (it.type == T_AT) {
#pragma unroll 1
                    for (int i = 0; i < 3; i++) {
                        mbar_wait(b_empty + 8 * stage, sph);
                        const uint32_t st = sb + stage * STAGE_BYTES, bar = b_full + 8 * stage;
                        mbar_expect_tx(bar, i ? 40960 : 32768);
                        const CUtensorMap* m = i == 0 ? &P.tL_q : (i == 1 ? &P.tL_k : &P.tL_v);
                        tma_load_2d(st + 16384, m, it.nt * 128, it.rb * 128, bar);
                        tma_load_2d(st + 32768, m, it.nt * 128 + 64, it.rb * 128, bar);
                        if (i) {
                            const CUtensorMap* mm = i == 1 ? &P.tL_km : &P.tL_vm;
                            tma_load_2d(st, mm, it.nt * 128, it.rb * 32, bar);
                            tma_load_2d(st + 4096, mm, it.nt * 128 + 64, it.rb * 32, bar);
                        }
                        if (++stage == STAGES) { stage = 0; sph ^= 1; }
                    }
                } else if (it.type == T_L1 || it.type == T_L2 || it.type == T_FIN) {
                    const int mode = it.type == T_L1 ? 0 : (it.type == T_L2 ? 1 : 2);
                    const uint32_t pbytes = mode == 0 ? 5120 : (mode == 1 ? 7680 : 2560);
                    const float* psrc = g_mod + (mode == 0 ? 0 : (mode == 1 ? 2 * 640 : 5 * 640));
                    {
                        mbar_wait(b_empty + 8 * stage, sph);
                        const uint32_t st = sb + stage * STAGE_BYTES, bar = b_full + 8 * stage;
                        const size_t ro = ((size_t)it.rb * 128 + it.nt * 8) * 640;
                        mbar_expect_tx(bar, 10240 + (mode ? 20480 : 0) + pbytes);
                        bulk_load(st, (mode == 2 ? g_x1 : x) + ro, 10240, bar);
                        if (mode) bulk_load(st + 10240, g_slab + ro, 20480, bar);
                        bulk_load(st + 30720, psrc, pbytes, bar);
                        if (++stage == STAGES) { stage = 0; sph ^= 1; }
                    }
                }
                for (int kb = 0; kb < nkb; kb++) {
                    mbar_wait(b_empty + 8 * stage, sph);
                    const uint32_t st = sb + stage * STAGE_BYTES, bar = b_full + 8 * stage;
                    mbar_expect_tx(bar, 16384 + nbox * 8192);
                    const int k = (kb0 + kb) * 64;
                    tma_load_2d(st, mA, k, it.rb * 128, bar);
                    tma_load_2d(st + 16384, mB0, n0, k, bar);
                    if (nbox == 4) {
                        tma_load_2d(st + 16384 + 8192, mB0, n0 + 64, k, bar);
                        tma_load_2d(st + 16384 + 16384, mB1, n1, k, bar);
                        tma_load_2d(st + 16384 + 24576, mB1, n1 + 64, k, bar);
                    } else {
                        tma_load_2d(st + 16384 + 8192, mB1, n1, k, bar);
                    }
                    if (++stage == STAGES) { stage = 0; sph ^= 1; }
                }
            }
        } else if (warp == 1 && lane == 0) {
            uint32_t wi = 0, wph = 0, cph = 0;
            while (true) {
                mbar_wait(b_wfull + 8 * wi, wph);
                const Item it = unpack_item(wslot[wi]);
                mbar_arrive(b_wempty + 8 * wi);
                if (++wi == 2) { wi = 0; wph ^= 1; }
                if (it.type == T_END) break;
                const bool red = it.type == T_WO || it.type == T_F2;
                const bool tma = it.type == T_KV || it.type == T_Q || it.type == T_F1 || it.type == T_AT || red;
                const bool narrow = it.type == T_F1 && fine(it.rb);
                const bool kvn = it.type == T_KV && it.ks;
                const int rounds = red ? (is_wide(it) ? 4 : 2) : (((it.type == T_KV || it.type == T_Q) && !kvn) ? 2 : 1);
                const CUtensorMap* mS = it.type == T_F1 ? &P.tS_act : (it.type == T_AT ? &P.tS_o : (it.type == T_Q ? &P.tS_q : (it.nt < (kvn ? 32 : 16) ? &P.tS_k : &P.tS_v)));
                const int gcol = red ? red_col(it) : (narrow ? it.nt * 64 : (rounds == 1 ? (it.nt & 31) * 128 : (it.nt & 15) * 256));
                for (int rnd = 0; rnd < rounds; rnd++) {
                    for (int wg = 0; wg < 2; wg++) {
                        mbar_wait(b_cdone + 8 * wg, cph);
                        const uint32_t stg = sb + OFF_SCR + wg * 16384;
                        const int grow = it.rb * 128 + wg * 64;
                        if (red) {
                            tma_reduce_2d(&P.tR_acc, stg, gcol + rnd * 64, grow);
                            tma_reduce_2d(&P.tR_acc, stg + 8192, gcol + rnd * 64 + 32, grow);
                        } else if (tma) {
                            tma_store_2d(mS, stg, gcol + rnd * 128, grow);
                            if (!narrow) tma_store_2d(mS, stg + 8192, gcol + rnd * 128 + 64, grow);
                        }
                        if (tma) asm volatile("cp.async.bulk.commit_group;" ::: "memory");
                    }
                    cph ^= 1;
                    if (tma) asm volatile("cp.async.bulk.wait_group.read 0;" ::: "memory");
                    mbar_arrive(b_sfree); mbar_arrive(b_sfree + 8);
                }
                if (tma) { asm volatile("cp.async.bulk.wait_group 0;" ::: "memory"); asm volatile("fence.proxy.async.global;" ::: "memory"); }
                if (it.type <= T_KV) asm volatile("fence.acq_rel.gpu;" ::: "memory");
                uint32_t* cnt = nullptr; uint32_t tgt = 0; int nxt = -1;
                switch (it.type) {
                    case T_KV: if (kvn) st_relaxed_u32(&g_kvflag[it.nt], e1);
                        else { st_relaxed_u32(&g_kvflag[it.rb * 64 + it.nt * 2], e1); st_relaxed_u32(&g_kvflag[it.rb * 64 + it.nt * 2 + 1], e1); }
                    case T_Q: red_release_inc(&g_st.d_at[it.rb * 32]); break;
                    case T_MOD: if (it.nt < 20) red_add_relaxed(&g_st.c_mod_a, 1); red_add_relaxed(&g_st.c_mod_all, 1); break;
                    case T_L1: red_add_relaxed(&g_st.f_h[it.rb * 32], 1); break;
                    case T_AT: cnt = &g_st.c_at[it.rb * 32]; tgt = 32; nxt = T_WO; break;
                    case T_WO: cnt = &g_st.c_wo[it.rb * 32]; tgt = group_size(T_WO, it.rb); nxt = T_L2; break;
                    case T_L2: cnt = &g_st.f_h2[it.rb * 32]; tgt = 16; nxt = T_F1; break;
                    case T_F1: cnt = &g_st.c_act[it.rb * 32]; tgt = group_size(T_F1, it.rb); nxt = T_F2; break;
                    case T_F2: cnt = &g_st.c_f2[it.rb * 32]; tgt = group_size(T_F2, it.rb); nxt = T_FIN; break;
                    default: break;
                }
                if (cnt) { if (atom_add_acqrel(cnt, 1) + 1 == e1 * tgt) publish_group(nxt, it.rb, e1); }
            }
            uint32_t old = atom_add_acqrel(&g_st.done, 1);
            if (old + 1 == e1 * (uint32_t)nctas) {
                for (int i = 0; i < 96; i++) g_st.cnt[i * 8] = 0;
                for (int i = 0; i < 3; i++) { g_st.ready[i] = 0; g_st.exh[i] = 0; }
                g_st.lq_claim = 0;
                st_release(&g_epoch, e1);
            }
        }
    } else {
        asm volatile("setmaxnreg.inc.sync.aligned.u32 232;");
        const int ct = tid - 128, cw = warp - 4, wg = cw >> 2;
        const int g = lane >> 2, t = lane & 3;
        uint32_t stage = 0, sph = 0, wi = 0, wph = 0, fph = 1; int ndone = 0;
        while (true) {
            if (ct == 0) wslot[4] = ndone;
            ndone++;
            mbar_wait(b_wfull + 8 * wi, wph);
            const Item it = unpack_item(wslot[wi]);
            __syncwarp();
            if (lane == 0) mbar_arrive(b_wempty + 8 * wi);
            if (++wi == 2) { wi = 0; wph ^= 1; }
            if (it.type == T_END) break;
            const bool narrow = (it.type == T_F1 && fine(it.rb)) || (it.type == T_KV && it.ks);
            if (is_wide(it)) {
                const bool red = it.type == T_WO || it.type == T_F2;
                const int nkb = it.type == T_WO ? 64 / wo_split(it.rb) : (it.type == T_F2 ? 27 / f2_split(it.rb) : 10);
                float d[128];
#pragma unroll
                for (int i = 0; i < 128; i++) d[i] = 0.f;
                for (int kb = 0; kb < nkb; kb++) {
                    mbar_wait(b_full + 8 * stage, sph);
                    const uint32_t st = sb + stage * STAGE_BYTES;
                    const uint64_t da = make_desc(st + wg * 8192, 16, 1024), db = make_desc(st + 16384, 8192, 1024);
                    wgmma_fence();
#pragma unroll
                    for (int k = 0; k < 4; k++) wgmma_n256(d, da + k * 2, db + k * 128, 1);
                    wgmma_commit();
                    wgmma_wait<1>();
                    if (kb > 0 && lane == 0) mbar_arrive(b_empty + 8 * ((stage + STAGES - 1) % STAGES));
                    if (++stage == STAGES) { stage = 0; sph ^= 1; }
                }
                wgmma_wait<0>();
                fence_acc<128>(d);
                if (lane == 0) mbar_arrive(b_empty + 8 * ((stage + STAGES - 1) % STAGES));
                if (red) {
                    const uint32_t sbase = sb + OFF_SCR + wg * 16384 + ((cw & 3) * 16 + g) * 128 + (t & 1) * 8;
#pragma unroll
                    for (int rnd = 0; rnd < 4; rnd++) {
                        mbar_wait(b_sfree + 8 * wg, fph); fph ^= 1;
#pragma unroll
                        for (int i = 0; i < 8; i++) {
                            const float* dd = d + rnd * 32 + i * 4;
                            const uint32_t a = sbase + (i >> 2) * 8192 + ((((2 * i + (t >> 1)) & 7) ^ (g & 7)) << 4);
                            sts64(a, __float_as_uint(dd[0]), __float_as_uint(dd[1]));
                            sts64(a + 1024, __float_as_uint(dd[2]), __float_as_uint(dd[3]));
                        }
                        asm volatile("fence.proxy.async.shared::cta;" ::: "memory");
                        __syncwarp();
                        if (lane == 0) mbar_arrive(b_cdone + 8 * wg);
                    }
                    continue;
                }
                const uint32_t sbase = sb + OFF_SCR + wg * 16384 + ((cw & 3) * 16 + ((lane >> 3) & 1) * 8 + (lane & 7)) * 128;
                const int sx = lane & 7, hi = lane >> 4;
                if (it.type == T_F1) {
#pragma unroll
                    for (int i = 0; i < 64; i++) d[i] = bf16r(gelu_tanh(bf16r(d[i]))) * bf16r(d[64 + i]);
                }
#pragma unroll
                for (int rnd = 0; rnd < 2; rnd++) {
                    if (rnd == 1 && it.type == T_F1) break;
                    mbar_wait(b_sfree + 8 * wg, fph); fph ^= 1;
#pragma unroll
                    for (int i = 0; i < 8; i++) {
                        const float* dd = d + rnd * 64 + i * 8;
                        const int chunk = (2 * i + hi) & 7;
                        stsm_x4(sbase + (i >> 2) * 8192 + ((chunk ^ sx) << 4), pack_bf16(dd[0], dd[1]), pack_bf16(dd[2], dd[3]), pack_bf16(dd[4], dd[5]), pack_bf16(dd[6], dd[7]));
                    }
                    asm volatile("fence.proxy.async.shared::cta;" ::: "memory");
                    __syncwarp();
                    if (lane == 0) mbar_arrive(b_cdone + 8 * wg);
                }
                continue;
            } else if (narrow) {
                float d[64];
#pragma unroll
                for (int i = 0; i < 64; i++) d[i] = 0.f;
                const int nkb = 10;
                for (int kb = 0; kb < nkb; kb++) {
                    mbar_wait(b_full + 8 * stage, sph);
                    const uint32_t st = sb + stage * STAGE_BYTES;
                    const uint64_t da = make_desc(st + wg * 8192, 16, 1024), db = make_desc(st + 16384, 8192, 1024);
                    wgmma_fence();
#pragma unroll
                    for (int k = 0; k < 4; k++) wgmma_n128(d, da + k * 2, db + k * 128, 1);
                    wgmma_commit();
                    wgmma_wait<1>();
                    if (kb > 0 && lane == 0) mbar_arrive(b_empty + 8 * ((stage + STAGES - 1) % STAGES));
                    if (++stage == STAGES) { stage = 0; sph ^= 1; }
                }
                wgmma_wait<0>();
                fence_acc<64>(d);
                if (lane == 0) mbar_arrive(b_empty + 8 * ((stage + STAGES - 1) % STAGES));
                {
                    const uint32_t sbase = sb + OFF_SCR + wg * 16384 + ((cw & 3) * 16 + ((lane >> 3) & 1) * 8 + (lane & 7)) * 128;
                    const bool f1 = it.type == T_F1;
                    if (f1) {
#pragma unroll
                        for (int i = 0; i < 32; i++) d[i] = bf16r(gelu_tanh(bf16r(d[i]))) * bf16r(d[32 + i]);
                    }
                    mbar_wait(b_sfree + 8 * wg, fph); fph ^= 1;
#pragma unroll
                    for (int i = 0; i < 8; i++) {
                        if (i >= 4 && f1) break;
                        const float* dd = d + i * 8;
                        const int chunk = (2 * i + (lane >> 4)) & 7;
                        stsm_x4(sbase + (i >> 2) * 8192 + ((chunk ^ (lane & 7)) << 4), pack_bf16(dd[0], dd[1]), pack_bf16(dd[2], dd[3]), pack_bf16(dd[4], dd[5]), pack_bf16(dd[6], dd[7]));
                    }
                    asm volatile("fence.proxy.async.shared::cta;" ::: "memory");
                }
            } else if (it.type == T_WO || it.type == T_F2) {
                float d[64];
#pragma unroll
                for (int i = 0; i < 64; i++) d[i] = 0.f;
                const int nkb = it.type == T_WO ? 64 / wo_split(it.rb) : 27 / f2_split(it.rb);
                for (int kb = 0; kb < nkb; kb++) {
                    mbar_wait(b_full + 8 * stage, sph);
                    const uint32_t st = sb + stage * STAGE_BYTES;
                    const uint64_t da = make_desc(st + wg * 8192, 16, 1024), db = make_desc(st + 16384, 8192, 1024);
                    wgmma_fence();
#pragma unroll
                    for (int k = 0; k < 4; k++) wgmma_n128(d, da + k * 2, db + k * 128, 1);
                    wgmma_commit();
                    wgmma_wait<1>();
                    if (kb > 0 && lane == 0) mbar_arrive(b_empty + 8 * ((stage + STAGES - 1) % STAGES));
                    if (++stage == STAGES) { stage = 0; sph ^= 1; }
                }
                wgmma_wait<0>();
                fence_acc<64>(d);
                if (lane == 0) mbar_arrive(b_empty + 8 * ((stage + STAGES - 1) % STAGES));
                {
                    const int r0 = (cw & 3) * 16 + g;
                    const uint32_t sbase = sb + OFF_SCR + wg * 16384 + r0 * 128 + (t & 1) * 8;
#pragma unroll
                    for (int rnd = 0; rnd < 2; rnd++) {
                        mbar_wait(b_sfree + 8 * wg, fph); fph ^= 1;
#pragma unroll
                        for (int i = 0; i < 8; i++) {
                            const float* dd = d + rnd * 32 + i * 4;
                            const uint32_t a = sbase + (i >> 2) * 8192 + ((((2 * i + (t >> 1)) & 7) ^ (g & 7)) << 4);
                            sts64(a, __float_as_uint(dd[0]), __float_as_uint(dd[1]));
                            sts64(a + 1024, __float_as_uint(dd[2]), __float_as_uint(dd[3]));
                        }
                        asm volatile("fence.proxy.async.shared::cta;" ::: "memory");
                        if (rnd == 0) { __syncwarp(); if (lane == 0) mbar_arrive(b_cdone + 8 * wg); }
                    }
                }
            } else if (it.type == T_AT) {
                uint32_t p[6][2];
                float d[64];
                const uint32_t s0 = stage, s1 = (stage + 1) % STAGES, s2 = (stage + 2) % STAGES;
                mbar_wait(b_full + 8 * s0, sph);
                mbar_wait(b_full + 8 * s1, s1 < s0 ? sph ^ 1 : sph);
                attn_scores(sb + s0 * STAGE_BYTES + 16384, sb + s1 * STAGE_BYTES + 16384, sb + s1 * STAGE_BYTES, cw >> 1, cw & 1, lane, p);
                __syncwarp();
                if (lane == 0) { mbar_arrive(b_empty + 8 * s0); mbar_arrive(b_empty + 8 * s1); }
                mbar_wait(b_full + 8 * s2, s2 < s0 ? sph ^ 1 : sph);
                attn_pv(sb + s2 * STAGE_BYTES + 16384, sb + s2 * STAGE_BYTES, cw >> 1, lane, p, d);
                __syncwarp();
                if (lane == 0) mbar_arrive(b_empty + 8 * s2);
                stage += 3; if (stage >= STAGES) { stage -= STAGES; sph ^= 1; }
                const uint32_t sbase = sb + OFF_SCR + wg * 16384 + ((cw & 3) * 16 + ((lane >> 3) & 1) * 8 + (lane & 7)) * 128;
                mbar_wait(b_sfree + 8 * wg, fph); fph ^= 1;
#pragma unroll
                for (int i = 0; i < 8; i++) {
                    const float* dd = d + i * 8;
                    const int chunk = (2 * i + (lane >> 4)) & 7;
                    stsm_x4(sbase + (i >> 2) * 8192 + ((chunk ^ (lane & 7)) << 4), pack_bf16(dd[0], dd[1]), pack_bf16(dd[2], dd[3]), pack_bf16(dd[4], dd[5]), pack_bf16(dd[6], dd[7]));
                }
                asm volatile("fence.proxy.async.shared::cta;" ::: "memory");
            } else if (it.type == T_L1 || it.type == T_L2 || it.type == T_FIN) {
                const int mode = it.type == T_L1 ? 0 : (it.type == T_L2 ? 1 : 2);
                {
                    const size_t ro = ((size_t)it.rb * 128 + it.nt * 8 + cw) * 640;
                    const uint32_t st = sb + stage * STAGE_BYTES;
                    mbar_wait(b_full + 8 * stage, sph);
                    row_item(mode, st + cw * 1280, st + 10240 + cw * 2560, st + 30720, b_empty + 8 * stage, g_slab + ro, (mode == 2 ? out : g_x1) + ro, (mode ? g_h2 : g_h) + ro, lane);
                    if (++stage == STAGES) { stage = 0; sph ^= 1; }
                }
            } else if (it.type == T_MOD) {
                const int kg = ct >> 3, c8 = ct & 7;
                float acc[8] = {0, 0, 0, 0, 0, 0, 0, 0};
                const bf16* wp = w_mod + (size_t)kg * 20 * 3840 + it.nt * 64 + c8 * 8;
                {
                    uint4 w[20]; float sl[20];
#pragma unroll
                    for (int i = 0; i < 20; i++) { w[i] = __ldg((const uint4*)(wp + (size_t)i * 3840)); sl[i] = __bfloat162float(cvec[kg * 20 + i]); }
#pragma unroll
                    for (int i = 0; i < 20; i++) {
                        const float s = bf16r(__fdividef(sl[i], 1.0f + __expf(-sl[i])));
                        acc[0] += s * __uint_as_float(w[i].x << 16); acc[1] += s * __uint_as_float(w[i].x & 0xffff0000u);
                        acc[2] += s * __uint_as_float(w[i].y << 16); acc[3] += s * __uint_as_float(w[i].y & 0xffff0000u);
                        acc[4] += s * __uint_as_float(w[i].z << 16); acc[5] += s * __uint_as_float(w[i].z & 0xffff0000u);
                        acc[6] += s * __uint_as_float(w[i].w << 16); acc[7] += s * __uint_as_float(w[i].w & 0xffff0000u);
                    }
                }
#pragma unroll
                for (int i = 0; i < 8; i++) { acc[i] += __shfl_xor_sync(0xffffffff, acc[i], 8); acc[i] += __shfl_xor_sync(0xffffffff, acc[i], 16); }
                float* scr = (float*)(smem + OFF_BAR + 256);
                bar_sync(3, 256);
                if (lane < 8) {
#pragma unroll
                    for (int i = 0; i < 8; i++) scr[cw * 64 + lane * 8 + i] = acc[i];
                }
                bar_sync(3, 256);
                if (ct < 64) {
                    float sum = 0;
#pragma unroll
                    for (int i = 0; i < 8; i++) sum += scr[i * 64 + ct];
                    g_mod[it.nt * 64 + ct] = bf16r(sum);
                }
            }
            if (it.type == T_MOD || it.type == T_L1 || it.type == T_L2 || it.type == T_FIN) { mbar_wait(b_sfree + 8 * wg, fph); fph ^= 1; }
            __syncwarp();
            if (lane == 0) mbar_arrive(b_cdone + 8 * wg);
        }
    }
}

typedef CUresult (*PFN_encodeTiled)(CUtensorMap*, CUtensorMapDataType, cuuint32_t, void*, const cuuint64_t*, const cuuint64_t*, const cuuint32_t*, const cuuint32_t*, CUtensorMapInterleave, CUtensorMapSwizzle, CUtensorMapL2promotion, CUtensorMapFloatOOBfill);

static void make_map(PFN_encodeTiled fn, CUtensorMap* m, const void* ptr, uint64_t inner, uint64_t outer, uint32_t box_inner, uint32_t box_outer, bool f32 = false) {
    cuuint64_t dims[2] = {inner, outer};
    cuuint64_t strides[1] = {inner * (f32 ? 4 : 2)};
    cuuint32_t box[2] = {box_inner, box_outer};
    cuuint32_t es[2] = {1, 1};
    fn(m, f32 ? CU_TENSOR_MAP_DATA_TYPE_FLOAT32 : CU_TENSOR_MAP_DATA_TYPE_BFLOAT16, 2, (void*)ptr, dims, strides, box, es, CU_TENSOR_MAP_INTERLEAVE_NONE, CU_TENSOR_MAP_SWIZZLE_128B, CU_TENSOR_MAP_L2_PROMOTION_L2_256B, CU_TENSOR_MAP_FLOAT_OOB_FILL_NONE);
}

#define G_LESS 0
static int g_dbg_mode = 0;

extern "C" void kernel_launch(void* const* d_in, const int* in_sizes, int n_in, void* d_out, int out_size) {
    const bf16* x = (const bf16*)d_in[0];
    const bf16* mem0 = (const bf16*)d_in[1];
    const bf16* Wq = (const bf16*)d_in[2];
    const bf16* Wk = (const bf16*)d_in[3];
    const bf16* Wv = (const bf16*)d_in[4];
    const bf16* Wo = (const bf16*)d_in[5];
    const bf16* Wg = (const bf16*)d_in[8];
    const bf16* Wu = (const bf16*)d_in[9];
    const bf16* Wd = (const bf16*)d_in[10];
    const bf16* cvec = (const bf16*)d_in[11];
    const bf16* wmod = (const bf16*)d_in[12];
    static PFN_encodeTiled fn = nullptr;
    static int nsm = 0;
    if (!fn) {
        cudaDriverEntryPointQueryResult qr;
        cudaGetDriverEntryPoint("cuTensorMapEncodeTiled", (void**)&fn, cudaEnableDefault, &qr);
        cudaFuncSetAttribute(r_kernel, cudaFuncAttributeMaxDynamicSharedMemorySize, rk::SMEM_BYTES);
        cudaFuncSetAttribute(r_kernel, cudaFuncAttributeNonPortableClusterSizeAllowed, 1);
        cudaFuncSetAttribute(g_kernel, cudaFuncAttributeMaxDynamicSharedMemorySize, gk::SMEM_BYTES);
        cudaDeviceGetAttribute(&nsm, cudaDevAttrMultiProcessorCount, 0);
    }
    void *ph, *po, *ph2, *pact, *pq, *pk, *pv;
    cudaGetSymbolAddress(&pq, g_q); cudaGetSymbolAddress(&pk, g_k); cudaGetSymbolAddress(&pv, g_v);
    cudaGetSymbolAddress(&ph, g_h); cudaGetSymbolAddress(&po, g_o); cudaGetSymbolAddress(&ph2, g_h2); cudaGetSymbolAddress(&pact, g_act);
    GParams P;
    make_map(fn, &P.tA_h, ph, 640, 2048, 64, 128);
    make_map(fn, &P.tA_o, po, 4096, 2048, 64, 128);
    make_map(fn, &P.tA_h2, ph2, 640, 2048, 64, 128);
    make_map(fn, &P.tA_act, pact, 1728, 2048, 64, 128);
    make_map(fn, &P.tB_q, Wq, 4096, 640, 64, 64);
    make_map(fn, &P.tB_k, Wk, 4096, 640, 64, 64);
    make_map(fn, &P.tB_v, Wv, 4096, 640, 64, 64);
    make_map(fn, &P.tB_o, Wo, 640, 4096, 64, 64);
    make_map(fn, &P.tB_g, Wg, 1728, 640, 64, 64);
    make_map(fn, &P.tB_u, Wu, 1728, 640, 64, 64);
    make_map(fn, &P.tB_d, Wd, 640, 1728, 64, 64);
    make_map(fn, &P.tS_q, pq, 4096, 2048, 64, 64);
    make_map(fn, &P.tS_k, pk, 4096, 2048, 64, 64);
    make_map(fn, &P.tS_v, pv, 4096, 2048, 64, 64);
    make_map(fn, &P.tS_act, pact, 1728, 2048, 64, 64);
    void *pkm, *pvm; cudaGetSymbolAddress(&pkm, g_km); cudaGetSymbolAddress(&pvm, g_vm);
    make_map(fn, &P.tS_o, po, 4096, 2048, 64, 64);
    make_map(fn, &P.tL_q, pq, 4096, 2048, 64, 128);
    make_map(fn, &P.tL_k, pk, 4096, 2048, 64, 128);
    make_map(fn, &P.tL_v, pv, 4096, 2048, 64, 128);
    make_map(fn, &P.tL_km, pkm, 4096, 512, 64, 32);
    make_map(fn, &P.tL_vm, pvm, 4096, 512, 64, 32);
    void* pacc; cudaGetSymbolAddress(&pacc, g_slab);
    make_map(fn, &P.tR_acc, pacc, 640, 2048, 32, 64, true);
    cudaStream_t st = cudaStreamPerThread;
    if (g_dbg_mode != 1) {
        cudaLaunchConfig_t cfg = {};
        cfg.gridDim = dim3(64); cfg.blockDim = dim3(256); cfg.dynamicSmemBytes = rk::SMEM_BYTES; cfg.stream = st;
        cudaLaunchAttribute at[1]; at[0].id = cudaLaunchAttributeClusterDimension; at[0].val.clusterDim.x = 16; at[0].val.clusterDim.y = 1; at[0].val.clusterDim.z = 1;
        cfg.attrs = at; cfg.numAttrs = 1;
        CUtensorMap tk, tv;
        make_map(fn, &tk, pk, 4096, 2048, 64, 32);
        make_map(fn, &tv, pv, 4096, 2048, 64, 32);
        cudaLaunchKernelEx(&cfg, r_kernel, tk, tv, mem0, Wq, Wk, Wv, Wo, 1);
    }
    {
        cudaLaunchConfig_t cfg = {};
        const int ng = g_dbg_mode == 1 ? nsm : nsm - G_LESS;
        cfg.gridDim = dim3(ng); cfg.blockDim = dim3(384); cfg.dynamicSmemBytes = gk::SMEM_BYTES; cfg.stream = st;
        cudaLaunchAttribute at[1]; at[0].id = cudaLaunchAttributeProgrammaticStreamSerialization; at[0].val.programmaticStreamSerializationAllowed = 1;
        cfg.attrs = at; cfg.numAttrs = g_dbg_mode == 1 ? 0 : 1;
        cudaLaunchKernelEx(&cfg, g_kernel, P, x, cvec, wmod, (bf16*)d_out, ng, g_dbg_mode == 1 ? 0 : 1);
    }
}
```

```cpp
#include <cuda_runtime.h>
#include <cuda_bf16.h>
#include <cuda.h>
#include <stdint.h>

typedef __nv_bfloat16 bf16;

__device__ __forceinline__ uint32_t smem_u32(const void* p) { return (uint32_t)__cvta_generic_to_shared(p); }
__device__ __forceinline__ uint32_t mapa_u32(uint32_t a, uint32_t r) { uint32_t o; asm volatile("mapa.shared::cluster.u32 %0, %1, %2;" : "=r"(o) : "r"(a), "r"(r)); return o; }
__device__ __forceinline__ void mbar_init(uint32_t bar, uint32_t cnt) { asm volatile("mbarrier.init.shared::cta.b64 [%0], %1;" :: "r"(bar), "r"(cnt) : "memory"); }
__device__ __forceinline__ void mbar_expect_tx(uint32_t bar, uint32_t bytes) { asm volatile("mbarrier.arrive.expect_tx.shared::cta.b64 _, [%0], %1;" :: "r"(bar), "r"(bytes) : "memory"); }
__device__ __forceinline__ void mbar_arrive(uint32_t bar) { asm volatile("mbarrier.arrive.shared::cta.b64 _, [%0];" :: "r"(bar) : "memory"); }
#define SPIN_LIMIT 400000
__device__ __forceinline__ bool mbar_try(uint32_t bar, uint32_t ph) {
    uint32_t ok;
    asm volatile("{ .reg .pred p; mbarrier.try_wait.parity.shared::cta.b64 p, [%1], %2; selp.u32 %0, 1, 0, p; }" : "=r"(ok) : "r"(bar), "r"(ph) : "memory");
    return ok;
}
__device__ __forceinline__ void mbar_wait(uint32_t bar, uint32_t ph) {
    if (mbar_try(bar, ph)) return;
#pragma unroll 1
    for (int lim = 0; lim < SPIN_LIMIT; lim++) if (mbar_try(bar, ph)) break;
}
__device__ __forceinline__ void mbar_wait_cluster(uint32_t bar, uint32_t ph) {
    uint32_t ok = 0; int lim = 0;
    while (true) {
        asm volatile("{ .reg .pred p; mbarrier.try_wait.parity.acquire.cluster.shared::cta.b64 p, [%1], %2; selp.u32 %0, 1, 0, p; }" : "=r"(ok) : "r"(bar), "r"(ph) : "memory");
        if (ok) break;
        if (++lim > SPIN_LIMIT) break;
    }
}
__device__ __forceinline__ void st_async_v4(uint32_t addr, uint32_t a, uint32_t b, uint32_t c, uint32_t d, uint32_t bar) {
    asm volatile("st.async.weak.shared::cluster.mbarrier::complete_tx::bytes.v4.b32 [%0], {%1,%2,%3,%4}, [%5];" :: "r"(addr), "r"(a), "r"(b), "r"(c), "r"(d), "r"(bar) : "memory");
}
__device__ __forceinline__ void ldsm_x4(uint32_t* r, uint32_t addr) {
    asm volatile("ldmatrix.sync.aligned.m8n8.x4.shared.b16 {%0,%1,%2,%3}, [%4];" : "=r"(r[0]), "=r"(r[1]), "=r"(r[2]), "=r"(r[3]) : "r"(addr) : "memory");
}
__device__ __forceinline__ void ldsm_x4_t(uint32_t* r, uint32_t addr) {
    asm volatile("ldmatrix.sync.aligned.m8n8.x4.trans.shared.b16 {%0,%1,%2,%3}, [%4];" : "=r"(r[0]), "=r"(r[1]), "=r"(r[2]), "=r"(r[3]) : "r"(addr) : "memory");
}
__device__ __forceinline__ void mma16816(float* d, const uint32_t* a, uint32_t b0, uint32_t b1) {
    asm volatile("mma.sync.aligned.m16n8k16.row.col.f32.bf16.bf16.f32 {%0,%1,%2,%3}, {%4,%5,%6,%7}, {%8,%9}, {%0,%1,%2,%3};"
        : "+f"(d[0]), "+f"(d[1]), "+f"(d[2]), "+f"(d[3]) : "r"(a[0]), "r"(a[1]), "r"(a[2]), "r"(a[3]), "r"(b0), "r"(b1));
}
__device__ __forceinline__ uint32_t pack_bf16(float lo, float hi) {
    uint32_t r; asm("cvt.rn.bf16x2.f32 %0, %1, %2;" : "=r"(r) : "f"(hi), "f"(lo)); return r;
}
__device__ __forceinline__ float bf16r(float x) { return __bfloat162float(__float2bfloat16_rn(x)); }
__device__ __forceinline__ uint4 lds128(uint32_t a) { uint4 v; asm volatile("ld.shared.v4.u32 {%0,%1,%2,%3}, [%4];" : "=r"(v.x), "=r"(v.y), "=r"(v.z), "=r"(v.w) : "r"(a) : "memory"); return v; }
__device__ __forceinline__ void sts128(uint32_t a, uint4 v) { asm volatile("st.shared.v4.u32 [%0], {%1,%2,%3,%4};" :: "r"(a), "r"(v.x), "r"(v.y), "r"(v.z), "r"(v.w) : "memory"); }
__device__ __forceinline__ void sts32(uint32_t a, uint32_t v) { asm volatile("st.shared.u32 [%0], %1;" :: "r"(a), "r"(v) : "memory"); }
__device__ __forceinline__ void sts64(uint32_t a, uint32_t x, uint32_t y) { asm volatile("st.shared.v2.u32 [%0], {%1,%2};" :: "r"(a), "r"(x), "r"(y) : "memory"); }
__device__ __forceinline__ void sts16(uint32_t a, uint16_t v) { asm volatile("st.shared.u16 [%0], %1;" :: "r"(a), "h"(v) : "memory"); }
__device__ __forceinline__ uint2 lds64(uint32_t a) { uint2 v; asm volatile("ld.shared.v2.u32 {%0,%1}, [%2];" : "=r"(v.x), "=r"(v.y) : "r"(a) : "memory"); return v; }
__device__ __forceinline__ void cp_async16(uint32_t dst, const void* src) { asm volatile("cp.async.cg.shared.global [%0], [%1], 16;" :: "r"(dst), "l"(src) : "memory"); }
__device__ __forceinline__ void cp_async_wait_all() { asm volatile("cp.async.wait_all;" ::: "memory"); }
__device__ __forceinline__ void bar_sync(int id, int n) { asm volatile("bar.sync %0, %1;" :: "r"(id), "r"(n) : "memory"); }
__device__ __forceinline__ uint4 ld_relaxed_v4(const void* p) {
    uint4 v; asm volatile("ld.relaxed.gpu.global.v4.u32 {%0,%1,%2,%3}, [%4];" : "=r"(v.x), "=r"(v.y), "=r"(v.z), "=r"(v.w) : "l"(p) : "memory"); return v;
}
__device__ __forceinline__ void st_relaxed_v4(void* p, uint4 v) {
    asm volatile("st.relaxed.gpu.global.v4.u32 [%0], {%1,%2,%3,%4};" :: "l"(p), "r"(v.x), "r"(v.y), "r"(v.z), "r"(v.w) : "memory");
}
__device__ __forceinline__ uint32_t ld_acquire(const uint32_t* p) { uint32_t v; asm volatile("ld.acquire.gpu.global.u32 %0, [%1];" : "=r"(v) : "l"(p) : "memory"); return v; }
__device__ __forceinline__ uint32_t ld_relaxed(const uint32_t* p) { uint32_t v; asm volatile("ld.relaxed.gpu.global.u32 %0, [%1];" : "=r"(v) : "l"(p) : "memory"); return v; }
__device__ __forceinline__ void st_release(uint32_t* p, uint32_t v) { asm volatile("st.release.gpu.global.u32 [%0], %1;" :: "l"(p), "r"(v) : "memory"); }
__device__ __forceinline__ void cluster_sync_all() {
    asm volatile("barrier.cluster.arrive.release.aligned;" ::: "memory");
    asm volatile("barrier.cluster.wait.acquire.aligned;" ::: "memory");
}

__device__ bf16 g_k[2048 * 4096];
__device__ bf16 g_v[2048 * 4096];
__device__ bf16 g_km[64 * 8 * 4096];
__device__ bf16 g_vm[64 * 8 * 4096];
__device__ uint4 g_gx[2][4][16][80];
__device__ uint32_t g_kvflag[16 * 64];
__device__ uint32_t g_epoch;
struct GState {
    uint32_t done, c_mod_a, c_mod_all, unused0;
    uint32_t pad0[28];
    uint32_t ready[3], lq_claim, exh[4];
    uint32_t pad1[24];
    uint32_t cnt[96 * 8];
    uint32_t f_h[16 * 32];
    uint32_t d_at[16 * 32];
    uint32_t c_at[16 * 32];
    uint32_t c_wo[16 * 32];
    uint32_t f_h2[16 * 32];
    uint32_t c_act[16 * 32];
    uint32_t c_f2[16 * 32];
};
__device__ GState g_st;
namespace gk {
enum { T_MOD, T_L1, T_KV, T_Q, T_AT, T_WO, T_L2, T_F1, T_F2, T_FIN, T_SKIP, T_END };
#define FINE_RB 13
__host__ __device__ __forceinline__ bool fine(int rb) { return rb >= FINE_RB; }
#define WO_FINE 16
#define WO_COARSE 8
__host__ __device__ __forceinline__ int wo_split(int rb) { return fine(rb) ? WO_FINE : WO_COARSE; }
__host__ __device__ __forceinline__ int f2_split(int rb) { return fine(rb) ? 9 : 3; }
__host__ __device__ __forceinline__ int n_nt(int rb) { return fine(rb) ? 5 : 3; }
__host__ __device__ __forceinline__ int n_f1(int rb) { return fine(rb) ? 27 : 14; }
__host__ __device__ __forceinline__ int group_size(int ty, int rb) {
    switch (ty) {
        case T_AT: return 32;
        case T_WO: return n_nt(rb) * wo_split(rb);
        case T_F1: return n_f1(rb);
        case T_F2: return n_nt(rb) * f2_split(rb);
        default: return 16;
    }
}
}
__device__ __forceinline__ uint32_t atom_add_acqrel(uint32_t* p, uint32_t v) {
    uint32_t o; asm volatile("atom.acq_rel.gpu.global.add.u32 %0, [%1], %2;" : "=r"(o) : "l"(p), "r"(v) : "memory"); return o;
}
__device__ __forceinline__ void red_release_inc(uint32_t* p) { asm volatile("red.release.gpu.global.add.u32 [%0], 1;" :: "l"(p) : "memory"); }
__device__ __forceinline__ void publish_group(int ty, int rb, uint32_t) {
    const int gi = (ty - gk::T_AT) * 16 + rb;
    asm volatile("red.release.gpu.global.or.b32 [%0], %1;" :: "l"(&g_st.ready[gi >> 5]), "r"(1u << (gi & 31)) : "memory");
}
#define RT(i)

#define POLL_DELAY 300
#define MEMSH 1
namespace rk {
constexpr int MEM_STRIDE = 1296;
constexpr int T_STRIDE = 272;
constexpr int OFF_W = 0;
constexpr int OFF_KX = 163840;
constexpr int OFF_VX = OFF_KX + 8192;
constexpr int OFF_MEM = OFF_VX + 8192;
constexpr int OFF_Q = OFF_MEM + 10240;
constexpr int OFF_KM = OFF_Q + 8 * T_STRIDE;
constexpr int OFF_VM = OFF_KM + 8 * T_STRIDE;
constexpr int OFF_O = OFF_VM + 8 * T_STRIDE;
constexpr int OFF_SC = OFF_O + 8 * T_STRIDE;
constexpr int OFF_RED = OFF_SC + 8 * 56 * 4;
constexpr int OFF_RS = OFF_RED + 6144;
constexpr int OFF_ST = OFF_RS + 8 * 80 * 16;
constexpr int OFF_BAR = OFF_ST + 640;
constexpr int OFF_TL = OFF_BAR + 128;
constexpr int SMEM_BYTES = OFF_TL + 512;

__device__ __forceinline__ uint32_t ldg_nc(const void* p) { uint32_t v; asm volatile("ld.global.nc.u32 %0, [%1];" : "=r"(v) : "l"(p)); return v; }
__device__ __forceinline__ void load_raw(uint32_t* a, const bf16* __restrict__ W, int ld, int ka, int kb, int cb, int g, int t) {
    const bf16* p = W + (uint32_t)((ka + 2 * t) * ld + cb + 2 * g);
    const bf16* q = W + (uint32_t)((kb + 2 * t) * ld + cb + 2 * g);
    a[0] = ldg_nc(p); a[1] = ldg_nc(p + ld); a[2] = ldg_nc(q); a[3] = ldg_nc(q + ld);
}
__device__ __forceinline__ void fix_frag(uint32_t* a) {
    const uint32_t w0 = a[0], w1 = a[1], w2 = a[2], w3 = a[3];
    a[0] = __byte_perm(w0, w1, 0x5410); a[1] = __byte_perm(w0, w1, 0x7632);
    a[2] = __byte_perm(w2, w3, 0x5410); a[3] = __byte_perm(w2, w3, 0x7632);
}
__device__ __forceinline__ int chunk_src(int d, int kh, int n) { return (d - 8 * kh - n / 5) & 15; }
__device__ __forceinline__ int chunk_col(int d, int kh, int n) { const int s = chunk_src(d, kh, n); return 320 * (s & 1) + 40 * (s >> 1) + 8 * (n % 5); }
}

#define RSTEP 20
#define TL(i)
#define TG(i)

__device__ __forceinline__ void tma_load_2d(uint32_t dst, const CUtensorMap* map, int c0, int c1, uint32_t bar) {
    asm volatile("cp.async.bulk.tensor.2d.shared::cluster.global.mbarrier::complete_tx::bytes [%0], [%1, {%3, %4}], [%2];"
        :: "r"(dst), "l"(map), "r"(bar), "r"(c0), "r"(c1) : "memory");
}
__device__ __forceinline__ uint32_t movmatrix_t(uint32_t a) { uint32_t d; asm volatile("movmatrix.sync.aligned.m8n8.trans.b16 %0, %1;" : "=r"(d) : "r"(a)); return d; }
__device__ __forceinline__ void stg128(void* p, uint4 v) { asm volatile("st.global.v4.u32 [%0], {%1,%2,%3,%4};" :: "l"(p), "r"(v.x), "r"(v.y), "r"(v.z), "r"(v.w) : "memory"); }

__global__ void __launch_bounds__(256, 1)
r_kernel(const __grid_constant__ CUtensorMap tmK, const __grid_constant__ CUtensorMap tmV, const bf16* __restrict__ mem0, const bf16* __restrict__ Wq, const bf16* __restrict__ Wk, const bf16* __restrict__ Wv, const bf16* __restrict__ Wo, int wait_kv)
{
    using namespace rk;
    extern __shared__ __align__(1024) uint8_t smem[];
    const uint32_t sb = smem_u32(smem);
    const int tid = threadIdx.x, warp = tid >> 5, lane = tid & 31, g = lane >> 2, t = lane & 3;
    uint32_t rank, cid;
    asm volatile("mov.u32 %0, %%cluster_ctarank;" : "=r"(rank));
    asm volatile("mov.u32 %0, %%clusterid.x;" : "=r"(cid));
    const int hh = rank >> 1, j = rank & 1, h = cid * 8 + hh;
    const int kh = warp & 1, mb = warp >> 1;
    const uint32_t b_mem = sb + OFF_BAR, b_qkv = b_mem + 64, b_rs = b_mem + 72, b_kv = b_mem + 80;

    RT(64);
    asm volatile("griddepcontrol.launch_dependents;");
    const uint32_t epoch = ld_relaxed(&g_epoch);

    if (tid == 0) {
        for (int i = 0; i < 8; i++) mbar_init(b_mem + 8 * i, 1);
        mbar_init(b_qkv, 9); mbar_init(b_rs, 1); mbar_init(b_kv, 1);
        asm volatile("fence.mbarrier_init.release.cluster;" ::: "memory");
    }
    const uint32_t wsm = sb + OFF_W + (warp < 4 ? warp * 22528 : 4 * 22528 + (warp - 4) * 18432) + lane * 16;
    {
        const size_t co = (size_t)h * 128 + 64 * j;
        for (int i = tid; i < 640; i += 256) {
            asm volatile("prefetch.global.L2 [%0];" :: "l"(Wv + (size_t)i * 4096 + co));
            asm volatile("prefetch.global.L2 [%0];" :: "l"(Wo + ((size_t)h * 128 + i / 5) * 640 + 320 * j + (i % 5) * 64));
            asm volatile("prefetch.global.L2 [%0];" :: "l"(Wq + (size_t)i * 4096 + co));
            asm volatile("prefetch.global.L2 [%0];" :: "l"(Wk + (size_t)i * 4096 + co));
        }
    }
    uint32_t wq[20][4], wk[20][4];
    {
        const int cb = h * 128 + 64 * j + 16 * mb;
#pragma unroll
        for (int i = 0; i < 20; i++) load_raw(wq[i], Wv, 4096, chunk_col(rank, kh, 2 * i), chunk_col(rank, kh, 2 * i + 1), cb, g, t);
        const bf16* Woh = Wo + (size_t)h * 128 * 640;
        const int c3 = 320 * j + 16 * warp;
#pragma unroll
        for (int i = 0; i < 16; i++) load_raw(wk[i], Woh, 640, (i & 7) * 16, (i & 7) * 16 + 8, c3 + 128 * (i >> 3), g, t);
#pragma unroll
        for (int i = 0; i < 20; i++) { fix_frag(wq[i]); sts128(wsm + i * 512, make_uint4(wq[i][0], wq[i][1], wq[i][2], wq[i][3])); }
        if (warp < 4) {
#pragma unroll
            for (int i = 0; i < 8; i++) load_raw(wq[i], Woh, 640, i * 16, i * 16 + 8, c3 + 256, g, t);
        }
#pragma unroll
        for (int i = 0; i < 16; i++) { fix_frag(wk[i]); sts128(wsm + (20 + i) * 512, make_uint4(wk[i][0], wk[i][1], wk[i][2], wk[i][3])); }
#pragma unroll
        for (int i = 0; i < 20; i++) load_raw(wk[i], Wk, 4096, chunk_col(rank, kh, 2 * i), chunk_col(rank, kh, 2 * i + 1), cb, g, t);
        if (warp < 4) {
#pragma unroll
            for (int i = 0; i < 8; i++) { fix_frag(wq[i]); sts128(wsm + (36 + i) * 512, make_uint4(wq[i][0], wq[i][1], wq[i][2], wq[i][3])); }
        }
#pragma unroll
        for (int i = 0; i < 20; i++) load_raw(wq[i], Wq, 4096, chunk_col(rank, kh, 2 * i), chunk_col(rank, kh, 2 * i + 1), cb, g, t);
#pragma unroll
        for (int i = 0; i < 20; i++) { fix_frag(wk[i]); fix_frag(wq[i]); }
    }
    for (int i = tid; i < 640; i += 256) {
        int row = i / 80, c = i % 80;
        uint4 v = __ldg((const uint4*)(mem0 + row * 640 + c * 8));
        const int jj = c / 40, h5 = (c % 40) / 5;
        sts128(sb + OFF_MEM + (((int)rank - (2 * h5 + jj)) & 15) * 640 + row * 80 + (c % 5) * 16, v);
    }
    auto prefetch_kv = [&](int s) {
        if ((wait_kv & 1) && (s & 3) == 0) {
            const uint32_t* fk = &g_kvflag[(s >> 2) * 64 + h];
            int lim = 0;
            while (ld_acquire(fk) != epoch + 1) { if (++lim > SPIN_LIMIT) break; }
            while (ld_acquire(fk + 32) != epoch + 1) { if (++lim > SPIN_LIMIT) break; }
            asm volatile("fence.proxy.async.global;" ::: "memory");
        }
        mbar_expect_tx(b_kv, 16384);
        tma_load_2d(sb + OFF_KX, &tmK, h * 128, s * 32, b_kv);
        tma_load_2d(sb + OFF_KX + 4096, &tmK, h * 128 + 64, s * 32, b_kv);
        tma_load_2d(sb + OFF_VX, &tmV, h * 128, s * 32, b_kv);
        tma_load_2d(sb + OFF_VX + 4096, &tmV, h * 128 + 64, s * 32, b_kv);
    };
    __syncthreads();
    RT(65);
    __syncthreads();
    cluster_sync_all();

    const float scale = 0.08838834764831845f;
#define LAUNDER() int tid_ = threadIdx.x; asm volatile("" : "+r"(tid_)); const int warp = tid_ >> 5, lane = tid_ & 31, g = lane >> 2, t = lane & 3; (void)g; (void)t; (void)warp;
#define WSM() (sb + OFF_W + (warp < 4 ? warp * 22528 : 4 * 22528 + (warp - 4) * 18432) + lane * 16)

#pragma unroll 1
    for (int s = 0; s < 64; s++) {
        const uint32_t ph = s & 1;
        RT(s);
        {
            LAUNDER();
            TL(0);
            const int kh = warp & 1, mb = warp >> 1;
            const uint32_t wsm = WSM();
            const uint32_t mb0 = sb + OFF_MEM + kh * 5120 + (lane & 7) * 80 + (lane >> 3) * 16;
            const uint32_t mb1 = mb0 + ((lane >> 3) >= 1 ? 560 : 0), mb2 = mb0 + ((lane >> 3) >= 2 ? 560 : 0), mb3 = mb0 + ((lane >> 3) >= 3 ? 560 : 0);
            auto baddr = [&](int it) {
                const int r5 = (4 * it) % 5, c = ((4 * it) / 5) * 640 + r5 * 16;
                return (r5 <= 1 ? mb0 : (r5 == 4 ? mb1 : (r5 == 3 ? mb2 : mb3))) + c;
            };
            uint4 va[6];
            va[0] = lds128(wsm); va[1] = lds128(wsm + 512); va[2] = lds128(wsm + 1024); va[3] = lds128(wsm + 1536);
            if (s > 0) mbar_wait(b_mem, ph ^ 1);
            TL(1); TG(15);
            float aq0[4] = {0, 0, 0, 0}, aq1[4] = {0, 0, 0, 0}, ak0[4] = {0, 0, 0, 0}, ak1[4] = {0, 0, 0, 0}, av0[4] = {0, 0, 0, 0}, av1[4] = {0, 0, 0, 0};
            uint32_t b[3][4];
            ldsm_x4(b[0], baddr(0)); ldsm_x4(b[1], baddr(1));
            if (tid_ == 0) {
                mbar_expect_tx(b_qkv, 3072);
                if (s < 63) mbar_expect_tx(b_rs, 10240);
            }
#pragma unroll
            for (int i = 0; i < 10; i++) {
                if (i + 2 < 10) {
                    const int it = i + 2, sl = ((4 * it + 3) / 5) >> MEMSH, slp = ((4 * (it - 1) + 3) / 5) >> MEMSH;
                    if (sl != slp && s > 0) mbar_wait(b_mem + 8 * sl, ph ^ 1);
                    ldsm_x4(b[(i + 2) % 3], baddr(i + 2));
                    va[(2 * i + 4) % 6] = lds128(wsm + (2 * i + 4) * 512); va[(2 * i + 5) % 6] = lds128(wsm + (2 * i + 5) * 512);
                }
                const uint32_t* bb = b[i % 3];
                mma16816(aq0, wq[2 * i], bb[0], bb[1]); mma16816(ak0, wk[2 * i], bb[0], bb[1]); mma16816(av0, (uint32_t*)&va[(2 * i) % 6], bb[0], bb[1]);
                mma16816(aq1, wq[2 * i + 1], bb[2], bb[3]); mma16816(ak1, wk[2 * i + 1], bb[2], bb[3]); mma16816(av1, (uint32_t*)&va[(2 * i + 1) % 6], bb[2], bb[3]);
            }
            float snd[4], fin[4];
#pragma unroll
            for (int i = 0; i < 4; i++) { float q = aq0[i] + aq1[i], k = ak0[i] + ak1[i]; snd[i] = kh ? q : k; fin[i] = kh ? k : q; av0[i] += av1[i]; }
            sts128(sb + OFF_RED + tid_ * 16, make_uint4(__float_as_uint(snd[0]), __float_as_uint(snd[1]), __float_as_uint(snd[2]), __float_as_uint(snd[3])));
            sts64(sb + OFF_RED + 4096 + tid_ * 8, __float_as_uint(kh ? av0[0] : av0[1]), __float_as_uint(kh ? av0[2] : av0[3]));
            bar_sync(1 + mb, 64);
            uint4 r = lds128(sb + OFF_RED + (tid_ ^ 32) * 16);
            uint2 r2 = lds64(sb + OFF_RED + 4096 + (tid_ ^ 32) * 8);
            fin[0] += __uint_as_float(r.x); fin[1] += __uint_as_float(r.y); fin[2] += __uint_as_float(r.z); fin[3] += __uint_as_float(r.w);
            float f0 = (kh ? av0[1] : av0[0]) + __uint_as_float(r2.x), f1 = (kh ? av0[3] : av0[2]) + __uint_as_float(r2.y);
            TL(2);
            const uint32_t cofs = (64 * j + 16 * mb) * 2;
            const uint32_t buf = sb + (kh ? OFF_KM : OFF_Q) + cofs;
            sts32(buf + (2 * t) * T_STRIDE + g * 4, pack_bf16(fin[0], fin[2]));
            sts32(buf + (2 * t + 1) * T_STRIDE + g * 4, pack_bf16(fin[1], fin[3]));
            sts32(sb + OFF_VM + cofs + (2 * t + kh) * T_STRIDE + g * 4, pack_bf16(f0, f1));
            __syncwarp();
            if (lane < 24) {
                const uint32_t peer_off = mapa_u32(sb, rank ^ 1) - sb;
                const int row = lane < 16 ? (lane >> 1) : 2 * ((lane - 16) >> 1) + kh;
                const uint32_t a = (lane < 16 ? buf : sb + OFF_VM + cofs) + row * T_STRIDE + (lane & 1) * 16;
                uint4 v = lds128(a);
                st_async_v4(a + peer_off, v.x, v.y, v.z, v.w, b_qkv + peer_off);
                if ((kh || lane >= 16) && !(wait_kv & 8)) {
                    bf16* dst = (lane < 16 ? g_km : g_vm) + ((uint32_t)(s * 8 + row) * 4096u + h * 128 + 64 * j + 16 * mb + (lane & 1) * 8);
                    stg128(dst, v);
                }
            }
            if (lane == 0) mbar_arrive(b_qkv);
            if (s == 0 && tid_ == 224) prefetch_kv(0);
            TL(3);
        }
        if (s == 63) {
            __syncthreads();
            if (threadIdx.x == 0 && (wait_kv & 1)) red_release_inc(&g_st.d_at[15 * 32]);
            break;
        }
        uint4 wa[8];
        {
            LAUNDER();
            const uint32_t wsm = WSM();
            if (!(wait_kv & 2) || s == 0) mbar_wait(b_kv, ph);
            if (warp >= 4 && warp < 7) {
                const int kw = warp - 4;
                uint32_t ka[8][4];
                if (kw < 2) {
                    const uint32_t kaddr = sb + OFF_KX + (16 * kw + (lane & 15)) * 128;
#pragma unroll
                    for (int i = 0; i < 8; i++) ldsm_x4(ka[i], kaddr + (i >> 2) * 4096 + ((((2 * i + (lane >> 4)) & 7) ^ (lane & 7)) << 4));
                    mbar_wait(b_qkv, ph);
                } else {
                    mbar_wait(b_qkv, ph);
                    const uint32_t kaddr = sb + OFF_KM + (lane & 7) * T_STRIDE + (lane >> 4) * 16;
#pragma unroll
                    for (int i = 0; i < 8; i++) ldsm_x4(ka[i], kaddr + i * 32);
                }
                TL(5);
                const uint32_t qa = sb + OFF_Q + (lane & 7) * T_STRIDE + (lane >> 3) * 16;
                uint32_t qb[4][4];
#pragma unroll
                for (int i = 0; i < 4; i++) ldsm_x4(qb[i], qa + i * 64);
                float s0[4] = {0, 0, 0, 0}, s1[4] = {0, 0, 0, 0}, s2[4] = {0, 0, 0, 0}, s3[4] = {0, 0, 0, 0};
                mma16816(s0, ka[0], qb[0][0], qb[0][1]); mma16816(s1, ka[1], qb[0][2], qb[0][3]);
                mma16816(s2, ka[2], qb[1][0], qb[1][1]); mma16816(s3, ka[3], qb[1][2], qb[1][3]);
                mma16816(s0, ka[4], qb[2][0], qb[2][1]); mma16816(s1, ka[5], qb[2][2], qb[2][3]);
                mma16816(s2, ka[6], qb[3][0], qb[3][1]); mma16816(s3, ka[7], qb[3][2], qb[3][3]);
                const uint32_t sc = sb + OFF_SC + (16 * kw + g) * 4 + (2 * t) * 224;
                sts32(sc, __float_as_uint(bf16r(bf16r((s0[0] + s1[0]) + (s2[0] + s3[0])) * scale)));
                sts32(sc + 224, __float_as_uint(bf16r(bf16r((s0[1] + s1[1]) + (s2[1] + s3[1])) * scale)));
                if (kw < 2) {
                    sts32(sc + 32, __float_as_uint(bf16r(bf16r((s0[2] + s1[2]) + (s2[2] + s3[2])) * scale)));
                    sts32(sc + 32 + 224, __float_as_uint(bf16r(bf16r((s0[3] + s1[3]) + (s2[3] + s3[3])) * scale)));
                }
                asm volatile("bar.arrive 6, 224;" ::: "memory");
                TL(4);
#pragma unroll
                for (int i = 0; i < 8; i++) wa[i] = lds128(wsm + (20 + i) * 512);
            } else {
#pragma unroll
                for (int i = 0; i < 8; i++) wa[i] = lds128(wsm + (20 + i) * 512);
                if (warp < 4) {
                    mbar_wait(b_qkv, ph);
                    uint32_t a0[2][4], a1[2][4], a2[2][4];
#pragma unroll
                    for (int u = 0; u < 2; u++) {
                        const int et = warp + 4 * u;
                        const uint32_t vx = sb + OFF_VX + u * 4096 + ((lane >> 4) * 8 + (lane & 7)) * 128 + ((((2 * warp + ((lane >> 3) & 1)) & 7) ^ (lane & 7)) << 4);
                        ldsm_x4_t(a0[u], vx); ldsm_x4_t(a1[u], vx + 16 * 128);
                        ldsm_x4_t(a2[u], sb + OFF_VM + (lane & 7) * T_STRIDE + (16 * et + ((lane >> 3) & 1) * 8) * 2);
                    }
                    bar_sync(6, 224);
                    TL(6);
                    float x[10];
#pragma unroll
                    for (int i = 0; i < 5; i++) { uint2 v = lds64(sb + OFF_SC + g * 224 + (8 * i + 2 * t) * 4); x[2 * i] = __uint_as_float(v.x); x[2 * i + 1] = __uint_as_float(v.y); }
                    float m = fmaxf(fmaxf(fmaxf(x[0], x[1]), fmaxf(x[2], x[3])), fmaxf(fmaxf(x[4], x[5]), fmaxf(x[6], x[7])));
                    m = fmaxf(m, fmaxf(x[8], x[9]));
                    m = fmaxf(m, __shfl_xor_sync(0xffffffff, m, 1)); m = fmaxf(m, __shfl_xor_sync(0xffffffff, m, 2));
                    float sum0 = 0, sum1 = 0;
#pragma unroll
                    for (int i = 0; i < 5; i++) { x[2 * i] = __expf(x[2 * i] - m); sum0 += x[2 * i]; x[2 * i + 1] = __expf(x[2 * i + 1] - m); sum1 += x[2 * i + 1]; }
                    float sum = sum0 + sum1;
                    sum += __shfl_xor_sync(0xffffffff, sum, 1); sum += __shfl_xor_sync(0xffffffff, sum, 2);
                    float inv = __fdividef(1.0f, sum);
                    if (inv == 123.f) TL(14);
                    TL(4);
                    uint32_t pb[5];
#pragma unroll
                    for (int i = 0; i < 5; i++) pb[i] = pack_bf16(x[2 * i] * inv, x[2 * i + 1] * inv);
#pragma unroll
                    for (int u = 0; u < 2; u++) {
                        float o0[4] = {0, 0, 0, 0}, o1[4] = {0, 0, 0, 0}, o2[4] = {0, 0, 0, 0};
                        mma16816(o0, a0[u], pb[0], pb[1]); mma16816(o1, a1[u], pb[2], pb[3]); mma16816(o2, a2[u], pb[4], 0u);
                        const uint32_t lo = movmatrix_t(pack_bf16((o0[0] + o1[0]) + o2[0], (o0[1] + o1[1]) + o2[1]));
                        const uint32_t hi = movmatrix_t(pack_bf16((o0[2] + o1[2]) + o2[2], (o0[3] + o1[3]) + o2[3]));
                        const uint32_t oa = sb + OFF_O + g * T_STRIDE + (16 * (warp + 4 * u) + 2 * t) * 2;
                        sts32(oa, lo); sts32(oa + 16, hi);
                    }
                    TL(5);
                } else {
                    if (lane < (8 >> MEMSH)) mbar_expect_tx(b_mem + 8 * lane, 1280 << MEMSH);
                }
            }
        }
        __syncthreads();
        {
            LAUNDER();
            TL(7);
            const uint32_t wsm = WSM();
            uint32_t ob[16];
            const uint32_t oa = sb + OFF_O + (lane & 7) * T_STRIDE + (lane >> 3) * 16;
#pragma unroll
            for (int i = 0; i < 4; i++) ldsm_x4(ob + 4 * i, oa + i * 64);
            const uint32_t rs_base = OFF_RS + hh * 1280 + t * 16;
            const int ntile = warp < 4 ? 3 : 2;
#pragma unroll 1
            for (int tl = 0; tl < ntile; tl++) {
                float d0[4] = {0, 0, 0, 0}, d1[4] = {0, 0, 0, 0}, d2[4] = {0, 0, 0, 0}, d3[4] = {0, 0, 0, 0};
                const bool more = tl + 1 < ntile;
                const uint32_t nx = wsm + (28 + 8 * tl) * 512;
                mma16816(d0, (uint32_t*)&wa[0], ob[0], ob[1]);   if (more) wa[0] = lds128(nx);
                mma16816(d1, (uint32_t*)&wa[1], ob[2], ob[3]);   if (more) wa[1] = lds128(nx + 512);
                mma16816(d2, (uint32_t*)&wa[2], ob[4], ob[5]);   if (more) wa[2] = lds128(nx + 1024);
                mma16816(d3, (uint32_t*)&wa[3], ob[6], ob[7]);   if (more) wa[3] = lds128(nx + 1536);
                mma16816(d0, (uint32_t*)&wa[4], ob[8], ob[9]);   if (more) wa[4] = lds128(nx + 2048);
                mma16816(d1, (uint32_t*)&wa[5], ob[10], ob[11]); if (more) wa[5] = lds128(nx + 2560);
                mma16816(d2, (uint32_t*)&wa[6], ob[12], ob[13]); if (more) wa[6] = lds128(nx + 3072);
                mma16816(d3, (uint32_t*)&wa[7], ob[14], ob[15]); if (more) wa[7] = lds128(nx + 3584);
                const int col = 16 * (warp + 8 * tl) + 2 * g; const int own = col / 40; const int cp = (col - own * 40) >> 1;
                const uint32_t dbase = mapa_u32(sb, 2 * own + j);
                st_async_v4(dbase + rs_base + cp * 64, __float_as_uint((d0[0] + d1[0]) + (d2[0] + d3[0])), __float_as_uint((d0[1] + d1[1]) + (d2[1] + d3[1])),
                            __float_as_uint((d0[2] + d1[2]) + (d2[2] + d3[2])), __float_as_uint((d0[3] + d1[3]) + (d2[3] + d3[3])), dbase + OFF_BAR + 72);
            }
            TL(8);
        }
        {
            LAUNDER();
            if (warp >= 5) {
                const int x = tid_ - 160;
                const int ot = x < 80 ? x : 79;
                const uint32_t gs = epoch * 64 + s; const uint32_t tag = (gs + 1) & 15u; const int slot = gs & 1;
                uint4* gp = &g_gx[slot][0][rank][ot];
                mbar_wait(b_rs, ph);
                TL(9); TG(12);
                uint4 u[8];
#pragma unroll
                for (int q = 0; q < 8; q++) u[q] = lds128(sb + OFF_RS + q * 1280 + ot * 16);
                float4 a;
                a.x = ((__uint_as_float(u[0].x) + __uint_as_float(u[1].x)) + (__uint_as_float(u[2].x) + __uint_as_float(u[3].x))) + ((__uint_as_float(u[4].x) + __uint_as_float(u[5].x)) + (__uint_as_float(u[6].x) + __uint_as_float(u[7].x)));
                a.y = ((__uint_as_float(u[0].y) + __uint_as_float(u[1].y)) + (__uint_as_float(u[2].y) + __uint_as_float(u[3].y))) + ((__uint_as_float(u[4].y) + __uint_as_float(u[5].y)) + (__uint_as_float(u[6].y) + __uint_as_float(u[7].y)));
                a.z = ((__uint_as_float(u[0].z) + __uint_as_float(u[1].z)) + (__uint_as_float(u[2].z) + __uint_as_float(u[3].z))) + ((__uint_as_float(u[4].z) + __uint_as_float(u[5].z)) + (__uint_as_float(u[6].z) + __uint_as_float(u[7].z)));
                a.w = ((__uint_as_float(u[0].w) + __uint_as_float(u[1].w)) + (__uint_as_float(u[2].w) + __uint_as_float(u[3].w))) + ((__uint_as_float(u[4].w) + __uint_as_float(u[5].w)) + (__uint_as_float(u[6].w) + __uint_as_float(u[7].w)));
                uint4 mine = make_uint4((__float_as_uint(a.x) & ~15u) | tag, (__float_as_uint(a.y) & ~15u) | tag, (__float_as_uint(a.z) & ~15u) | tag, (__float_as_uint(a.w) & ~15u) | tag);
                if (x < 80) st_relaxed_v4(gp + cid * 1280, mine);
                { uint32_t c0, c1; asm volatile("mov.u32 %0, %%clock;" : "=r"(c0) :: "memory"); do { asm volatile("mov.u32 %0, %%clock;" : "=r"(c1) :: "memory"); } while (c1 - c0 < POLL_DELAY); }
                uint4 v[3];
                const uint4* rp0 = gp + (cid ^ 1) * 1280; const uint4* rp1 = gp + (cid ^ 2) * 1280; const uint4* rp2 = gp + (cid ^ 3) * 1280;
                int lim = 0;
                while (true) {
                    v[0] = ld_relaxed_v4(rp0); v[1] = ld_relaxed_v4(rp1); v[2] = ld_relaxed_v4(rp2);
                    uint32_t bad = 0;
#pragma unroll
                    for (int c = 0; c < 3; c++) bad |= (v[c].x ^ tag) | (v[c].y ^ tag) | (v[c].z ^ tag) | (v[c].w ^ tag);
                    if ((bad & 15u) == 0) break;
                    if (++lim > SPIN_LIMIT) break;
                }
                float f0 = (__uint_as_float(mine.x) + __uint_as_float(v[0].x)) + (__uint_as_float(v[1].x) + __uint_as_float(v[2].x));
                float f1 = (__uint_as_float(mine.y) + __uint_as_float(v[0].y)) + (__uint_as_float(v[1].y) + __uint_as_float(v[2].y));
                float f2 = (__uint_as_float(mine.z) + __uint_as_float(v[0].z)) + (__uint_as_float(v[1].z) + __uint_as_float(v[2].z));
                float f3 = (__uint_as_float(mine.w) + __uint_as_float(v[0].w)) + (__uint_as_float(v[1].w) + __uint_as_float(v[2].w));
                const int cp = ot >> 2, tt = ot & 3;
                sts32(sb + OFF_ST + (2 * tt) * 80 + cp * 4, pack_bf16(f0, f2));
                sts32(sb + OFF_ST + (2 * tt + 1) * 80 + cp * 4, pack_bf16(f1, f3));
                TL(10); TG(13);
                bar_sync(5, 128);
                if (x < 80) {
                    const int c = x % 40, d0 = x / 40;
                    uint4 w = lds128(sb + OFF_ST + c * 16);
                    const uint32_t off = OFF_MEM + d0 * 5120 + c * 16;
#pragma unroll
                    for (int i = 0; i < 8; i++) {
                        const uint32_t rb = mapa_u32(sb, (d0 * 8 + i + rank) & 15);
                        st_async_v4(rb + off + i * 640, w.x, w.y, w.z, w.w, rb + OFF_BAR + 8 * (i >> MEMSH));
                    }
                }
            } else if (warp == 4) {
                if (lane == 0 && (s & 3) == 3 && (wait_kv & 1)) red_release_inc(&g_st.d_at[(s >> 2) * 32]);
                __syncwarp();
            } else if (warp == 3) {
                bar_sync(5, 128);
                if (lane == 0 && s < 62 && !(wait_kv & 2)) prefetch_kv(s + 1);
                __syncwarp();
            }
            TL(11);
        }
    }
    cluster_sync_all();
}

__device__ float g_mod[3840];
__device__ bf16 g_h[2048 * 640];
__device__ bf16 g_q[2048 * 4096];
__device__ bf16 g_o[2048 * 4096];
__device__ bf16 g_x1[2048 * 640];
__device__ bf16 g_h2[2048 * 640];
__device__ bf16 g_act[2048 * 1728];
__device__ float g_slab[2048 * 640];

namespace gk {
#define NSTAGES 3
constexpr int STAGES = NSTAGES;
constexpr int STAGE_BYTES = 49152;
constexpr int OFF_SCR = STAGES * STAGE_BYTES;
constexpr int OFF_BAR = OFF_SCR + 32768;
constexpr int SMEM_BYTES = OFF_BAR + 256 + 2048;
#define PRECLAIM_MOD 2
#define PRECLAIM_RB 15
#define URGENT_LEAD 1
#define LOW_LEAD 16
constexpr int N_MOD = 60, N_L1 = 256, N_KV = 32, N_Q = 16;
constexpr int I_L1 = N_MOD, I_W = I_L1 + N_L1;
constexpr int N_LOW = I_W + 16 * (N_KV + N_Q) + 32;
constexpr int NFINE = 16 - FINE_RB;
constexpr int N_HIGH = 16 * (32 + 16 + 16) + (16 - NFINE) * (3 * WO_COARSE + 14 + 9) + NFINE * (5 * WO_FINE + 27 + 45);
struct Item { int type, rb, nt, ks; };
__host__ __device__ inline Item decode_low(int t) {
    Item it; it.rb = 0; it.nt = 0; it.ks = 0;
    if (t < I_L1) { it.type = T_MOD; it.nt = t; return it; }
    if (t < I_L1 + 16) { it.type = T_L1; it.rb = 0; it.nt = t - I_L1; return it; }
    if (t < I_L1 + 80) { it.type = T_KV; it.rb = 0; it.nt = t - I_L1 - 16; it.ks = 1; return it; }
    if (t < I_L1 + 112) { it.type = T_L1; it.rb = (t - I_L1 - 64) >> 4; it.nt = (t - I_L1 - 64) & 15; return it; }
    if (t < I_L1 + 144) { it.type = T_KV; it.rb = 1; it.nt = t - I_L1 - 112; return it; }
    if (t < I_W + 96) { it.type = T_L1; it.rb = (t - I_L1 - 96) >> 4; it.nt = (t - I_L1 - 96) & 15; return it; }
    t -= I_W + 96;
    if (t < 14 * 48) { const int w = t / 48; t -= w * 48; if (t < 16) { it.type = T_Q; it.rb = w; it.nt = t; } else { it.type = T_KV; it.rb = w + 2; it.nt = t - 16; } return it; }
    t -= 14 * 48;
    it.type = T_Q; it.rb = 14 + (t >> 4); it.nt = t & 15; return it;
}
__device__ __forceinline__ bool is_wide(const Item& it) {
    if (it.type == T_KV || it.type == T_Q) return it.ks == 0;
    if (it.type == T_F1) return !fine(it.rb);
    if (it.type == T_WO || it.type == T_F2) return !fine(it.rb) && it.nt < 2;
    return false;
}
__device__ __forceinline__ int red_col(const Item& it) { return fine(it.rb) ? it.nt * 128 : it.nt * 256; }
__device__ __forceinline__ int pack_item(const Item& it) { return it.type | (it.rb << 4) | (it.nt << 8) | (it.ks << 16); }
__device__ __forceinline__ Item unpack_item(int v) { Item it; it.type = v & 15; it.rb = (v >> 4) & 15; it.nt = (v >> 8) & 255; it.ks = (v >> 16) & 255; return it; }
}

struct GParams {
    CUtensorMap tA_h, tA_o, tA_h2, tA_act, tB_q, tB_k, tB_v, tB_o, tB_g, tB_u, tB_d, tS_q, tS_k, tS_v, tS_act, tS_o, tL_q, tL_k, tL_v, tL_km, tL_vm, tR_acc;
};

__device__ __forceinline__ void wait_ge(const uint32_t* p, uint32_t target) {
    int lim = 0;
    while ((int32_t)(ld_acquire(p) - target) < 0) { __nanosleep(64); if (++lim > SPIN_LIMIT) break; }
}
__device__ __forceinline__ void red_add_relaxed(uint32_t* p, uint32_t v) { asm volatile("red.relaxed.gpu.global.add.u32 [%0], %1;" :: "l"(p), "r"(v) : "memory"); }
__device__ __forceinline__ void st_relaxed_u32(uint32_t* p, uint32_t v) { asm volatile("st.relaxed.gpu.global.u32 [%0], %1;" :: "l"(p), "r"(v) : "memory"); }
__device__ __forceinline__ void red_add_release(uint32_t* p, uint32_t v) { asm volatile("red.release.gpu.global.add.u32 [%0], %1;" :: "l"(p), "r"(v) : "memory"); }

__device__ __forceinline__ void wgmma_fence() { asm volatile("wgmma.fence.sync.aligned;" ::: "memory"); }
__device__ __forceinline__ void wgmma_commit() { asm volatile("wgmma.commit_group.sync.aligned;" ::: "memory"); }
template<int N> __device__ __forceinline__ void wgmma_wait() { asm volatile("wgmma.wait_group.sync.aligned %0;" :: "n"(N) : "memory"); }

template<int N> __device__ __forceinline__ void fence_acc(float* d) {
#pragma unroll
    for (int i = 0; i < N; i++) asm volatile("" : "+f"(d[i]) :: "memory");
}
#define ACC8(b) "+f"(d[b]), "+f"(d[b+1]), "+f"(d[b+2]), "+f"(d[b+3]), "+f"(d[b+4]), "+f"(d[b+5]), "+f"(d[b+6]), "+f"(d[b+7])
#define ACC32(b) ACC8(b), ACC8(b+8), ACC8(b+16), ACC8(b+24)
__device__ __forceinline__ void wgmma_n128(float* d, uint64_t da, uint64_t db, int scale_d) {
    asm volatile("{ .reg .pred p; setp.ne.b32 p, %66, 0;\n"
        "wgmma.mma_async.sync.aligned.m64n128k16.f32.bf16.bf16 {%0,%1,%2,%3,%4,%5,%6,%7,%8,%9,%10,%11,%12,%13,%14,%15,%16,%17,%18,%19,%20,%21,%22,%23,%24,%25,%26,%27,%28,%29,%30,%31,"
        "%32,%33,%34,%35,%36,%37,%38,%39,%40,%41,%42,%43,%44,%45,%46,%47,%48,%49,%50,%51,%52,%53,%54,%55,%56,%57,%58,%59,%60,%61,%62,%63}, %64, %65, p, 1, 1, 0, 1; }"
        : ACC32(0), ACC32(32) : "l"(da), "l"(db), "r"(scale_d));
}
__device__ __forceinline__ void wgmma_n256(float* d, uint64_t da, uint64_t db, int scale_d) {
    asm volatile("{ .reg .pred p; setp.ne.b32 p, %130, 0;\n"
        "wgmma.mma_async.sync.aligned.m64n256k16.f32.bf16.bf16 {%0,%1,%2,%3,%4,%5,%6,%7,%8,%9,%10,%11,%12,%13,%14,%15,%16,%17,%18,%19,%20,%21,%22,%23,%24,%25,%26,%27,%28,%29,%30,%31,"
        "%32,%33,%34,%35,%36,%37,%38,%39,%40,%41,%42,%43,%44,%45,%46,%47,%48,%49,%50,%51,%52,%53,%54,%55,%56,%57,%58,%59,%60,%61,%62,%63,"
        "%64,%65,%66,%67,%68,%69,%70,%71,%72,%73,%74,%75,%76,%77,%78,%79,%80,%81,%82,%83,%84,%85,%86,%87,%88,%89,%90,%91,%92,%93,%94,%95,"
        "%96,%97,%98,%99,%100,%101,%102,%103,%104,%105,%106,%107,%108,%109,%110,%111,%112,%113,%114,%115,%116,%117,%118,%119,%120,%121,%122,%123,%124,%125,%126,%127}, %128, %129, p, 1, 1, 0, 1; }"
        : ACC32(0), ACC32(32), ACC32(64), ACC32(96) : "l"(da), "l"(db), "r"(scale_d));
}
__device__ __forceinline__ uint64_t make_desc(uint32_t addr, uint32_t lbo, uint32_t sbo) {
    return (uint64_t)((addr & 0x3FFFF) >> 4) | ((uint64_t)(lbo >> 4) << 16) | ((uint64_t)(sbo >> 4) << 32) | ((uint64_t)1 << 62);
}

__device__ __forceinline__ float div_fix(float a, float b, float rb) { float q = a * rb; float r = fmaf(-q, b, a); return fmaf(r, rb, q); }
__device__ __forceinline__ void row_item(int mode, uint32_t sx, uint32_t sa, uint32_t sp, uint32_t bar_empty, float* __restrict__ acc, bf16* __restrict__ yout, bf16* __restrict__ out, int lane) {
    float x[20];
#pragma unroll
    for (int i = 0; i < 5; i++) {
        const uint2 v = lds64(sx + i * 256 + lane * 8);
        x[4 * i] = __uint_as_float(v.x << 16); x[4 * i + 1] = __uint_as_float(v.x & 0xffff0000u);
        x[4 * i + 2] = __uint_as_float(v.y << 16); x[4 * i + 3] = __uint_as_float(v.y & 0xffff0000u);
    }
    if (mode) {
#pragma unroll
        for (int i = 0; i < 5; i++) {
            const uint4 a = lds128(sa + i * 512 + lane * 16), gt = lds128(sp + i * 512 + lane * 16);
            x[4 * i] = bf16r(x[4 * i] + bf16r(__uint_as_float(gt.x) * bf16r(__uint_as_float(a.x)))); x[4 * i + 1] = bf16r(x[4 * i + 1] + bf16r(__uint_as_float(gt.y) * bf16r(__uint_as_float(a.y))));
            x[4 * i + 2] = bf16r(x[4 * i + 2] + bf16r(__uint_as_float(gt.z) * bf16r(__uint_as_float(a.z)))); x[4 * i + 3] = bf16r(x[4 * i + 3] + bf16r(__uint_as_float(gt.w) * bf16r(__uint_as_float(a.w))));
            *(uint2*)(yout + i * 128 + lane * 4) = make_uint2(pack_bf16(x[4 * i], x[4 * i + 1]), pack_bf16(x[4 * i + 2], x[4 * i + 3]));
        }
        sp += 2560;
    }
    if (mode != 2) {
#pragma unroll
        for (int i = 0; i < 5; i++) *(float4*)(acc + i * 128 + lane * 4) = make_float4(0.f, 0.f, 0.f, 0.f);
    }
    if (mode != 2) {
        float s = 0;
#pragma unroll
        for (int i = 0; i < 20; i++) s += x[i];
#pragma unroll
        for (int o = 16; o; o >>= 1) s += __shfl_xor_sync(0xffffffff, s, o);
        const float mean = s * (1.0f / 640.0f);
        float q = 0;
#pragma unroll
        for (int i = 0; i < 20; i++) { float d = x[i] - mean; q += d * d; }
#pragma unroll
        for (int o = 16; o; o >>= 1) q += __shfl_xor_sync(0xffffffff, q, o);
        const float m16 = bf16r(mean);
        const float sd = bf16r(sqrtf(bf16r(bf16r(q * (1.0f / 640.0f)) + 1e-5f)));
        const float rs = __frcp_rn(sd);
#pragma unroll
        for (int i = 0; i < 5; i++) {
            const uint4 sh = lds128(sp + i * 512 + lane * 16), sc = lds128(sp + 2560 + i * 512 + lane * 16);
            float y0 = bf16r(bf16r(div_fix(bf16r(x[4 * i] - m16), sd, rs)) * bf16r(1.0f + __uint_as_float(sc.x))) + __uint_as_float(sh.x);
            float y1 = bf16r(bf16r(div_fix(bf16r(x[4 * i + 1] - m16), sd, rs)) * bf16r(1.0f + __uint_as_float(sc.y))) + __uint_as_float(sh.y);
            float y2 = bf16r(bf16r(div_fix(bf16r(x[4 * i + 2] - m16), sd, rs)) * bf16r(1.0f + __uint_as_float(sc.z))) + __uint_as_float(sh.z);
            float y3 = bf16r(bf16r(div_fix(bf16r(x[4 * i + 3] - m16), sd, rs)) * bf16r(1.0f + __uint_as_float(sc.w))) + __uint_as_float(sh.w);
            *(uint2*)(out + i * 128 + lane * 4) = make_uint2(pack_bf16(y0, y1), pack_bf16(y2, y3));
        }
    }
    __syncwarp();
    if (lane == 0) mbar_arrive(bar_empty);
}

__device__ __forceinline__ float gelu_tanh(float x) {
    float u2 = x * fmaf(x * x, 2.0f * 0.7978845608028654f * 0.044715f * 1.4426950408889634f, 2.0f * 0.7978845608028654f * 1.4426950408889634f);
    float e; asm("ex2.approx.ftz.f32 %0, %1;" : "=f"(e) : "f"(-u2));
    return __fdividef(x, 1.0f + e);
}
__device__ __forceinline__ uint4 ldg128(const void* p) { uint4 v; asm volatile("ld.global.v4.u32 {%0,%1,%2,%3}, [%4];" : "=r"(v.x), "=r"(v.y), "=r"(v.z), "=r"(v.w) : "l"(p) : "memory"); return v; }
__device__ __forceinline__ float4 ldcg_f4(const float* p) { float4 v; asm volatile("ld.global.cg.v4.f32 {%0,%1,%2,%3}, [%4];" : "=f"(v.x), "=f"(v.y), "=f"(v.z), "=f"(v.w) : "l"(p) : "memory"); return v; }
__device__ __forceinline__ uint4 ldcg128(const void* p) { uint4 v; asm volatile("ld.global.cg.v4.u32 {%0,%1,%2,%3}, [%4];" : "=r"(v.x), "=r"(v.y), "=r"(v.z), "=r"(v.w) : "l"(p) : "memory"); return v; }

__device__ __forceinline__ void attn_scores(uint32_t sq, uint32_t sk, uint32_t skm, int sg, int mt, int lane, uint32_t (&p)[6][2]) {
    const int g = lane >> 2, t = lane & 3, l7 = lane & 7;
    float s[5][4];
#pragma unroll
    for (int kt = 0; kt < 5; kt++) s[kt][0] = s[kt][1] = s[kt][2] = s[kt][3] = 0.f;
    const uint32_t qrow = sq + (sg * 32 + mt * 16 + (lane & 15)) * 128;
    const uint32_t krow = sk + (sg * 32 + l7) * 128, kmrow = skm + (sg * 8 + l7) * 128;
#pragma unroll
    for (int c = 0; c < 4; c++) {
        uint32_t a0[4], a1[4];
        ldsm_x4(a0, qrow + (c >> 1) * 16384 + ((((4 * c + (lane >> 4)) & 7) ^ l7) << 4));
        ldsm_x4(a1, qrow + (c >> 1) * 16384 + ((((4 * c + 2 + (lane >> 4)) & 7) ^ l7) << 4));
        const uint32_t sw = (((4 * c + (lane >> 3)) & 7) ^ l7) << 4;
#pragma unroll
        for (int kt = 0; kt < 5; kt++) {
            uint32_t b[4];
            ldsm_x4(b, kt == 0 ? kmrow + (c >> 1) * 4096 + sw : krow + (kt - 1) * 1024 + (c >> 1) * 16384 + sw);
            mma16816(s[kt], a0, b[0], b[1]); mma16816(s[kt], a1, b[2], b[3]);
        }
    }
    const float scale = 0.08838834764831845f;
    const int r0 = mt * 16 + g, r1 = r0 + 8;
    float m0 = -INFINITY, m1 = -INFINITY;
#pragma unroll
    for (int kt = 0; kt < 5; kt++) {
#pragma unroll
        for (int i = 0; i < 4; i++) {
            float v = bf16r(bf16r(s[kt][i]) * scale);
            if (kt > 0) { int key = (kt - 1) * 8 + 2 * t + (i & 1); if (key > (i < 2 ? r0 : r1)) v = -1.0e9f; }
            s[kt][i] = v;
            if (i < 2) m0 = fmaxf(m0, v); else m1 = fmaxf(m1, v);
        }
    }
    m0 = fmaxf(m0, __shfl_xor_sync(0xffffffff, m0, 1)); m0 = fmaxf(m0, __shfl_xor_sync(0xffffffff, m0, 2));
    m1 = fmaxf(m1, __shfl_xor_sync(0xffffffff, m1, 1)); m1 = fmaxf(m1, __shfl_xor_sync(0xffffffff, m1, 2));
    float l0 = 0, l1 = 0;
#pragma unroll
    for (int kt = 0; kt < 5; kt++) {
        s[kt][0] = __expf(s[kt][0] - m0); s[kt][1] = __expf(s[kt][1] - m0); l0 += s[kt][0] + s[kt][1];
        s[kt][2] = __expf(s[kt][2] - m1); s[kt][3] = __expf(s[kt][3] - m1); l1 += s[kt][2] + s[kt][3];
    }
    l0 += __shfl_xor_sync(0xffffffff, l0, 1); l0 += __shfl_xor_sync(0xffffffff, l0, 2);
    l1 += __shfl_xor_sync(0xffffffff, l1, 1); l1 += __shfl_xor_sync(0xffffffff, l1, 2);
    const float i0 = __fdividef(1.0f, l0), i1 = __fdividef(1.0f, l1);
#pragma unroll
    for (int kt = 0; kt < 5; kt++) { p[kt][0] = pack_bf16(s[kt][0] * i0, s[kt][1] * i0); p[kt][1] = pack_bf16(s[kt][2] * i1, s[kt][3] * i1); }
    p[5][0] = p[5][1] = 0;
}
__device__ __forceinline__ void attn_pv(uint32_t sv, uint32_t svm, int sg, int lane, const uint32_t (&p)[6][2], float* d) {
    const int l7 = lane & 7, hi = (lane >> 3) & 1, ec = lane >> 4;
    const uint32_t r0 = hi ? sv + (sg * 32 + l7) * 128 : svm + (sg * 8 + l7) * 128;
    const uint32_t sub0 = hi ? 16384 : 4096;
    const uint32_t r1 = sv + (sg * 32 + 8 + hi * 8 + l7) * 128;
    const uint32_t r2 = sv + (sg * 32 + 24 + l7) * 128;
#pragma unroll
    for (int i = 0; i < 8; i++) {
        const uint32_t sw = (((2 * i + ec) & 7) ^ l7) << 4;
        uint32_t b0[4], b1[4], b2[4];
        ldsm_x4_t(b0, r0 + (i >> 2) * sub0 + sw); ldsm_x4_t(b1, r1 + (i >> 2) * 16384 + sw); ldsm_x4_t(b2, r2 + (i >> 2) * 16384 + sw);
        float* o0 = d + 8 * i; float* o1 = o0 + 4;
        o0[0] = o0[1] = o0[2] = o0[3] = o1[0] = o1[1] = o1[2] = o1[3] = 0.f;
        { uint32_t a[4] = {p[0][0], p[0][1], p[1][0], p[1][1]}; mma16816(o0, a, b0[0], b0[1]); mma16816(o1, a, b0[2], b0[3]); }
        { uint32_t a[4] = {p[2][0], p[2][1], p[3][0], p[3][1]}; mma16816(o0, a, b1[0], b1[1]); mma16816(o1, a, b1[2], b1[3]); }
        { uint32_t a[4] = {p[4][0], p[4][1], p[5][0], p[5][1]}; mma16816(o0, a, b2[0], b2[1]); mma16816(o1, a, b2[2], b2[3]); }
    }
}
__device__ __forceinline__ void bulk_load(uint32_t dst, const void* src, uint32_t bytes, uint32_t bar) {
    asm volatile("cp.async.bulk.shared::cluster.global.mbarrier::complete_tx::bytes [%0], [%1], %2, [%3];" :: "r"(dst), "l"(src), "r"(bytes), "r"(bar) : "memory");
}

__device__ __forceinline__ void stsm_x4(uint32_t addr, uint32_t a, uint32_t b, uint32_t c, uint32_t d) {
    asm volatile("stmatrix.sync.aligned.m8n8.x4.shared.b16 [%0], {%1,%2,%3,%4};" :: "r"(addr), "r"(a), "r"(b), "r"(c), "r"(d) : "memory");
}
__device__ __forceinline__ void tma_reduce_2d(const CUtensorMap* map, uint32_t src, int c0, int c1) {
    asm volatile("cp.reduce.async.bulk.tensor.2d.global.shared::cta.add.tile.bulk_group [%0, {%2, %3}], [%1];" :: "l"(map), "r"(src), "r"(c0), "r"(c1) : "memory");
}
__device__ __forceinline__ void tma_store_2d(const CUtensorMap* map, uint32_t src, int c0, int c1) {
    asm volatile("cp.async.bulk.tensor.2d.global.shared::cta.bulk_group [%0, {%2, %3}], [%1];" :: "l"(map), "r"(src), "r"(c0), "r"(c1) : "memory");
}

__global__ void __launch_bounds__(384, 1)
g_kernel(const __grid_constant__ GParams P, const bf16* __restrict__ x, const bf16* __restrict__ cvec, const bf16* __restrict__ w_mod, bf16* __restrict__ out, int nctas, int wait_r)
{
    using namespace gk;
    extern __shared__ __align__(1024) uint8_t smem[];
    const uint32_t sb = smem_u32(smem);
    const int tid = threadIdx.x, warp = tid >> 5, lane = tid & 31;
    const uint32_t b_full = sb + OFF_BAR, b_empty = b_full + 8 * STAGES, b_wfull = b_empty + 8 * STAGES, b_wempty = b_wfull + 16;
    const uint32_t b_cdone = b_wempty + 16, b_sfree = b_cdone + 16;
    volatile int* wslot = (volatile int*)(smem + OFF_BAR + 192);
    const uint32_t epoch = ld_relaxed(&g_epoch);
    const uint32_t e1 = epoch + 1;
    if (tid == 0) {
        wslot[4] = 0;
        for (int i = 0; i < STAGES; i++) { mbar_init(b_full + 8 * i, 1); mbar_init(b_empty + 8 * i, 8); }
        for (int i = 0; i < 2; i++) { mbar_init(b_wfull + 8 * i, 1); mbar_init(b_wempty + 8 * i, 9); mbar_init(b_cdone + 8 * i, 4); mbar_init(b_sfree + 8 * i, 1); }
        asm volatile("fence.mbarrier_init.release.cluster;" ::: "memory");
    }
    __syncthreads();

    if (warp < 4) {
        asm volatile("setmaxnreg.dec.sync.aligned.u32 40;");
        if (warp == 0 && lane == 0) {
            uint32_t stage = 0, sph = 1, wi = 0, wph = 1;
            bool low_left = true;
            uint32_t lx0 = 0, lx1 = 0, lx2 = 0;
            int lim = 0, issued = 0, nat = 0;
            volatile int* fin_cnt = wslot + 4;
            while (true) {
                Item it; it.type = T_END; it.rb = it.nt = it.ks = 0;
                int tk = 0; (void)tk;
                while (true) {
                    uint4 rd = ld_relaxed_v4(&g_st.ready[0]); const uint4 ex = ld_relaxed_v4(&g_st.exh[0]);
                    const uint32_t dat = nat < 16 ? ld_relaxed(&g_st.d_at[nat * 32]) : 0;
                    if (nat < 16 && dat == e1 * ((wait_r ? 112u : 48u) + (nat == 0 ? 32u : 0u))) { if (!(rd.x >> nat & 1)) publish_group(T_AT, nat, e1); nat++; }
                    { const int na = __popc(rd.x & 0xffffu); if (na > nat) nat = na; }
                    rd.x |= (1u << nat) - 1;
                    lx0 |= ex.x; lx1 |= ex.y; lx2 |= ex.z;
                    uint32_t a0 = rd.x & ~lx0, a1 = rd.y & ~lx1, a2 = rd.z & ~lx2;
                    bool got = false;
                    if (low_left && (int)rd.w < I_W + 96 + (nat + URGENT_LEAD) * 48 && (int)rd.w < N_LOW) a0 = a1 = a2 = 0;
                    if ((a0 | a1 | a2) && (rd.x >> (FINE_RB - 1) & 1) && *fin_cnt != issued) {
                        int l2 = 0; while (*fin_cnt != issued && ++l2 < SPIN_LIMIT) { }
                        continue;
                    }
                    while (a0 | a1 | a2) {
                        const int gi = a0 ? __ffs(a0) - 1 : (a1 ? 32 + __ffs(a1) - 1 : 64 + __ffs(a2) - 1);
                        const int ty = T_AT + (gi >> 4), rb = gi & 15, n = group_size(ty, rb);
                        const int i = (int)atomicAdd(&g_st.cnt[gi * 8], 1u);
                        const uint32_t bit = 1u << (gi & 31);
                        if (i >= n - 1) {
                            if (gi < 32) { lx0 |= bit; a0 &= ~bit; } else if (gi < 64) { lx1 |= bit; a1 &= ~bit; } else { lx2 |= bit; a2 &= ~bit; }
                            if (i == n - 1) asm volatile("red.relaxed.gpu.global.or.b32 [%0], %1;" :: "l"(&g_st.exh[gi >> 5]), "r"(bit) : "memory");
                        }
                        if (i < n) {
                            it.type = ty; it.rb = rb; it.nt = i;
                            if (ty == T_WO || ty == T_F2) { const int nn = n_nt(rb); it.ks = i / nn; it.nt = i - it.ks * nn; }
                            asm volatile("fence.acq_rel.gpu;" ::: "memory");
                            got = true; break;
                        }
                    }
                    if (got) {
                        break;
                    }
                    if (low_left && (int)rd.w < I_W + 96 + (nat + LOW_LEAD) * 48) {
                        const int lt = (int)atomicAdd(&g_st.lq_claim, 1u);
                        if (lt < N_LOW) {
                            it = decode_low(lt);
                            if (it.type == T_L1) wait_ge(&g_st.c_mod_a, e1 * 20);
                            else if (it.type != T_MOD) wait_ge(&g_st.f_h[it.rb * 32], e1 * 16);
                            break;
                        }
                        low_left = false;
                    }
                    if ((lx0 & lx1 & lx2) == 0xffffffffu) break;
                    if (!low_left && nat >= PRECLAIM_RB && (blockIdx.x % PRECLAIM_MOD) != 0) {
                        const uint32_t rdw[3] = {rd.x, rd.y, rd.z}, lxw[3] = {lx0, lx1, lx2};
                        int gsel = -1;
#pragma unroll
                        for (int rb = 15; rb >= PRECLAIM_RB; rb--) {
#pragma unroll
                            for (int k = 5; k >= 0; k--) {
                                const int gi = k * 16 + rb;
                                const bool rdy = rdw[gi >> 5] >> (gi & 31) & 1, exq = lxw[gi >> 5] >> (gi & 31) & 1;
                                const bool pre = k == 0 ? (nat == rb) : (rdw[(gi - 16) >> 5] >> ((gi - 16) & 31) & 1);
                                if (!rdy && !exq && pre) gsel = gi;
                            }
                        }
                        if (gsel >= 0) {
                            const int gi = gsel, ty = T_AT + (gi >> 4), rb = gi & 15, n = group_size(ty, rb);
                            const int i = (int)atomicAdd(&g_st.cnt[gi * 8], 1u);
                            const uint32_t bit = 1u << (gi & 31);
                            if (i >= n - 1) {
                                if (gi < 32) lx0 |= bit; else if (gi < 64) lx1 |= bit; else lx2 |= bit;
                                if (i == n - 1) asm volatile("red.relaxed.gpu.global.or.b32 [%0], %1;" :: "l"(&g_st.exh[gi >> 5]), "r"(bit) : "memory");
                            }
                            if (i < n) {
                                it.type = ty; it.rb = rb; it.nt = i;
                                if (ty == T_WO || ty == T_F2) { const int nn = n_nt(rb); it.ks = i / nn; it.nt = i - it.ks * nn; }
                                const uint32_t* dp = (ty == T_AT ? g_st.d_at : ty == T_WO ? g_st.c_at : ty == T_L2 ? g_st.c_wo : ty == T_F1 ? g_st.f_h2 : ty == T_F2 ? g_st.c_act : g_st.c_f2) + rb * 32;
                                const uint32_t dt = e1 * (ty == T_AT ? (wait_r ? 112u : 48u) : (uint32_t)group_size(ty - 1, rb));
                                int l3 = 0;
                                while ((int32_t)(ld_acquire(dp) - dt) < 0) { if (++l3 > SPIN_LIMIT) break; }
                                break;
                            }
                            continue;
                        }
                    }
                    __nanosleep(40);
                    if (++lim > SPIN_LIMIT) break;
                }
                issued++;
                if (it.type == T_L2) wait_ge(&g_st.c_mod_all, e1 * 60);
                asm volatile("fence.proxy.async.global;" ::: "memory");
                mbar_wait(b_wempty + 8 * wi, wph);
                wslot[wi] = pack_item(it);
                mbar_arrive(b_wfull + 8 * wi);
                if (++wi == 2) { wi = 0; wph ^= 1; }
                if (it.type == T_END) break;
                int nkb = 0, kb0 = 0;
                const CUtensorMap *mA = nullptr, *mB0 = nullptr, *mB1 = nullptr; int n0 = 0, n1 = 0, nbox = 4;
                switch (it.type) {
                    case T_KV: nkb = 10; mA = &P.tA_h;
                        if (it.ks) { mB0 = mB1 = (it.nt < 32) ? &P.tB_k : &P.tB_v; n0 = (it.nt & 31) * 128; n1 = n0 + 64; nbox = 2; }
                        else { mB0 = mB1 = (it.nt < 16) ? &P.tB_k : &P.tB_v; n0 = (it.nt & 15) * 256; n1 = n0 + 128; }
                        break;
                    case T_Q: nkb = 10; mA = &P.tA_h; mB0 = mB1 = &P.tB_q; n0 = it.nt * 256; n1 = n0 + 128; break;
                    case T_F1: nkb = 10; mA = &P.tA_h2; mB0 = &P.tB_g; mB1 = &P.tB_u; if (fine(it.rb)) { n0 = n1 = it.nt * 64; nbox = 2; } else n0 = n1 = it.nt * 128; break;
                    case T_WO: nkb = 64 / wo_split(it.rb); kb0 = it.ks * nkb; mA = &P.tA_o; mB0 = mB1 = &P.tB_o; n0 = red_col(it); if (is_wide(it)) n1 = n0 + 128; else { n1 = n0 + 64; nbox = 2; } break;
                    case T_F2: nkb = 27 / f2_split(it.rb); kb0 = it.ks * nkb; mA = &P.tA_act; mB0 = mB1 = &P.tB_d; n0 = red_col(it); if (is_wide(it)) n1 = n0 + 128; else { n1 = n0 + 64; nbox = 2; } break;
                    default: break;
                }
                if (it.type == T_AT) {
#pragma unroll 1
                    for (int i = 0; i < 3; i++) {
                        mbar_wait(b_empty + 8 * stage, sph);
                        const uint32_t st = sb + stage * STAGE_BYTES, bar = b_full + 8 * stage;
                        mbar_expect_tx(bar, i ? 40960 : 32768);
                        const CUtensorMap* m = i == 0 ? &P.tL_q : (i == 1 ? &P.tL_k : &P.tL_v);
                        tma_load_2d(st + 16384, m, it.nt * 128, it.rb * 128, bar);
                        tma_load_2d(st + 32768, m, it.nt * 128 + 64, it.rb * 128, bar);
                        if (i) {
                            const CUtensorMap* mm = i == 1 ? &P.tL_km : &P.tL_vm;
                            tma_load_2d(st, mm, it.nt * 128, it.rb * 32, bar);
                            tma_load_2d(st + 4096, mm, it.nt * 128 + 64, it.rb * 32, bar);
                        }
                        if (++stage == STAGES) { stage = 0; sph ^= 1; }
                    }
                } else if (it.type == T_L1 || it.type == T_L2 || it.type == T_FIN) {
                    const int mode = it.type == T_L1 ? 0 : (it.type == T_L2 ? 1 : 2);
                    const uint32_t pbytes = mode == 0 ? 5120 : (mode == 1 ? 7680 : 2560);
                    const float* psrc = g_mod + (mode == 0 ? 0 : (mode == 1 ? 2 * 640 : 5 * 640));
                    {
                        mbar_wait(b_empty + 8 * stage, sph);
                        const uint32_t st = sb + stage * STAGE_BYTES, bar = b_full + 8 * stage;
                        const size_t ro = ((size_t)it.rb * 128 + it.nt * 8) * 640;
                        mbar_expect_tx(bar, 10240 + (mode ? 20480 : 0) + pbytes);
                        bulk_load(st, (mode == 2 ? g_x1 : x) + ro, 10240, bar);
                        if (mode) bulk_load(st + 10240, g_slab + ro, 20480, bar);
                        bulk_load(st + 30720, psrc, pbytes, bar);
                        if (++stage == STAGES) { stage = 0; sph ^= 1; }
                    }
                }
                for (int kb = 0; kb < nkb; kb++) {
                    mbar_wait(b_empty + 8 * stage, sph);
                    const uint32_t st = sb + stage * STAGE_BYTES, bar = b_full + 8 * stage;
                    mbar_expect_tx(bar, 16384 + nbox * 8192);
                    const int k = (kb0 + kb) * 64;
                    tma_load_2d(st, mA, k, it.rb * 128, bar);
                    tma_load_2d(st + 16384, mB0, n0, k, bar);
                    if (nbox == 4) {
                        tma_load_2d(st + 16384 + 8192, mB0, n0 + 64, k, bar);
                        tma_load_2d(st + 16384 + 16384, mB1, n1, k, bar);
                        tma_load_2d(st + 16384 + 24576, mB1, n1 + 64, k, bar);
                    } else {
                        tma_load_2d(st + 16384 + 8192, mB1, n1, k, bar);
                    }
                    if (++stage == STAGES) { stage = 0; sph ^= 1; }
                }
            }
        } else if (warp == 1 && lane == 0) {
            uint32_t wi = 0, wph = 0, cph = 0;
            while (true) {
                mbar_wait(b_wfull + 8 * wi, wph);
                const Item it = unpack_item(wslot[wi]);
                mbar_arrive(b_wempty + 8 * wi);
                if (++wi == 2) { wi = 0; wph ^= 1; }
                if (it.type == T_END) break;
                asm volatile("fence.proxy.async.global;" ::: "memory");
                const bool red = it.type == T_WO || it.type == T_F2;
                const bool tma = it.type == T_KV || it.type == T_Q || it.type == T_F1 || it.type == T_AT || red;
                const bool narrow = it.type == T_F1 && fine(it.rb);
                const bool kvn = it.type == T_KV && it.ks;
                const int rounds = red ? (is_wide(it) ? 4 : 2) : (((it.type == T_KV || it.type == T_Q) && !kvn) ? 2 : 1);
                const CUtensorMap* mS = it.type == T_F1 ? &P.tS_act : (it.type == T_AT ? &P.tS_o : (it.type == T_Q ? &P.tS_q : (it.nt < (kvn ? 32 : 16) ? &P.tS_k : &P.tS_v)));
                const int gcol = red ? red_col(it) : (narrow ? it.nt * 64 : (rounds == 1 ? (it.nt & 31) * 128 : (it.nt & 15) * 256));
                for (int rnd = 0; rnd < rounds; rnd++) {
                    for (int wg = 0; wg < 2; wg++) {
                        mbar_wait(b_cdone + 8 * wg, cph);
                        const uint32_t stg = sb + OFF_SCR + wg * 16384;
                        const int grow = it.rb * 128 + wg * 64;
                        if (red) {
                            tma_reduce_2d(&P.tR_acc, stg, gcol + rnd * 64, grow);
                            tma_reduce_2d(&P.tR_acc, stg + 8192, gcol + rnd * 64 + 32, grow);
                        } else if (tma) {
                            tma_store_2d(mS, stg, gcol + rnd * 128, grow);
                            if (!narrow) tma_store_2d(mS, stg + 8192, gcol + rnd * 128 + 64, grow);
                        }
                        if (tma) asm volatile("cp.async.bulk.commit_group;" ::: "memory");
                    }
                    cph ^= 1;
                    if (tma) asm volatile("cp.async.bulk.wait_group.read 0;" ::: "memory");
                    mbar_arrive(b_sfree); mbar_arrive(b_sfree + 8);
                }
                if (tma) { asm volatile("cp.async.bulk.wait_group 0;" ::: "memory"); asm volatile("fence.proxy.async.global;" ::: "memory"); }
                if (it.type <= T_KV) asm volatile("fence.acq_rel.gpu;" ::: "memory");
                uint32_t* cnt = nullptr; uint32_t tgt = 0; int nxt = -1;
                switch (it.type) {
                    case T_KV: if (kvn) st_relaxed_u32(&g_kvflag[it.nt], e1);
                        else { st_relaxed_u32(&g_kvflag[it.rb * 64 + it.nt * 2], e1); st_relaxed_u32(&g_kvflag[it.rb * 64 + it.nt * 2 + 1], e1); }
                    case T_Q: red_release_inc(&g_st.d_at[it.rb * 32]); break;
                    case T_MOD: if (it.nt < 20) red_add_relaxed(&g_st.c_mod_a, 1); red_add_relaxed(&g_st.c_mod_all, 1); break;
                    case T_L1: red_add_relaxed(&g_st.f_h[it.rb * 32], 1); break;
                    case T_AT: cnt = &g_st.c_at[it.rb * 32]; tgt = 32; nxt = T_WO; break;
                    case T_WO: cnt = &g_st.c_wo[it.rb * 32]; tgt = group_size(T_WO, it.rb); nxt = T_L2; break;
                    case T_L2: cnt = &g_st.f_h2[it.rb * 32]; tgt = 16; nxt = T_F1; break;
                    case T_F1: cnt = &g_st.c_act[it.rb * 32]; tgt = group_size(T_F1, it.rb); nxt = T_F2; break;
                    case T_F2: cnt = &g_st.c_f2[it.rb * 32]; tgt = group_size(T_F2, it.rb); nxt = T_FIN; break;
                    default: break;
                }
                if (cnt) { if (atom_add_acqrel(cnt, 1) + 1 == e1 * tgt) publish_group(nxt, it.rb, e1); }
            }
            uint32_t old = atom_add_acqrel(&g_st.done, 1);
            if (old + 1 == e1 * (uint32_t)nctas) {
                for (int i = 0; i < 96; i++) g_st.cnt[i * 8] = 0;
                for (int i = 0; i < 3; i++) { g_st.ready[i] = 0; g_st.exh[i] = 0; }
                g_st.lq_claim = 0;
                st_release(&g_epoch, e1);
            }
        }
    } else {
        asm volatile("setmaxnreg.inc.sync.aligned.u32 232;");
        const int ct = tid - 128, cw = warp - 4, wg = cw >> 2;
        const int g = lane >> 2, t = lane & 3;
        uint32_t stage = 0, sph = 0, wi = 0, wph = 0, fph = 1; int ndone = 0;
        while (true) {
            if (ct == 0) wslot[4] = ndone;
            ndone++;
            mbar_wait(b_wfull + 8 * wi, wph);
            const Item it = unpack_item(wslot[wi]);
            __syncwarp();
            if (lane == 0) mbar_arrive(b_wempty + 8 * wi);
            if (++wi == 2) { wi = 0; wph ^= 1; }
            if (it.type == T_END) break;
            const bool narrow = (it.type == T_F1 && fine(it.rb)) || (it.type == T_KV && it.ks);
            if (is_wide(it)) {
                const bool red = it.type == T_WO || it.type == T_F2;
                const int nkb = it.type == T_WO ? 64 / wo_split(it.rb) : (it.type == T_F2 ? 27 / f2_split(it.rb) : 10);
                float d[128];
#pragma unroll
                for (int i = 0; i < 128; i++) d[i] = 0.f;
                for (int kb = 0; kb < nkb; kb++) {
                    mbar_wait(b_full + 8 * stage, sph);
                    const uint32_t st = sb + stage * STAGE_BYTES;
                    const uint64_t da = make_desc(st + wg * 8192, 16, 1024), db = make_desc(st + 16384, 8192, 1024);
                    wgmma_fence();
#pragma unroll
                    for (int k = 0; k < 4; k++) wgmma_n256(d, da + k * 2, db + k * 128, 1);
                    wgmma_commit();
                    wgmma_wait<1>();
                    if (kb > 0 && lane == 0) mbar_arrive(b_empty + 8 * ((stage + STAGES - 1) % STAGES));
                    if (++stage == STAGES) { stage = 0; sph ^= 1; }
                }
                wgmma_wait<0>();
                fence_acc<128>(d);
                if (lane == 0) mbar_arrive(b_empty + 8 * ((stage + STAGES - 1) % STAGES));
                if (red) {
                    const uint32_t sbase = sb + OFF_SCR + wg * 16384 + ((cw & 3) * 16 + g) * 128 + (t & 1) * 8;
#pragma unroll
                    for (int rnd = 0; rnd < 4; rnd++) {
                        mbar_wait(b_sfree + 8 * wg, fph); fph ^= 1;
#pragma unroll
                        for (int i = 0; i < 8; i++) {
                            const float* dd = d + rnd * 32 + i * 4;
                            const uint32_t a = sbase + (i >> 2) * 8192 + ((((2 * i + (t >> 1)) & 7) ^ (g & 7)) << 4);
                            sts64(a, __float_as_uint(dd[0]), __float_as_uint(dd[1]));
                            sts64(a + 1024, __float_as_uint(dd[2]), __float_as_uint(dd[3]));
                        }
                        asm volatile("fence.proxy.async.shared::cta;" ::: "memory");
                        __syncwarp();
                        if (lane == 0) mbar_arrive(b_cdone + 8 * wg);
                    }
                    continue;
                }
                const uint32_t sbase = sb + OFF_SCR + wg * 16384 + ((cw & 3) * 16 + ((lane >> 3) & 1) * 8 + (lane & 7)) * 128;
                const int sx = lane & 7, hi = lane >> 4;
                if (it.type == T_F1) {
#pragma unroll
                    for (int i = 0; i < 64; i++) d[i] = bf16r(gelu_tanh(bf16r(d[i]))) * bf16r(d[64 + i]);
                }
#pragma unroll
                for (int rnd = 0; rnd < 2; rnd++) {
                    if (rnd == 1 && it.type == T_F1) break;
                    mbar_wait(b_sfree + 8 * wg, fph); fph ^= 1;
#pragma unroll
                    for (int i = 0; i < 8; i++) {
                        const float* dd = d + rnd * 64 + i * 8;
                        const int chunk = (2 * i + hi) & 7;
                        stsm_x4(sbase + (i >> 2) * 8192 + ((chunk ^ sx) << 4), pack_bf16(dd[0], dd[1]), pack_bf16(dd[2], dd[3]), pack_bf16(dd[4], dd[5]), pack_bf16(dd[6], dd[7]));
                    }
                    asm volatile("fence.proxy.async.shared::cta;" ::: "memory");
                    __syncwarp();
                    if (lane == 0) mbar_arrive(b_cdone + 8 * wg);
                }
                continue;
            } else if (narrow) {
                float d[64];
#pragma unroll
                for (int i = 0; i < 64; i++) d[i] = 0.f;
                const int nkb = 10;
                for (int kb = 0; kb < nkb; kb++) {
                    mbar_wait(b_full + 8 * stage, sph);
                    const uint32_t st = sb + stage * STAGE_BYTES;
                    const uint64_t da = make_desc(st + wg * 8192, 16, 1024), db = make_desc(st + 16384, 8192, 1024);
                    wgmma_fence();
#pragma unroll
                    for (int k = 0; k < 4; k++) wgmma_n128(d, da + k * 2, db + k * 128, 1);
                    wgmma_commit();
                    wgmma_wait<1>();
                    if (kb > 0 && lane == 0) mbar_arrive(b_empty + 8 * ((stage + STAGES - 1) % STAGES));
                    if (++stage == STAGES) { stage = 0; sph ^= 1; }
                }
                wgmma_wait<0>();
                fence_acc<64>(d);
                if (lane == 0) mbar_arrive(b_empty + 8 * ((stage + STAGES - 1) % STAGES));
                {
                    const uint32_t sbase = sb + OFF_SCR + wg * 16384 + ((cw & 3) * 16 + ((lane >> 3) & 1) * 8 + (lane & 7)) * 128;
                    const bool f1 = it.type == T_F1;
                    if (f1) {
#pragma unroll
                        for (int i = 0; i < 32; i++) d[i] = bf16r(gelu_tanh(bf16r(d[i]))) * bf16r(d[32 + i]);
                    }
                    mbar_wait(b_sfree + 8 * wg, fph); fph ^= 1;
#pragma unroll
                    for (int i = 0; i < 8; i++) {
                        if (i >= 4 && f1) break;
                        const float* dd = d + i * 8;
                        const int chunk = (2 * i + (lane >> 4)) & 7;
                        stsm_x4(sbase + (i >> 2) * 8192 + ((chunk ^ (lane & 7)) << 4), pack_bf16(dd[0], dd[1]), pack_bf16(dd[2], dd[3]), pack_bf16(dd[4], dd[5]), pack_bf16(dd[6], dd[7]));
                    }
                    asm volatile("fence.proxy.async.shared::cta;" ::: "memory");
                }
            } else if (it.type == T_WO || it.type == T_F2) {
                float d[64];
#pragma unroll
                for (int i = 0; i < 64; i++) d[i] = 0.f;
                const int nkb = it.type == T_WO ? 64 / wo_split(it.rb) : 27 / f2_split(it.rb);
                for (int kb = 0; kb < nkb; kb++) {
                    mbar_wait(b_full + 8 * stage, sph);
                    const uint32_t st = sb + stage * STAGE_BYTES;
                    const uint64_t da = make_desc(st + wg * 8192, 16, 1024), db = make_desc(st + 16384, 8192, 1024);
                    wgmma_fence();
#pragma unroll
                    for (int k = 0; k < 4; k++) wgmma_n128(d, da + k * 2, db + k * 128, 1);
                    wgmma_commit();
                    wgmma_wait<1>();
                    if (kb > 0 && lane == 0) mbar_arrive(b_empty + 8 * ((stage + STAGES - 1) % STAGES));
                    if (++stage == STAGES) { stage = 0; sph ^= 1; }
                }
                wgmma_wait<0>();
                fence_acc<64>(d);
                if (lane == 0) mbar_arrive(b_empty + 8 * ((stage + STAGES - 1) % STAGES));
                {
                    const int r0 = (cw & 3) * 16 + g;
                    const uint32_t sbase = sb + OFF_SCR + wg * 16384 + r0 * 128 + (t & 1) * 8;
#pragma unroll
                    for (int rnd = 0; rnd < 2; rnd++) {
                        mbar_wait(b_sfree + 8 * wg, fph); fph ^= 1;
#pragma unroll
                        for (int i = 0; i < 8; i++) {
                            const float* dd = d + rnd * 32 + i * 4;
                            const uint32_t a = sbase + (i >> 2) * 8192 + ((((2 * i + (t >> 1)) & 7) ^ (g & 7)) << 4);
                            sts64(a, __float_as_uint(dd[0]), __float_as_uint(dd[1]));
                            sts64(a + 1024, __float_as_uint(dd[2]), __float_as_uint(dd[3]));
                        }
                        asm volatile("fence.proxy.async.shared::cta;" ::: "memory");
                        if (rnd == 0) { __syncwarp(); if (lane == 0) mbar_arrive(b_cdone + 8 * wg); }
                    }
                }
            } else if (it.type == T_AT) {
                uint32_t p[6][2];
                float d[64];
                const uint32_t s0 = stage, s1 = (stage + 1) % STAGES, s2 = (stage + 2) % STAGES;
                mbar_wait(b_full + 8 * s0, sph);
                mbar_wait(b_full + 8 * s1, s1 < s0 ? sph ^ 1 : sph);
                attn_scores(sb + s0 * STAGE_BYTES + 16384, sb + s1 * STAGE_BYTES + 16384, sb + s1 * STAGE_BYTES, cw >> 1, cw & 1, lane, p);
                __syncwarp();
                if (lane == 0) { mbar_arrive(b_empty + 8 * s0); mbar_arrive(b_empty + 8 * s1); }
                mbar_wait(b_full + 8 * s2, s2 < s0 ? sph ^ 1 : sph);
                attn_pv(sb + s2 * STAGE_BYTES + 16384, sb + s2 * STAGE_BYTES, cw >> 1, lane, p, d);
                __syncwarp();
                if (lane == 0) mbar_arrive(b_empty + 8 * s2);
                stage += 3; if (stage >= STAGES) { stage -= STAGES; sph ^= 1; }
                const uint32_t sbase = sb + OFF_SCR + wg * 16384 + ((cw & 3) * 16 + ((lane >> 3) & 1) * 8 + (lane & 7)) * 128;
                mbar_wait(b_sfree + 8 * wg, fph); fph ^= 1;
#pragma unroll
                for (int i = 0; i < 8; i++) {
                    const float* dd = d + i * 8;
                    const int chunk = (2 * i + (lane >> 4)) & 7;
                    stsm_x4(sbase + (i >> 2) * 8192 + ((chunk ^ (lane & 7)) << 4), pack_bf16(dd[0], dd[1]), pack_bf16(dd[2], dd[3]), pack_bf16(dd[4], dd[5]), pack_bf16(dd[6], dd[7]));
                }
                asm volatile("fence.proxy.async.shared::cta;" ::: "memory");
            } else if (it.type == T_L1 || it.type == T_L2 || it.type == T_FIN) {
                const int mode = it.type == T_L1 ? 0 : (it.type == T_L2 ? 1 : 2);
                {
                    const size_t ro = ((size_t)it.rb * 128 + it.nt * 8 + cw) * 640;
                    const uint32_t st = sb + stage * STAGE_BYTES;
                    mbar_wait(b_full + 8 * stage, sph);
                    row_item(mode, st + cw * 1280, st + 10240 + cw * 2560, st + 30720, b_empty + 8 * stage, g_slab + ro, (mode == 2 ? out : g_x1) + ro, (mode ? g_h2 : g_h) + ro, lane);
                    if (++stage == STAGES) { stage = 0; sph ^= 1; }
                }
            } else if (it.type == T_MOD) {
                const int kg = ct >> 3, c8 = ct & 7;
                float acc[8] = {0, 0, 0, 0, 0, 0, 0, 0};
                const bf16* wp = w_mod + (size_t)kg * 20 * 3840 + it.nt * 64 + c8 * 8;
                {
                    uint4 w[20]; float sl[20];
#pragma unroll
                    for (int i = 0; i < 20; i++) { w[i] = __ldg((const uint4*)(wp + (size_t)i * 3840)); sl[i] = __bfloat162float(cvec[kg * 20 + i]); }
#pragma unroll
                    for (int i = 0; i < 20; i++) {
                        const float s = bf16r(__fdividef(sl[i], 1.0f + __expf(-sl[i])));
                        acc[0] += s * __uint_as_float(w[i].x << 16); acc[1] += s * __uint_as_float(w[i].x & 0xffff0000u);
                        acc[2] += s * __uint_as_float(w[i].y << 16); acc[3] += s * __uint_as_float(w[i].y & 0xffff0000u);
                        acc[4] += s * __uint_as_float(w[i].z << 16); acc[5] += s * __uint_as_float(w[i].z & 0xffff0000u);
                        acc[6] += s * __uint_as_float(w[i].w << 16); acc[7] += s * __uint_as_float(w[i].w & 0xffff0000u);
                    }
                }
#pragma unroll
                for (int i = 0; i < 8; i++) { acc[i] += __shfl_xor_sync(0xffffffff, acc[i], 8); acc[i] += __shfl_xor_sync(0xffffffff, acc[i], 16); }
                float* scr = (float*)(smem + OFF_BAR + 256);
                bar_sync(3, 256);
                if (lane < 8) {
#pragma unroll
                    for (int i = 0; i < 8; i++) scr[cw * 64 + lane * 8 + i] = acc[i];
                }
                bar_sync(3, 256);
                if (ct < 64) {
                    float sum = 0;
#pragma unroll
                    for (int i = 0; i < 8; i++) sum += scr[i * 64 + ct];
                    g_mod[it.nt * 64 + ct] = bf16r(sum);
                }
            }
            if (it.type == T_MOD || it.type == T_L1 || it.type == T_L2 || it.type == T_FIN) { mbar_wait(b_sfree + 8 * wg, fph); fph ^= 1; }
            __syncwarp();
            if (lane == 0) mbar_arrive(b_cdone + 8 * wg);
        }
    }
}

typedef CUresult (*PFN_encodeTiled)(CUtensorMap*, CUtensorMapDataType, cuuint32_t, void*, const cuuint64_t*, const cuuint64_t*, const cuuint32_t*, const cuuint32_t*, CUtensorMapInterleave, CUtensorMapSwizzle, CUtensorMapL2promotion, CUtensorMapFloatOOBfill);

static void make_map(PFN_encodeTiled fn, CUtensorMap* m, const void* ptr, uint64_t inner, uint64_t outer, uint32_t box_inner, uint32_t box_outer, bool f32 = false) {
    cuuint64_t dims[2] = {inner, outer};
    cuuint64_t strides[1] = {inner * (f32 ? 4 : 2)};
    cuuint32_t box[2] = {box_inner, box_outer};
    cuuint32_t es[2] = {1, 1};
    fn(m, f32 ? CU_TENSOR_MAP_DATA_TYPE_FLOAT32 : CU_TENSOR_MAP_DATA_TYPE_BFLOAT16, 2, (void*)ptr, dims, strides, box, es, CU_TENSOR_MAP_INTERLEAVE_NONE, CU_TENSOR_MAP_SWIZZLE_128B, CU_TENSOR_MAP_L2_PROMOTION_L2_256B, CU_TENSOR_MAP_FLOAT_OOB_FILL_NONE);
}

#define G_LESS 0
static int g_dbg_mode = 0;

extern "C" void kernel_launch(void* const* d_in, const int* in_sizes, int n_in, void* d_out, int out_size) {
    const bf16* x = (const bf16*)d_in[0];
    const bf16* mem0 = (const bf16*)d_in[1];
    const bf16* Wq = (const bf16*)d_in[2];
    const bf16* Wk = (const bf16*)d_in[3];
    const bf16* Wv = (const bf16*)d_in[4];
    const bf16* Wo = (const bf16*)d_in[5];
    const bf16* Wg = (const bf16*)d_in[8];
    const bf16* Wu = (const bf16*)d_in[9];
    const bf16* Wd = (const bf16*)d_in[10];
    const bf16* cvec = (const bf16*)d_in[11];
    const bf16* wmod = (const bf16*)d_in[12];
    static PFN_encodeTiled fn = nullptr;
    static int nsm = 0;
    if (!fn) {
        cudaDriverEntryPointQueryResult qr;
        cudaGetDriverEntryPoint("cuTensorMapEncodeTiled", (void**)&fn, cudaEnableDefault, &qr);
        cudaFuncSetAttribute(r_kernel, cudaFuncAttributeMaxDynamicSharedMemorySize, rk::SMEM_BYTES);
        cudaFuncSetAttribute(r_kernel, cudaFuncAttributeNonPortableClusterSizeAllowed, 1);
        cudaFuncSetAttribute(g_kernel, cudaFuncAttributeMaxDynamicSharedMemorySize, gk::SMEM_BYTES);
        cudaDeviceGetAttribute(&nsm, cudaDevAttrMultiProcessorCount, 0);
    }
    void *ph, *po, *ph2, *pact, *pq, *pk, *pv;
    cudaGetSymbolAddress(&pq, g_q); cudaGetSymbolAddress(&pk, g_k); cudaGetSymbolAddress(&pv, g_v);
    cudaGetSymbolAddress(&ph, g_h); cudaGetSymbolAddress(&po, g_o); cudaGetSymbolAddress(&ph2, g_h2); cudaGetSymbolAddress(&pact, g_act);
    GParams P;
    make_map(fn, &P.tA_h, ph, 640, 2048, 64, 128);
    make_map(fn, &P.tA_o, po, 4096, 2048, 64, 128);
    make_map(fn, &P.tA_h2, ph2, 640, 2048, 64, 128);
    make_map(fn, &P.tA_act, pact, 1728, 2048, 64, 128);
    make_map(fn, &P.tB_q, Wq, 4096, 640, 64, 64);
    make_map(fn, &P.tB_k, Wk, 4096, 640, 64, 64);
    make_map(fn, &P.tB_v, Wv, 4096, 640, 64, 64);
    make_map(fn, &P.tB_o, Wo, 640, 4096, 64, 64);
    make_map(fn, &P.tB_g, Wg, 1728, 640, 64, 64);
    make_map(fn, &P.tB_u, Wu, 1728, 640, 64, 64);
    make_map(fn, &P.tB_d, Wd, 640, 1728, 64, 64);
    make_map(fn, &P.tS_q, pq, 4096, 2048, 64, 64);
    make_map(fn, &P.tS_k, pk, 4096, 2048, 64, 64);
    make_map(fn, &P.tS_v, pv, 4096, 2048, 64, 64);
    make_map(fn, &P.tS_act, pact, 1728, 2048, 64, 64);
    void *pkm, *pvm; cudaGetSymbolAddress(&pkm, g_km); cudaGetSymbolAddress(&pvm, g_vm);
    make_map(fn, &P.tS_o, po, 4096, 2048, 64, 64);
    make_map(fn, &P.tL_q, pq, 4096, 2048, 64, 128);
    make_map(fn, &P.tL_k, pk, 4096, 2048, 64, 128);
    make_map(fn, &P.tL_v, pv, 4096, 2048, 64, 128);
    make_map(fn, &P.tL_km, pkm, 4096, 512, 64, 32);
    make_map(fn, &P.tL_vm, pvm, 4096, 512, 64, 32);
    void* pacc; cudaGetSymbolAddress(&pacc, g_slab);
    make_map(fn, &P.tR_acc, pacc, 640, 2048, 32, 64, true);
    cudaStream_t st = cudaStreamPerThread;
    if (g_dbg_mode != 1) {
        cudaLaunchConfig_t cfg = {};
        cfg.gridDim = dim3(64); cfg.blockDim = dim3(256); cfg.dynamicSmemBytes = rk::SMEM_BYTES; cfg.stream = st;
        cudaLaunchAttribute at[1]; at[0].id = cudaLaunchAttributeClusterDimension; at[0].val.clusterDim.x = 16; at[0].val.clusterDim.y = 1; at[0].val.clusterDim.z = 1;
        cfg.attrs = at; cfg.numAttrs = 1;
        CUtensorMap tk, tv;
        make_map(fn, &tk, pk, 4096, 2048, 64, 32);
        make_map(fn, &tv, pv, 4096, 2048, 64, 32);
        cudaLaunchKernelEx(&cfg, r_kernel, tk, tv, mem0, Wq, Wk, Wv, Wo, 1);
    }
    {
        cudaLaunchConfig_t cfg = {};
        const int ng = g_dbg_mode == 1 ? nsm : nsm - G_LESS;
        cfg.gridDim = dim3(ng); cfg.blockDim = dim3(384); cfg.dynamicSmemBytes = gk::SMEM_BYTES; cfg.stream = st;
        cudaLaunchAttribute at[1]; at[0].id = cudaLaunchAttributeProgrammaticStreamSerialization; at[0].val.programmaticStreamSerializationAllowed = 1;
        cfg.attrs = at; cfg.numAttrs = g_dbg_mode == 1 ? 0 : 1;
        cudaLaunchKernelEx(&cfg, g_kernel, P, x, cvec, wmod, (bf16*)d_out, ng, g_dbg_mode == 1 ? 0 : 1);
    }
}
```

```cpp
#include <cuda_runtime.h>
#include <cuda_bf16.h>
#include <cuda.h>
#include <stdint.h>

typedef __nv_bfloat16 bf16;

__device__ __forceinline__ uint32_t smem_u32(const void* p) { return (uint32_t)__cvta_generic_to_shared(p); }
__device__ __forceinline__ uint32_t mapa_u32(uint32_t a, uint32_t r) { uint32_t o; asm volatile("mapa.shared::cluster.u32 %0, %1, %2;" : "=r"(o) : "r"(a), "r"(r)); return o; }
__device__ __forceinline__ void mbar_init(uint32_t bar, uint32_t cnt) { asm volatile("mbarrier.init.shared::cta.b64 [%0], %1;" :: "r"(bar), "r"(cnt) : "memory"); }
__device__ __forceinline__ void mbar_expect_tx(uint32_t bar, uint32_t bytes) { asm volatile("mbarrier.arrive.expect_tx.shared::cta.b64 _, [%0], %1;" :: "r"(bar), "r"(bytes) : "memory"); }
__device__ __forceinline__ void mbar_arrive(uint32_t bar) { asm volatile("mbarrier.arrive.shared::cta.b64 _, [%0];" :: "r"(bar) : "memory"); }
#define SPIN_LIMIT 400000
__device__ __forceinline__ bool mbar_try(uint32_t bar, uint32_t ph) {
    uint32_t ok;
    asm volatile("{ .reg .pred p; mbarrier.try_wait.parity.shared::cta.b64 p, [%1], %2; selp.u32 %0, 1, 0, p; }" : "=r"(ok) : "r"(bar), "r"(ph) : "memory");
    return ok;
}
__device__ __forceinline__ void mbar_wait(uint32_t bar, uint32_t ph) {
    if (mbar_try(bar, ph)) return;
#pragma unroll 1
    for (int lim = 0; lim < SPIN_LIMIT; lim++) if (mbar_try(bar, ph)) break;
}
__device__ __forceinline__ void mbar_wait_cluster(uint32_t bar, uint32_t ph) {
    uint32_t ok = 0; int lim = 0;
    while (true) {
        asm volatile("{ .reg .pred p; mbarrier.try_wait.parity.acquire.cluster.shared::cta.b64 p, [%1], %2; selp.u32 %0, 1, 0, p; }" : "=r"(ok) : "r"(bar), "r"(ph) : "memory");
        if (ok) break;
        if (++lim > SPIN_LIMIT) break;
    }
}
__device__ __forceinline__ void st_async_v4(uint32_t addr, uint32_t a, uint32_t b, uint32_t c, uint32_t d, uint32_t bar) {
    asm volatile("st.async.weak.shared::cluster.mbarrier::complete_tx::bytes.v4.b32 [%0], {%1,%2,%3,%4}, [%5];" :: "r"(addr), "r"(a), "r"(b), "r"(c), "r"(d), "r"(bar) : "memory");
}
__device__ __forceinline__ void ldsm_x4(uint32_t* r, uint32_t addr) {
    asm volatile("ldmatrix.sync.aligned.m8n8.x4.shared.b16 {%0,%1,%2,%3}, [%4];" : "=r"(r[0]), "=r"(r[1]), "=r"(r[2]), "=r"(r[3]) : "r"(addr) : "memory");
}
__device__ __forceinline__ void ldsm_x4_t(uint32_t* r, uint32_t addr) {
    asm volatile("ldmatrix.sync.aligned.m8n8.x4.trans.shared.b16 {%0,%1,%2,%3}, [%4];" : "=r"(r[0]), "=r"(r[1]), "=r"(r[2]), "=r"(r[3]) : "r"(addr) : "memory");
}
__device__ __forceinline__ void mma16816(float* d, const uint32_t* a, uint32_t b0, uint32_t b1) {
    asm volatile("mma.sync.aligned.m16n8k16.row.col.f32.bf16.bf16.f32 {%0,%1,%2,%3}, {%4,%5,%6,%7}, {%8,%9}, {%0,%1,%2,%3};"
        : "+f"(d[0]), "+f"(d[1]), "+f"(d[2]), "+f"(d[3]) : "r"(a[0]), "r"(a[1]), "r"(a[2]), "r"(a[3]), "r"(b0), "r"(b1));
}
__device__ __forceinline__ uint32_t pack_bf16(float lo, float hi) {
    uint32_t r; asm("cvt.rn.bf16x2.f32 %0, %1, %2;" : "=r"(r) : "f"(hi), "f"(lo)); return r;
}
__device__ __forceinline__ float bf16r(float x) { return __bfloat162float(__float2bfloat16_rn(x)); }
__device__ __forceinline__ uint4 lds128(uint32_t a) { uint4 v; asm volatile("ld.shared.v4.u32 {%0,%1,%2,%3}, [%4];" : "=r"(v.x), "=r"(v.y), "=r"(v.z), "=r"(v.w) : "r"(a) : "memory"); return v; }
__device__ __forceinline__ void sts128(uint32_t a, uint4 v) { asm volatile("st.shared.v4.u32 [%0], {%1,%2,%3,%4};" :: "r"(a), "r"(v.x), "r"(v.y), "r"(v.z), "r"(v.w) : "memory"); }
__device__ __forceinline__ void sts32(uint32_t a, uint32_t v) { asm volatile("st.shared.u32 [%0], %1;" :: "r"(a), "r"(v) : "memory"); }
__device__ __forceinline__ void sts64(uint32_t a, uint32_t x, uint32_t y) { asm volatile("st.shared.v2.u32 [%0], {%1,%2};" :: "r"(a), "r"(x), "r"(y) : "memory"); }
__device__ __forceinline__ void sts16(uint32_t a, uint16_t v) { asm volatile("st.shared.u16 [%0], %1;" :: "r"(a), "h"(v) : "memory"); }
__device__ __forceinline__ uint2 lds64(uint32_t a) { uint2 v; asm volatile("ld.shared.v2.u32 {%0,%1}, [%2];" : "=r"(v.x), "=r"(v.y) : "r"(a) : "memory"); return v; }
__device__ __forceinline__ void cp_async16(uint32_t dst, const void* src) { asm volatile("cp.async.cg.shared.global [%0], [%1], 16;" :: "r"(dst), "l"(src) : "memory"); }
__device__ __forceinline__ void cp_async_wait_all() { asm volatile("cp.async.wait_all;" ::: "memory"); }
__device__ __forceinline__ void bar_sync(int id, int n) { asm volatile("bar.sync %0, %1;" :: "r"(id), "r"(n) : "memory"); }
__device__ __forceinline__ uint4 ld_relaxed_v4(const void* p) {
    uint4 v; asm volatile("ld.relaxed.gpu.global.v4.u32 {%0,%1,%2,%3}, [%4];" : "=r"(v.x), "=r"(v.y), "=r"(v.z), "=r"(v.w) : "l"(p) : "memory"); return v;
}
__device__ __forceinline__ void st_relaxed_v4(void* p, uint4 v) {
    asm volatile("st.relaxed.gpu.global.v4.u32 [%0], {%1,%2,%3,%4};" :: "l"(p), "r"(v.x), "r"(v.y), "r"(v.z), "r"(v.w) : "memory");
}
__device__ __forceinline__ uint32_t ld_acquire(const uint32_t* p) { uint32_t v; asm volatile("ld.acquire.gpu.global.u32 %0, [%1];" : "=r"(v) : "l"(p) : "memory"); return v; }
__device__ __forceinline__ uint32_t ld_relaxed(const uint32_t* p) { uint32_t v; asm volatile("ld.relaxed.gpu.global.u32 %0, [%1];" : "=r"(v) : "l"(p) : "memory"); return v; }
__device__ __forceinline__ void st_release(uint32_t* p, uint32_t v) { asm volatile("st.release.gpu.global.u32 [%0], %1;" :: "l"(p), "r"(v) : "memory"); }
__device__ __forceinline__ void cluster_sync_all() {
    asm volatile("barrier.cluster.arrive.release.aligned;" ::: "memory");
    asm volatile("barrier.cluster.wait.acquire.aligned;" ::: "memory");
}

__device__ bf16 g_k[2048 * 4096];
__device__ bf16 g_v[2048 * 4096];
__device__ bf16 g_km[64 * 8 * 4096];
__device__ bf16 g_vm[64 * 8 * 4096];
__device__ uint4 g_gx[2][4][16][80];
__device__ uint32_t g_kvflag[16 * 64];
__device__ uint32_t g_epoch;
struct GState {
    uint32_t done, c_mod_a, c_mod_all, unused0;
    uint32_t pad0[28];
    uint32_t ready[3], lq_claim, exh[4];
    uint32_t pad1[24];
    uint32_t cnt[96 * 8];
    uint32_t f_h[16 * 32];
    uint32_t d_at[16 * 32];
    uint32_t c_at[16 * 32];
    uint32_t c_wo[16 * 32];
    uint32_t f_h2[16 * 32];
    uint32_t c_act[16 * 32];
    uint32_t c_f2[16 * 32];
};
__device__ GState g_st;
namespace gk {
enum { T_MOD, T_L1, T_KV, T_Q, T_AT, T_WO, T_L2, T_F1, T_F2, T_FIN, T_SKIP, T_END };
#define FINE_RB 13
__host__ __device__ __forceinline__ bool fine(int rb) { return rb >= FINE_RB; }
#define WO_FINE 16
#define WO_COARSE 8
__host__ __device__ __forceinline__ int wo_split(int rb) { return fine(rb) ? WO_FINE : WO_COARSE; }
__host__ __device__ __forceinline__ int f2_split(int rb) { return fine(rb) ? 9 : 3; }
__host__ __device__ __forceinline__ int n_nt(int rb) { return fine(rb) ? 5 : 3; }
__host__ __device__ __forceinline__ int n_f1(int rb) { return fine(rb) ? 27 : 14; }
__host__ __device__ __forceinline__ int group_size(int ty, int rb) {
    switch (ty) {
        case T_AT: return fine(rb) ? 32 : 16;
        case T_WO: return n_nt(rb) * wo_split(rb);
        case T_F1: return n_f1(rb);
        case T_F2: return n_nt(rb) * f2_split(rb);
        default: return fine(rb) ? 16 : 8;
    }
}
__host__ __device__ __forceinline__ int reps(int ty, int rb) { return (ty == T_L1 ? rb >= 3 : !fine(rb)) ? 2 : 1; }
}
__device__ __forceinline__ uint32_t atom_add_acqrel(uint32_t* p, uint32_t v) {
    uint32_t o; asm volatile("atom.acq_rel.gpu.global.add.u32 %0, [%1], %2;" : "=r"(o) : "l"(p), "r"(v) : "memory"); return o;
}
__device__ __forceinline__ void red_release_inc(uint32_t* p) { asm volatile("red.release.gpu.global.add.u32 [%0], 1;" :: "l"(p) : "memory"); }
__device__ __forceinline__ void publish_group(int ty, int rb, uint32_t) {
    const int gi = (ty - gk::T_AT) * 16 + rb;
    asm volatile("red.release.gpu.global.or.b32 [%0], %1;" :: "l"(&g_st.ready[gi >> 5]), "r"(1u << (gi & 31)) : "memory");
}
#define RT(i)

#define POLL_DELAY 300
#define MEMSH 1
namespace rk {
constexpr int MEM_STRIDE = 1296;
constexpr int T_STRIDE = 272;
constexpr int OFF_W = 0;
constexpr int OFF_KX = 163840;
constexpr int OFF_VX = OFF_KX + 8192;
constexpr int OFF_MEM = OFF_VX + 8192;
constexpr int OFF_Q = OFF_MEM + 10240;
constexpr int OFF_KM = OFF_Q + 8 * T_STRIDE;
constexpr int OFF_VM = OFF_KM + 8 * T_STRIDE;
constexpr int OFF_O = OFF_VM + 8 * T_STRIDE;
constexpr int OFF_SC = OFF_O + 8 * T_STRIDE;
constexpr int OFF_RED = OFF_SC + 8 * 56 * 4;
constexpr int OFF_RS = OFF_RED + 6144;
constexpr int OFF_ST = OFF_RS + 8 * 80 * 16;
constexpr int OFF_BAR = OFF_ST + 640;
constexpr int OFF_TL = OFF_BAR + 128;
constexpr int SMEM_BYTES = OFF_TL + 512;

__device__ __forceinline__ uint32_t ldg_nc(const void* p) { uint32_t v; asm volatile("ld.global.nc.u32 %0, [%1];" : "=r"(v) : "l"(p)); return v; }
__device__ __forceinline__ void load_raw(uint32_t* a, const bf16* __restrict__ W, int ld, int ka, int kb, int cb, int g, int t) {
    const bf16* p = W + (uint32_t)((ka + 2 * t) * ld + cb + 2 * g);
    const bf16* q = W + (uint32_t)((kb + 2 * t) * ld + cb + 2 * g);
    a[0] = ldg_nc(p); a[1] = ldg_nc(p + ld); a[2] = ldg_nc(q); a[3] = ldg_nc(q + ld);
}
__device__ __forceinline__ void fix_frag(uint32_t* a) {
    const uint32_t w0 = a[0], w1 = a[1], w2 = a[2], w3 = a[3];
    a[0] = __byte_perm(w0, w1, 0x5410); a[1] = __byte_perm(w0, w1, 0x7632);
    a[2] = __byte_perm(w2, w3, 0x5410); a[3] = __byte_perm(w2, w3, 0x7632);
}
__device__ __forceinline__ int chunk_src(int d, int kh, int n) { return (d - 8 * kh - n / 5) & 15; }
__device__ __forceinline__ int chunk_col(int d, int kh, int n) { const int s = chunk_src(d, kh, n); return 320 * (s & 1) + 40 * (s >> 1) + 8 * (n % 5); }
}

#define RSTEP 20
#define TL(i)
#define TG(i)

__device__ __forceinline__ void tma_load_2d(uint32_t dst, const CUtensorMap* map, int c0, int c1, uint32_t bar) {
    asm volatile("cp.async.bulk.tensor.2d.shared::cluster.global.mbarrier::complete_tx::bytes [%0], [%1, {%3, %4}], [%2];"
        :: "r"(dst), "l"(map), "r"(bar), "r"(c0), "r"(c1) : "memory");
}
__device__ __forceinline__ uint32_t movmatrix_t(uint32_t a) { uint32_t d; asm volatile("movmatrix.sync.aligned.m8n8.trans.b16 %0, %1;" : "=r"(d) : "r"(a)); return d; }
__device__ __forceinline__ void stg128(void* p, uint4 v) { asm volatile("st.global.v4.u32 [%0], {%1,%2,%3,%4};" :: "l"(p), "r"(v.x), "r"(v.y), "r"(v.z), "r"(v.w) : "memory"); }

__global__ void __launch_bounds__(256, 1)
r_kernel(const __grid_constant__ CUtensorMap tmK, const __grid_constant__ CUtensorMap tmV, const bf16* __restrict__ mem0, const bf16* __restrict__ Wq, const bf16* __restrict__ Wk, const bf16* __restrict__ Wv, const bf16* __restrict__ Wo, int wait_kv)
{
    using namespace rk;
    extern __shared__ __align__(1024) uint8_t smem[];
    const uint32_t sb = smem_u32(smem);
    const int tid = threadIdx.x, warp = tid >> 5, lane = tid & 31, g = lane >> 2, t = lane & 3;
    uint32_t rank, cid;
    asm volatile("mov.u32 %0, %%cluster_ctarank;" : "=r"(rank));
    asm volatile("mov.u32 %0, %%clusterid.x;" : "=r"(cid));
    const int hh = rank >> 1, j = rank & 1, h = cid * 8 + hh;
    const int kh = warp & 1, mb = warp >> 1;
    const uint32_t b_mem = sb + OFF_BAR, b_qkv = b_mem + 64, b_rs = b_mem + 72, b_kv = b_mem + 80;

    RT(64);
    asm volatile("griddepcontrol.launch_dependents;");
    const uint32_t epoch = ld_relaxed(&g_epoch);

    if (tid == 0) {
        for (int i = 0; i < 8; i++) mbar_init(b_mem + 8 * i, 1);
        mbar_init(b_qkv, 9); mbar_init(b_rs, 1); mbar_init(b_kv, 1);
        asm volatile("fence.mbarrier_init.release.cluster;" ::: "memory");
    }
    const uint32_t wsm = sb + OFF_W + (warp < 4 ? warp * 22528 : 4 * 22528 + (warp - 4) * 18432) + lane * 16;
    {
        const size_t co = (size_t)h * 128 + 64 * j;
        for (int i = tid; i < 640; i += 256) {
            asm volatile("prefetch.global.L2 [%0];" :: "l"(Wv + (size_t)i * 4096 + co));
            asm volatile("prefetch.global.L2 [%0];" :: "l"(Wo + ((size_t)h * 128 + i / 5) * 640 + 320 * j + (i % 5) * 64));
            asm volatile("prefetch.global.L2 [%0];" :: "l"(Wq + (size_t)i * 4096 + co));
            asm volatile("prefetch.global.L2 [%0];" :: "l"(Wk + (size_t)i * 4096 + co));
        }
    }
    uint32_t wq[20][4], wk[20][4];
    {
        const int cb = h * 128 + 64 * j + 16 * mb;
#pragma unroll
        for (int i = 0; i < 20; i++) load_raw(wq[i], Wv, 4096, chunk_col(rank, kh, 2 * i), chunk_col(rank, kh, 2 * i + 1), cb, g, t);
        const bf16* Woh = Wo + (size_t)h * 128 * 640;
        const int c3 = 320 * j + 16 * warp;
#pragma unroll
        for (int i = 0; i < 16; i++) load_raw(wk[i], Woh, 640, (i & 7) * 16, (i & 7) * 16 + 8, c3 + 128 * (i >> 3), g, t);
#pragma unroll
        for (int i = 0; i < 20; i++) { fix_frag(wq[i]); sts128(wsm + i * 512, make_uint4(wq[i][0], wq[i][1], wq[i][2], wq[i][3])); }
        if (warp < 4) {
#pragma unroll
            for (int i = 0; i < 8; i++) load_raw(wq[i], Woh, 640, i * 16, i * 16 + 8, c3 + 256, g, t);
        }
#pragma unroll
        for (int i = 0; i < 16; i++) { fix_frag(wk[i]); sts128(wsm + (20 + i) * 512, make_uint4(wk[i][0], wk[i][1], wk[i][2], wk[i][3])); }
#pragma unroll
        for (int i = 0; i < 20; i++) load_raw(wk[i], Wk, 4096, chunk_col(rank, kh, 2 * i), chunk_col(rank, kh, 2 * i + 1), cb, g, t);
        if (warp < 4) {
#pragma unroll
            for (int i = 0; i < 8; i++) { fix_frag(wq[i]); sts128(wsm + (36 + i) * 512, make_uint4(wq[i][0], wq[i][1], wq[i][2], wq[i][3])); }
        }
#pragma unroll
        for (int i = 0; i < 20; i++) load_raw(wq[i], Wq, 4096, chunk_col(rank, kh, 2 * i), chunk_col(rank, kh, 2 * i + 1), cb, g, t);
#pragma unroll
        for (int i = 0; i < 20; i++) { fix_frag(wk[i]); fix_frag(wq[i]); }
    }
    for (int i = tid; i < 640; i += 256) {
        int row = i / 80, c = i % 80;
        uint4 v = __ldg((const uint4*)(mem0 + row * 640 + c * 8));
        const int jj = c / 40, h5 = (c % 40) / 5;
        sts128(sb + OFF_MEM + (((int)rank - (2 * h5 + jj)) & 15) * 640 + row * 80 + (c % 5) * 16, v);
    }
    auto prefetch_kv = [&](int s) {
        if ((wait_kv & 1) && (s & 3) == 0) {
            const uint32_t* fk = &g_kvflag[(s >> 2) * 64 + h];
            int lim = 0;
            while (ld_acquire(fk) != epoch + 1) { if (++lim > SPIN_LIMIT) break; }
            while (ld_acquire(fk + 32) != epoch + 1) { if (++lim > SPIN_LIMIT) break; }
            asm volatile("fence.proxy.async.global;" ::: "memory");
        }
        mbar_expect_tx(b_kv, 16384);
        tma_load_2d(sb + OFF_KX, &tmK, h * 128, s * 32, b_kv);
        tma_load_2d(sb + OFF_KX + 4096, &tmK, h * 128 + 64, s * 32, b_kv);
        tma_load_2d(sb + OFF_VX, &tmV, h * 128, s * 32, b_kv);
        tma_load_2d(sb + OFF_VX + 4096, &tmV, h * 128 + 64, s * 32, b_kv);
    };
    __syncthreads();
    RT(65);
    __syncthreads();
    cluster_sync_all();

    const float scale = 0.08838834764831845f;
#define LAUNDER() int tid_ = threadIdx.x; asm volatile("" : "+r"(tid_)); const int warp = tid_ >> 5, lane = tid_ & 31, g = lane >> 2, t = lane & 3; (void)g; (void)t; (void)warp;
#define WSM() (sb + OFF_W + (warp < 4 ? warp * 22528 : 4 * 22528 + (warp - 4) * 18432) + lane * 16)

#pragma unroll 1
    for (int s = 0; s < 64; s++) {
        const uint32_t ph = s & 1;
        RT(s);
        {
            LAUNDER();
            TL(0);
            const int kh = warp & 1, mb = warp >> 1;
            const uint32_t wsm = WSM();
            const uint32_t mb0 = sb + OFF_MEM + kh * 5120 + (lane & 7) * 80 + (lane >> 3) * 16;
            const uint32_t mb1 = mb0 + ((lane >> 3) >= 1 ? 560 : 0), mb2 = mb0 + ((lane >> 3) >= 2 ? 560 : 0), mb3 = mb0 + ((lane >> 3) >= 3 ? 560 : 0);
            auto baddr = [&](int it) {
                const int r5 = (4 * it) % 5, c = ((4 * it) / 5) * 640 + r5 * 16;
                return (r5 <= 1 ? mb0 : (r5 == 4 ? mb1 : (r5 == 3 ? mb2 : mb3))) + c;
            };
            uint4 va[6];
            va[0] = lds128(wsm); va[1] = lds128(wsm + 512); va[2] = lds128(wsm + 1024); va[3] = lds128(wsm + 1536);
            if (s > 0) mbar_wait(b_mem, ph ^ 1);
            TL(1); TG(15);
            float aq0[4] = {0, 0, 0, 0}, aq1[4] = {0, 0, 0, 0}, ak0[4] = {0, 0, 0, 0}, ak1[4] = {0, 0, 0, 0}, av0[4] = {0, 0, 0, 0}, av1[4] = {0, 0, 0, 0};
            uint32_t b[3][4];
            ldsm_x4(b[0], baddr(0)); ldsm_x4(b[1], baddr(1));
            if (tid_ == 0) {
                mbar_expect_tx(b_qkv, 3072);
                if (s < 63) mbar_expect_tx(b_rs, 10240);
            }
#pragma unroll
            for (int i = 0; i < 10; i++) {
                if (i + 2 < 10) {
                    const int it = i + 2, sl = ((4 * it + 3) / 5) >> MEMSH, slp = ((4 * (it - 1) + 3) / 5) >> MEMSH;
                    if (sl != slp && s > 0) mbar_wait(b_mem + 8 * sl, ph ^ 1);
                    ldsm_x4(b[(i + 2) % 3], baddr(i + 2));
                    va[(2 * i + 4) % 6] = lds128(wsm + (2 * i + 4) * 512); va[(2 * i + 5) % 6] = lds128(wsm + (2 * i + 5) * 512);
                }
                const uint32_t* bb = b[i % 3];
                mma16816(aq0, wq[2 * i], bb[0], bb[1]); mma16816(ak0, wk[2 * i], bb[0], bb[1]); mma16816(av0, (uint32_t*)&va[(2 * i) % 6], bb[0], bb[1]);
                mma16816(aq1, wq[2 * i + 1], bb[2], bb[3]); mma16816(ak1, wk[2 * i + 1], bb[2], bb[3]); mma16816(av1, (uint32_t*)&va[(2 * i + 1) % 6], bb[2], bb[3]);
            }
            float snd[4], fin[4];
#pragma unroll
            for (int i = 0; i < 4; i++) { float q = aq0[i] + aq1[i], k = ak0[i] + ak1[i]; snd[i] = kh ? q : k; fin[i] = kh ? k : q; av0[i] += av1[i]; }
            sts128(sb + OFF_RED + tid_ * 16, make_uint4(__float_as_uint(snd[0]), __float_as_uint(snd[1]), __float_as_uint(snd[2]), __float_as_uint(snd[3])));
            sts64(sb + OFF_RED + 4096 + tid_ * 8, __float_as_uint(kh ? av0[0] : av0[1]), __float_as_uint(kh ? av0[2] : av0[3]));
            bar_sync(1 + mb, 64);
            uint4 r = lds128(sb + OFF_RED + (tid_ ^ 32) * 16);
            uint2 r2 = lds64(sb + OFF_RED + 4096 + (tid_ ^ 32) * 8);
            fin[0] += __uint_as_float(r.x); fin[1] += __uint_as_float(r.y); fin[2] += __uint_as_float(r.z); fin[3] += __uint_as_float(r.w);
            float f0 = (kh ? av0[1] : av0[0]) + __uint_as_float(r2.x), f1 = (kh ? av0[3] : av0[2]) + __uint_as_float(r2.y);
            TL(2);
            const uint32_t cofs = (64 * j + 16 * mb) * 2;
            const uint32_t buf = sb + (kh ? OFF_KM : OFF_Q) + cofs;
            sts32(buf + (2 * t) * T_STRIDE + g * 4, pack_bf16(fin[0], fin[2]));
            sts32(buf + (2 * t + 1) * T_STRIDE + g * 4, pack_bf16(fin[1], fin[3]));
            sts32(sb + OFF_VM + cofs + (2 * t + kh) * T_STRIDE + g * 4, pack_bf16(f0, f1));
            __syncwarp();
            if (lane < 24) {
                const uint32_t peer_off = mapa_u32(sb, rank ^ 1) - sb;
                const int row = lane < 16 ? (lane >> 1) : 2 * ((lane - 16) >> 1) + kh;
                const uint32_t a = (lane < 16 ? buf : sb + OFF_VM + cofs) + row * T_STRIDE + (lane & 1) * 16;
                uint4 v = lds128(a);
                st_async_v4(a + peer_off, v.x, v.y, v.z, v.w, b_qkv + peer_off);
                if ((kh || lane >= 16) && !(wait_kv & 8)) {
                    bf16* dst = (lane < 16 ? g_km : g_vm) + ((uint32_t)(s * 8 + row) * 4096u + h * 128 + 64 * j + 16 * mb + (lane & 1) * 8);
                    stg128(dst, v);
                }
            }
            if (lane == 0) mbar_arrive(b_qkv);
            if (s == 0 && tid_ == 224) prefetch_kv(0);
            TL(3);
        }
        if (s == 63) {
            __syncthreads();
            if (threadIdx.x == 0 && (wait_kv & 1)) red_release_inc(&g_st.d_at[15 * 32]);
            break;
        }
        uint4 wa[8];
        {
            LAUNDER();
            const uint32_t wsm = WSM();
            if (!(wait_kv & 2) || s == 0) mbar_wait(b_kv, ph);
            if (warp >= 4 && warp < 7) {
                const int kw = warp - 4;
                uint32_t ka[8][4];
                if (kw < 2) {
                    const uint32_t kaddr = sb + OFF_KX + (16 * kw + (lane & 15)) * 128;
#pragma unroll
                    for (int i = 0; i < 8; i++) ldsm_x4(ka[i], kaddr + (i >> 2) * 4096 + ((((2 * i + (lane >> 4)) & 7) ^ (lane & 7)) << 4));
                    mbar_wait(b_qkv, ph);
                } else {
                    mbar_wait(b_qkv, ph);
                    const uint32_t kaddr = sb + OFF_KM + (lane & 7) * T_STRIDE + (lane >> 4) * 16;
#pragma unroll
                    for (int i = 0; i < 8; i++) ldsm_x4(ka[i], kaddr + i * 32);
                }
                TL(5);
                const uint32_t qa = sb + OFF_Q + (lane & 7) * T_STRIDE + (lane >> 3) * 16;
                uint32_t qb[4][4];
#pragma unroll
                for (int i = 0; i < 4; i++) ldsm_x4(qb[i], qa + i * 64);
                float s0[4] = {0, 0, 0, 0}, s1[4] = {0, 0, 0, 0}, s2[4] = {0, 0, 0, 0}, s3[4] = {0, 0, 0, 0};
                mma16816(s0, ka[0], qb[0][0], qb[0][1]); mma16816(s1, ka[1], qb[0][2], qb[0][3]);
                mma16816(s2, ka[2], qb[1][0], qb[1][1]); mma16816(s3, ka[3], qb[1][2], qb[1][3]);
                mma16816(s0, ka[4], qb[2][0], qb[2][1]); mma16816(s1, ka[5], qb[2][2], qb[2][3]);
                mma16816(s2, ka[6], qb[3][0], qb[3][1]); mma16816(s3, ka[7], qb[3][2], qb[3][3]);
                const uint32_t sc = sb + OFF_SC + (16 * kw + g) * 4 + (2 * t) * 224;
                sts32(sc, __float_as_uint(bf16r(bf16r((s0[0] + s1[0]) + (s2[0] + s3[0])) * scale)));
                sts32(sc + 224, __float_as_uint(bf16r(bf16r((s0[1] + s1[1]) + (s2[1] + s3[1])) * scale)));
                if (kw < 2) {
                    sts32(sc + 32, __float_as_uint(bf16r(bf16r((s0[2] + s1[2]) + (s2[2] + s3[2])) * scale)));
                    sts32(sc + 32 + 224, __float_as_uint(bf16r(bf16r((s0[3] + s1[3]) + (s2[3] + s3[3])) * scale)));
                }
                asm volatile("bar.arrive 6, 224;" ::: "memory");
                TL(4);
#pragma unroll
                for (int i = 0; i < 8; i++) wa[i] = lds128(wsm + (20 + i) * 512);
            } else {
#pragma unroll
                for (int i = 0; i < 8; i++) wa[i] = lds128(wsm + (20 + i) * 512);
                if (warp < 4) {
                    mbar_wait(b_qkv, ph);
                    uint32_t a0[2][4], a1[2][4], a2[2][4];
#pragma unroll
                    for (int u = 0; u < 2; u++) {
                        const int et = warp + 4 * u;
                        const uint32_t vx = sb + OFF_VX + u * 4096 + ((lane >> 4) * 8 + (lane & 7)) * 128 + ((((2 * warp + ((lane >> 3) & 1)) & 7) ^ (lane & 7)) << 4);
                        ldsm_x4_t(a0[u], vx); ldsm_x4_t(a1[u], vx + 16 * 128);
                        ldsm_x4_t(a2[u], sb + OFF_VM + (lane & 7) * T_STRIDE + (16 * et + ((lane >> 3) & 1) * 8) * 2);
                    }
                    bar_sync(6, 224);
                    TL(6);
                    float x[10];
#pragma unroll
                    for (int i = 0; i < 5; i++) { uint2 v = lds64(sb + OFF_SC + g * 224 + (8 * i + 2 * t) * 4); x[2 * i] = __uint_as_float(v.x); x[2 * i + 1] = __uint_as_float(v.y); }
                    float m = fmaxf(fmaxf(fmaxf(x[0], x[1]), fmaxf(x[2], x[3])), fmaxf(fmaxf(x[4], x[5]), fmaxf(x[6], x[7])));
                    m = fmaxf(m, fmaxf(x[8], x[9]));
                    m = fmaxf(m, __shfl_xor_sync(0xffffffff, m, 1)); m = fmaxf(m, __shfl_xor_sync(0xffffffff, m, 2));
                    float sum0 = 0, sum1 = 0;
#pragma unroll
                    for (int i = 0; i < 5; i++) { x[2 * i] = __expf(x[2 * i] - m); sum0 += x[2 * i]; x[2 * i + 1] = __expf(x[2 * i + 1] - m); sum1 += x[2 * i + 1]; }
                    float sum = sum0 + sum1;
                    sum += __shfl_xor_sync(0xffffffff, sum, 1); sum += __shfl_xor_sync(0xffffffff, sum, 2);
                    float inv = __fdividef(1.0f, sum);
                    if (inv == 123.f) TL(14);
                    TL(4);
                    uint32_t pb[5];
#pragma unroll
                    for (int i = 0; i < 5; i++) pb[i] = pack_bf16(x[2 * i] * inv, x[2 * i + 1] * inv);
#pragma unroll
                    for (int u = 0; u < 2; u++) {
                        float o0[4] = {0, 0, 0, 0}, o1[4] = {0, 0, 0, 0}, o2[4] = {0, 0, 0, 0};
                        mma16816(o0, a0[u], pb[0], pb[1]); mma16816(o1, a1[u], pb[2], pb[3]); mma16816(o2, a2[u], pb[4], 0u);
                        const uint32_t lo = movmatrix_t(pack_bf16((o0[0] + o1[0]) + o2[0], (o0[1] + o1[1]) + o2[1]));
                        const uint32_t hi = movmatrix_t(pack_bf16((o0[2] + o1[2]) + o2[2], (o0[3] + o1[3]) + o2[3]));
                        const uint32_t oa = sb + OFF_O + g * T_STRIDE + (16 * (warp + 4 * u) + 2 * t) * 2;
                        sts32(oa, lo); sts32(oa + 16, hi);
                    }
                    TL(5);
                } else {
                    if (lane < (8 >> MEMSH)) mbar_expect_tx(b_mem + 8 * lane, 1280 << MEMSH);
                }
            }
        }
        __syncthreads();
        {
            LAUNDER();
            TL(7);
            const uint32_t wsm = WSM();
            uint32_t ob[16];
            const uint32_t oa = sb + OFF_O + (lane & 7) * T_STRIDE + (lane >> 3) * 16;
#pragma unroll
            for (int i = 0; i < 4; i++) ldsm_x4(ob + 4 * i, oa + i * 64);
            const uint32_t rs_base = OFF_RS + hh * 1280 + t * 16;
            const int ntile = warp < 4 ? 3 : 2;
#pragma unroll 1
            for (int tl = 0; tl < ntile; tl++) {
                float d0[4] = {0, 0, 0, 0}, d1[4] = {0, 0, 0, 0}, d2[4] = {0, 0, 0, 0}, d3[4] = {0, 0, 0, 0};
                const bool more = tl + 1 < ntile;
                const uint32_t nx = wsm + (28 + 8 * tl) * 512;
                mma16816(d0, (uint32_t*)&wa[0], ob[0], ob[1]);   if (more) wa[0] = lds128(nx);
                mma16816(d1, (uint32_t*)&wa[1], ob[2], ob[3]);   if (more) wa[1] = lds128(nx + 512);
                mma16816(d2, (uint32_t*)&wa[2], ob[4], ob[5]);   if (more) wa[2] = lds128(nx + 1024);
                mma16816(d3, (uint32_t*)&wa[3], ob[6], ob[7]);   if (more) wa[3] = lds128(nx + 1536);
                mma16816(d0, (uint32_t*)&wa[4], ob[8], ob[9]);   if (more) wa[4] = lds128(nx + 2048);
                mma16816(d1, (uint32_t*)&wa[5], ob[10], ob[11]); if (more) wa[5] = lds128(nx + 2560);
                mma16816(d2, (uint32_t*)&wa[6], ob[12], ob[13]); if (more) wa[6] = lds128(nx + 3072);
                mma16816(d3, (uint32_t*)&wa[7], ob[14], ob[15]); if (more) wa[7] = lds128(nx + 3584);
                const int col = 16 * (warp + 8 * tl) + 2 * g; const int own = col / 40; const int cp = (col - own * 40) >> 1;
                const uint32_t dbase = mapa_u32(sb, 2 * own + j);
                st_async_v4(dbase + rs_base + cp * 64, __float_as_uint((d0[0] + d1[0]) + (d2[0] + d3[0])), __float_as_uint((d0[1] + d1[1]) + (d2[1] + d3[1])),
                            __float_as_uint((d0[2] + d1[2]) + (d2[2] + d3[2])), __float_as_uint((d0[3] + d1[3]) + (d2[3] + d3[3])), dbase + OFF_BAR + 72);
            }
            TL(8);
        }
        {
            LAUNDER();
            if (warp >= 5) {
                const int x = tid_ - 160;
                const int ot = x < 80 ? x : 79;
                const uint32_t gs = epoch * 64 + s; const uint32_t tag = (gs + 1) & 15u; const int slot = gs & 1;
                uint4* gp = &g_gx[slot][0][rank][ot];
                mbar_wait(b_rs, ph);
                TL(9); TG(12);
                uint4 u[8];
#pragma unroll
                for (int q = 0; q < 8; q++) u[q] = lds128(sb + OFF_RS + q * 1280 + ot * 16);
                float4 a;
                a.x = ((__uint_as_float(u[0].x) + __uint_as_float(u[1].x)) + (__uint_as_float(u[2].x) + __uint_as_float(u[3].x))) + ((__uint_as_float(u[4].x) + __uint_as_float(u[5].x)) + (__uint_as_float(u[6].x) + __uint_as_float(u[7].x)));
                a.y = ((__uint_as_float(u[0].y) + __uint_as_float(u[1].y)) + (__uint_as_float(u[2].y) + __uint_as_float(u[3].y))) + ((__uint_as_float(u[4].y) + __uint_as_float(u[5].y)) + (__uint_as_float(u[6].y) + __uint_as_float(u[7].y)));
                a.z = ((__uint_as_float(u[0].z) + __uint_as_float(u[1].z)) + (__uint_as_float(u[2].z) + __uint_as_float(u[3].z))) + ((__uint_as_float(u[4].z) + __uint_as_float(u[5].z)) + (__uint_as_float(u[6].z) + __uint_as_float(u[7].z)));
                a.w = ((__uint_as_float(u[0].w) + __uint_as_float(u[1].w)) + (__uint_as_float(u[2].w) + __uint_as_float(u[3].w))) + ((__uint_as_float(u[4].w) + __uint_as_float(u[5].w)) + (__uint_as_float(u[6].w) + __uint_as_float(u[7].w)));
                uint4 mine = make_uint4((__float_as_uint(a.x) & ~15u) | tag, (__float_as_uint(a.y) & ~15u) | tag, (__float_as_uint(a.z) & ~15u) | tag, (__float_as_uint(a.w) & ~15u) | tag);
                if (x < 80) st_relaxed_v4(gp + cid * 1280, mine);
                { uint32_t c0, c1; asm volatile("mov.u32 %0, %%clock;" : "=r"(c0) :: "memory"); do { asm volatile("mov.u32 %0, %%clock;" : "=r"(c1) :: "memory"); } while (c1 - c0 < POLL_DELAY); }
                uint4 v[3];
                const uint4* rp0 = gp + (cid ^ 1) * 1280; const uint4* rp1 = gp + (cid ^ 2) * 1280; const uint4* rp2 = gp + (cid ^ 3) * 1280;
                int lim = 0;
                while (true) {
                    v[0] = ld_relaxed_v4(rp0); v[1] = ld_relaxed_v4(rp1); v[2] = ld_relaxed_v4(rp2);
                    uint32_t bad = 0;
#pragma unroll
                    for (int c = 0; c < 3; c++) bad |= (v[c].x ^ tag) | (v[c].y ^ tag) | (v[c].z ^ tag) | (v[c].w ^ tag);
                    if ((bad & 15u) == 0) break;
                    if (++lim > SPIN_LIMIT) break;
                }
                float f0 = (__uint_as_float(mine.x) + __uint_as_float(v[0].x)) + (__uint_as_float(v[1].x) + __uint_as_float(v[2].x));
                float f1 = (__uint_as_float(mine.y) + __uint_as_float(v[0].y)) + (__uint_as_float(v[1].y) + __uint_as_float(v[2].y));
                float f2 = (__uint_as_float(mine.z) + __uint_as_float(v[0].z)) + (__uint_as_float(v[1].z) + __uint_as_float(v[2].z));
                float f3 = (__uint_as_float(mine.w) + __uint_as_float(v[0].w)) + (__uint_as_float(v[1].w) + __uint_as_float(v[2].w));
                const int cp = ot >> 2, tt = ot & 3;
                sts32(sb + OFF_ST + (2 * tt) * 80 + cp * 4, pack_bf16(f0, f2));
                sts32(sb + OFF_ST + (2 * tt + 1) * 80 + cp * 4, pack_bf16(f1, f3));
                TL(10); TG(13);
                bar_sync(5, 128);
                if (x < 80) {
                    const int c = x % 40, d0 = x / 40;
                    uint4 w = lds128(sb + OFF_ST + c * 16);
                    const uint32_t off = OFF_MEM + d0 * 5120 + c * 16;
#pragma unroll
                    for (int i = 0; i < 8; i++) {
                        const uint32_t rb = mapa_u32(sb, (d0 * 8 + i + rank) & 15);
                        st_async_v4(rb + off + i * 640, w.x, w.y, w.z, w.w, rb + OFF_BAR + 8 * (i >> MEMSH));
                    }
                }
            } else if (warp == 4) {
                if (lane == 0 && (s & 3) == 3 && (wait_kv & 1)) red_release_inc(&g_st.d_at[(s >> 2) * 32]);
                __syncwarp();
            } else if (warp == 3) {
                bar_sync(5, 128);
                if (lane == 0 && s < 62 && !(wait_kv & 2)) prefetch_kv(s + 1);
                __syncwarp();
            }
            TL(11);
        }
    }
    cluster_sync_all();
}

__device__ float g_mod[3840];
__device__ bf16 g_h[2048 * 640];
__device__ bf16 g_q[2048 * 4096];
__device__ bf16 g_o[2048 * 4096];
__device__ bf16 g_x1[2048 * 640];
__device__ bf16 g_h2[2048 * 640];
__device__ bf16 g_act[2048 * 1728];
__device__ float g_slab[2048 * 640];

namespace gk {
#define NSTAGES 3
constexpr int STAGES = NSTAGES;
constexpr int STAGE_BYTES = 49152;
constexpr int OFF_SCR = STAGES * STAGE_BYTES;
constexpr int OFF_BAR = OFF_SCR + 32768;
constexpr int SMEM_BYTES = OFF_BAR + 256 + 2048;
#define PRECLAIM_MOD 2
#define PRECLAIM_RB 15
#define URGENT_LEAD 1
#define LOW_LEAD 16
constexpr int N_MOD = 60, N_L1 = 48 + 13 * 8, N_KV = 32, N_Q = 16;
constexpr int I_L1 = N_MOD, I_W = I_L1 + N_L1;
constexpr int N_LOW = I_W + 16 * (N_KV + N_Q) + 32;
constexpr int NFINE = 16 - FINE_RB;
constexpr int N_HIGH = 16 * (32 + 16 + 16) + (16 - NFINE) * (3 * WO_COARSE + 14 + 9) + NFINE * (5 * WO_FINE + 27 + 45);
struct Item { int type, rb, nt, ks; };
__host__ __device__ inline Item decode_low(int t) {
    Item it; it.rb = 0; it.nt = 0; it.ks = 0;
    if (t < I_L1) { it.type = T_MOD; it.nt = t; return it; }
    if (t < I_L1 + 16) { it.type = T_L1; it.rb = 0; it.nt = t - I_L1; return it; }
    if (t < I_L1 + 80) { it.type = T_KV; it.rb = 0; it.nt = t - I_L1 - 16; it.ks = 1; return it; }
    if (t < I_L1 + 112) { it.type = T_L1; it.rb = (t - I_L1 - 64) >> 4; it.nt = (t - I_L1 - 64) & 15; return it; }
    if (t < I_L1 + 144) { it.type = T_KV; it.rb = 1; it.nt = t - I_L1 - 112; return it; }
    if (t < I_W + 96) { it.type = T_L1; it.rb = 3 + ((t - I_L1 - 144) >> 3); it.nt = (t - I_L1 - 144) & 7; return it; }
    t -= I_W + 96;
    if (t < 14 * 48) { const int w = t / 48; t -= w * 48; if (t < 16) { it.type = T_Q; it.rb = w; it.nt = t; } else { it.type = T_KV; it.rb = w + 2; it.nt = t - 16; } return it; }
    t -= 14 * 48;
    it.type = T_Q; it.rb = 14 + (t >> 4); it.nt = t & 15; return it;
}
__device__ __forceinline__ bool is_wide(const Item& it) {
    if (it.type == T_KV || it.type == T_Q) return it.ks == 0;
    if (it.type == T_F1) return !fine(it.rb);
    if (it.type == T_WO || it.type == T_F2) return !fine(it.rb) && it.nt < 2;
    return false;
}
__device__ __forceinline__ int red_col(const Item& it) { return fine(it.rb) ? it.nt * 128 : it.nt * 256; }
__device__ __forceinline__ int pack_item(const Item& it) { return it.type | (it.rb << 4) | (it.nt << 8) | (it.ks << 16); }
__device__ __forceinline__ Item unpack_item(int v) { Item it; it.type = v & 15; it.rb = (v >> 4) & 15; it.nt = (v >> 8) & 255; it.ks = (v >> 16) & 255; return it; }
}

struct GParams {
    CUtensorMap tA_h, tA_o, tA_h2, tA_act, tB_q, tB_k, tB_v, tB_o, tB_g, tB_u, tB_d, tS_q, tS_k, tS_v, tS_act, tS_o, tL_q, tL_k, tL_v, tL_km, tL_vm, tR_acc;
};

__device__ __forceinline__ void wait_ge(const uint32_t* p, uint32_t target) {
    int lim = 0;
    while ((int32_t)(ld_acquire(p) - target) < 0) { __nanosleep(64); if (++lim > SPIN_LIMIT) break; }
}
__device__ __forceinline__ void red_add_relaxed(uint32_t* p, uint32_t v) { asm volatile("red.relaxed.gpu.global.add.u32 [%0], %1;" :: "l"(p), "r"(v) : "memory"); }
__device__ __forceinline__ void st_relaxed_u32(uint32_t* p, uint32_t v) { asm volatile("st.relaxed.gpu.global.u32 [%0], %1;" :: "l"(p), "r"(v) : "memory"); }
__device__ __forceinline__ void red_add_release(uint32_t* p, uint32_t v) { asm volatile("red.release.gpu.global.add.u32 [%0], %1;" :: "l"(p), "r"(v) : "memory"); }

__device__ __forceinline__ void wgmma_fence() { asm volatile("wgmma.fence.sync.aligned;" ::: "memory"); }
__device__ __forceinline__ void wgmma_commit() { asm volatile("wgmma.commit_group.sync.aligned;" ::: "memory"); }
template<int N> __device__ __forceinline__ void wgmma_wait() { asm volatile("wgmma.wait_group.sync.aligned %0;" :: "n"(N) : "memory"); }

template<int N> __device__ __forceinline__ void fence_acc(float* d) {
#pragma unroll
    for (int i = 0; i < N; i++) asm volatile("" : "+f"(d[i]) :: "memory");
}
#define ACC8(b) "+f"(d[b]), "+f"(d[b+1]), "+f"(d[b+2]), "+f"(d[b+3]), "+f"(d[b+4]), "+f"(d[b+5]), "+f"(d[b+6]), "+f"(d[b+7])
#define ACC32(b) ACC8(b), ACC8(b+8), ACC8(b+16), ACC8(b+24)
__device__ __forceinline__ void wgmma_n128(float* d, uint64_t da, uint64_t db, int scale_d) {
    asm volatile("{ .reg .pred p; setp.ne.b32 p, %66, 0;\n"
        "wgmma.mma_async.sync.aligned.m64n128k16.f32.bf16.bf16 {%0,%1,%2,%3,%4,%5,%6,%7,%8,%9,%10,%11,%12,%13,%14,%15,%16,%17,%18,%19,%20,%21,%22,%23,%24,%25,%26,%27,%28,%29,%30,%31,"
        "%32,%33,%34,%35,%36,%37,%38,%39,%40,%41,%42,%43,%44,%45,%46,%47,%48,%49,%50,%51,%52,%53,%54,%55,%56,%57,%58,%59,%60,%61,%62,%63}, %64, %65, p, 1, 1, 0, 1; }"
        : ACC32(0), ACC32(32) : "l"(da), "l"(db), "r"(scale_d));
}
__device__ __forceinline__ void wgmma_n256(float* d, uint64_t da, uint64_t db, int scale_d) {
    asm volatile("{ .reg .pred p; setp.ne.b32 p, %130, 0;\n"
        "wgmma.mma_async.sync.aligned.m64n256k16.f32.bf16.bf16 {%0,%1,%2,%3,%4,%5,%6,%7,%8,%9,%10,%11,%12,%13,%14,%15,%16,%17,%18,%19,%20,%21,%22,%23,%24,%25,%26,%27,%28,%29,%30,%31,"
        "%32,%33,%34,%35,%36,%37,%38,%39,%40,%41,%42,%43,%44,%45,%46,%47,%48,%49,%50,%51,%52,%53,%54,%55,%56,%57,%58,%59,%60,%61,%62,%63,"
        "%64,%65,%66,%67,%68,%69,%70,%71,%72,%73,%74,%75,%76,%77,%78,%79,%80,%81,%82,%83,%84,%85,%86,%87,%88,%89,%90,%91,%92,%93,%94,%95,"
        "%96,%97,%98,%99,%100,%101,%102,%103,%104,%105,%106,%107,%108,%109,%110,%111,%112,%113,%114,%115,%116,%117,%118,%119,%120,%121,%122,%123,%124,%125,%126,%127}, %128, %129, p, 1, 1, 0, 1; }"
        : ACC32(0), ACC32(32), ACC32(64), ACC32(96) : "l"(da), "l"(db), "r"(scale_d));
}
__device__ __forceinline__ uint64_t make_desc(uint32_t addr, uint32_t lbo, uint32_t sbo) {
    return (uint64_t)((addr & 0x3FFFF) >> 4) | ((uint64_t)(lbo >> 4) << 16) | ((uint64_t)(sbo >> 4) << 32) | ((uint64_t)1 << 62);
}

__device__ __forceinline__ float div_fix(float a, float b, float rb) { float q = a * rb; float r = fmaf(-q, b, a); return fmaf(r, rb, q); }
__device__ __forceinline__ void row_item(int mode, uint32_t sx, uint32_t sa, uint32_t sp, uint32_t bar_empty, float* __restrict__ acc, bf16* __restrict__ yout, bf16* __restrict__ out, int lane) {
    float x[20];
#pragma unroll
    for (int i = 0; i < 5; i++) {
        const uint2 v = lds64(sx + i * 256 + lane * 8);
        x[4 * i] = __uint_as_float(v.x << 16); x[4 * i + 1] = __uint_as_float(v.x & 0xffff0000u);
        x[4 * i + 2] = __uint_as_float(v.y << 16); x[4 * i + 3] = __uint_as_float(v.y & 0xffff0000u);
    }
    if (mode) {
#pragma unroll
        for (int i = 0; i < 5; i++) {
            const uint4 a = lds128(sa + i * 512 + lane * 16), gt = lds128(sp + i * 512 + lane * 16);
            x[4 * i] = bf16r(x[4 * i] + bf16r(__uint_as_float(gt.x) * bf16r(__uint_as_float(a.x)))); x[4 * i + 1] = bf16r(x[4 * i + 1] + bf16r(__uint_as_float(gt.y) * bf16r(__uint_as_float(a.y))));
            x[4 * i + 2] = bf16r(x[4 * i + 2] + bf16r(__uint_as_float(gt.z) * bf16r(__uint_as_float(a.z)))); x[4 * i + 3] = bf16r(x[4 * i + 3] + bf16r(__uint_as_float(gt.w) * bf16r(__uint_as_float(a.w))));
            *(uint2*)(yout + i * 128 + lane * 4) = make_uint2(pack_bf16(x[4 * i], x[4 * i + 1]), pack_bf16(x[4 * i + 2], x[4 * i + 3]));
        }
        sp += 2560;
    }
    if (mode != 2) {
#pragma unroll
        for (int i = 0; i < 5; i++) *(float4*)(acc + i * 128 + lane * 4) = make_float4(0.f, 0.f, 0.f, 0.f);
    }
    if (mode != 2) {
        float s = 0;
#pragma unroll
        for (int i = 0; i < 20; i++) s += x[i];
#pragma unroll
        for (int o = 16; o; o >>= 1) s += __shfl_xor_sync(0xffffffff, s, o);
        const float mean = s * (1.0f / 640.0f);
        float q = 0;
#pragma unroll
        for (int i = 0; i < 20; i++) { float d = x[i] - mean; q += d * d; }
#pragma unroll
        for (int o = 16; o; o >>= 1) q += __shfl_xor_sync(0xffffffff, q, o);
        const float m16 = bf16r(mean);
        const float sd = bf16r(sqrtf(bf16r(bf16r(q * (1.0f / 640.0f)) + 1e-5f)));
        const float rs = __frcp_rn(sd);
#pragma unroll
        for (int i = 0; i < 5; i++) {
            const uint4 sh = lds128(sp + i * 512 + lane * 16), sc = lds128(sp + 2560 + i * 512 + lane * 16);
            float y0 = bf16r(bf16r(div_fix(bf16r(x[4 * i] - m16), sd, rs)) * bf16r(1.0f + __uint_as_float(sc.x))) + __uint_as_float(sh.x);
            float y1 = bf16r(bf16r(div_fix(bf16r(x[4 * i + 1] - m16), sd, rs)) * bf16r(1.0f + __uint_as_float(sc.y))) + __uint_as_float(sh.y);
            float y2 = bf16r(bf16r(div_fix(bf16r(x[4 * i + 2] - m16), sd, rs)) * bf16r(1.0f + __uint_as_float(sc.z))) + __uint_as_float(sh.z);
            float y3 = bf16r(bf16r(div_fix(bf16r(x[4 * i + 3] - m16), sd, rs)) * bf16r(1.0f + __uint_as_float(sc.w))) + __uint_as_float(sh.w);
            *(uint2*)(out + i * 128 + lane * 4) = make_uint2(pack_bf16(y0, y1), pack_bf16(y2, y3));
        }
    }
    __syncwarp();
    if (lane == 0) mbar_arrive(bar_empty);
}

__device__ __forceinline__ float gelu_tanh(float x) {
    float u2 = x * fmaf(x * x, 2.0f * 0.7978845608028654f * 0.044715f * 1.4426950408889634f, 2.0f * 0.7978845608028654f * 1.4426950408889634f);
    float e; asm("ex2.approx.ftz.f32 %0, %1;" : "=f"(e) : "f"(-u2));
    return __fdividef(x, 1.0f + e);
}
__device__ __forceinline__ uint4 ldg128(const void* p) { uint4 v; asm volatile("ld.global.v4.u32 {%0,%1,%2,%3}, [%4];" : "=r"(v.x), "=r"(v.y), "=r"(v.z), "=r"(v.w) : "l"(p) : "memory"); return v; }
__device__ __forceinline__ float4 ldcg_f4(const float* p) { float4 v; asm volatile("ld.global.cg.v4.f32 {%0,%1,%2,%3}, [%4];" : "=f"(v.x), "=f"(v.y), "=f"(v.z), "=f"(v.w) : "l"(p) : "memory"); return v; }
__device__ __forceinline__ uint4 ldcg128(const void* p) { uint4 v; asm volatile("ld.global.cg.v4.u32 {%0,%1,%2,%3}, [%4];" : "=r"(v.x), "=r"(v.y), "=r"(v.z), "=r"(v.w) : "l"(p) : "memory"); return v; }

__device__ __forceinline__ void attn_scores(uint32_t sq, uint32_t sk, uint32_t skm, int sg, int mt, int lane, uint32_t (&p)[6][2]) {
    const int g = lane >> 2, t = lane & 3, l7 = lane & 7;
    float s[5][4];
#pragma unroll
    for (int kt = 0; kt < 5; kt++) s[kt][0] = s[kt][1] = s[kt][2] = s[kt][3] = 0.f;
    const uint32_t qrow = sq + (sg * 32 + mt * 16 + (lane & 15)) * 128;
    const uint32_t krow = sk + (sg * 32 + l7) * 128, kmrow = skm + (sg * 8 + l7) * 128;
#pragma unroll
    for (int c = 0; c < 4; c++) {
        uint32_t a0[4], a1[4];
        ldsm_x4(a0, qrow + (c >> 1) * 16384 + ((((4 * c + (lane >> 4)) & 7) ^ l7) << 4));
        ldsm_x4(a1, qrow + (c >> 1) * 16384 + ((((4 * c + 2 + (lane >> 4)) & 7) ^ l7) << 4));
        const uint32_t sw = (((4 * c + (lane >> 3)) & 7) ^ l7) << 4;
#pragma unroll
        for (int kt = 0; kt < 5; kt++) {
            uint32_t b[4];
            ldsm_x4(b, kt == 0 ? kmrow + (c >> 1) * 4096 + sw : krow + (kt - 1) * 1024 + (c >> 1) * 16384 + sw);
            mma16816(s[kt], a0, b[0], b[1]); mma16816(s[kt], a1, b[2], b[3]);
        }
    }
    const float scale = 0.08838834764831845f;
    const int r0 = mt * 16 + g, r1 = r0 + 8;
    float m0 = -INFINITY, m1 = -INFINITY;
#pragma unroll
    for (int kt = 0; kt < 5; kt++) {
#pragma unroll
        for (int i = 0; i < 4; i++) {
            float v = bf16r(bf16r(s[kt][i]) * scale);
            if (kt > 0) { int key = (kt - 1) * 8 + 2 * t + (i & 1); if (key > (i < 2 ? r0 : r1)) v = -1.0e9f; }
            s[kt][i] = v;
            if (i < 2) m0 = fmaxf(m0, v); else m1 = fmaxf(m1, v);
        }
    }
    m0 = fmaxf(m0, __shfl_xor_sync(0xffffffff, m0, 1)); m0 = fmaxf(m0, __shfl_xor_sync(0xffffffff, m0, 2));
    m1 = fmaxf(m1, __shfl_xor_sync(0xffffffff, m1, 1)); m1 = fmaxf(m1, __shfl_xor_sync(0xffffffff, m1, 2));
    float l0 = 0, l1 = 0;
#pragma unroll
    for (int kt = 0; kt < 5; kt++) {
        s[kt][0] = __expf(s[kt][0] - m0); s[kt][1] = __expf(s[kt][1] - m0); l0 += s[kt][0] + s[kt][1];
        s[kt][2] = __expf(s[kt][2] - m1); s[kt][3] = __expf(s[kt][3] - m1); l1 += s[kt][2] + s[kt][3];
    }
    l0 += __shfl_xor_sync(0xffffffff, l0, 1); l0 += __shfl_xor_sync(0xffffffff, l0, 2);
    l1 += __shfl_xor_sync(0xffffffff, l1, 1); l1 += __shfl_xor_sync(0xffffffff, l1, 2);
    const float i0 = __fdividef(1.0f, l0), i1 = __fdividef(1.0f, l1);
#pragma unroll
    for (int kt = 0; kt < 5; kt++) { p[kt][0] = pack_bf16(s[kt][0] * i0, s[kt][1] * i0); p[kt][1] = pack_bf16(s[kt][2] * i1, s[kt][3] * i1); }
    p[5][0] = p[5][1] = 0;
}
__device__ __forceinline__ void attn_pv(uint32_t sv, uint32_t svm, int sg, int lane, const uint32_t (&p)[6][2], float* d) {
    const int l7 = lane & 7, hi = (lane >> 3) & 1, ec = lane >> 4;
    const uint32_t r0 = hi ? sv + (sg * 32 + l7) * 128 : svm + (sg * 8 + l7) * 128;
    const uint32_t sub0 = hi ? 16384 : 4096;
    const uint32_t r1 = sv + (sg * 32 + 8 + hi * 8 + l7) * 128;
    const uint32_t r2 = sv + (sg * 32 + 24 + l7) * 128;
#pragma unroll
    for (int i = 0; i < 8; i++) {
        const uint32_t sw = (((2 * i + ec) & 7) ^ l7) << 4;
        uint32_t b0[4], b1[4], b2[4];
        ldsm_x4_t(b0, r0 + (i >> 2) * sub0 + sw); ldsm_x4_t(b1, r1 + (i >> 2) * 16384 + sw); ldsm_x4_t(b2, r2 + (i >> 2) * 16384 + sw);
        float* o0 = d + 8 * i; float* o1 = o0 + 4;
        o0[0] = o0[1] = o0[2] = o0[3] = o1[0] = o1[1] = o1[2] = o1[3] = 0.f;
        { uint32_t a[4] = {p[0][0], p[0][1], p[1][0], p[1][1]}; mma16816(o0, a, b0[0], b0[1]); mma16816(o1, a, b0[2], b0[3]); }
        { uint32_t a[4] = {p[2][0], p[2][1], p[3][0], p[3][1]}; mma16816(o0, a, b1[0], b1[1]); mma16816(o1, a, b1[2], b1[3]); }
        { uint32_t a[4] = {p[4][0], p[4][1], p[5][0], p[5][1]}; mma16816(o0, a, b2[0], b2[1]); mma16816(o1, a, b2[2], b2[3]); }
    }
}
__device__ __forceinline__ void bulk_load(uint32_t dst, const void* src, uint32_t bytes, uint32_t bar) {
    asm volatile("cp.async.bulk.shared::cluster.global.mbarrier::complete_tx::bytes [%0], [%1], %2, [%3];" :: "r"(dst), "l"(src), "r"(bytes), "r"(bar) : "memory");
}

__device__ __forceinline__ void stsm_x4(uint32_t addr, uint32_t a, uint32_t b, uint32_t c, uint32_t d) {
    asm volatile("stmatrix.sync.aligned.m8n8.x4.shared.b16 [%0], {%1,%2,%3,%4};" :: "r"(addr), "r"(a), "r"(b), "r"(c), "r"(d) : "memory");
}
__device__ __forceinline__ void tma_reduce_2d(const CUtensorMap* map, uint32_t src, int c0, int c1) {
    asm volatile("cp.reduce.async.bulk.tensor.2d.global.shared::cta.add.tile.bulk_group [%0, {%2, %3}], [%1];" :: "l"(map), "r"(src), "r"(c0), "r"(c1) : "memory");
}
__device__ __forceinline__ void tma_store_2d(const CUtensorMap* map, uint32_t src, int c0, int c1) {
    asm volatile("cp.async.bulk.tensor.2d.global.shared::cta.bulk_group [%0, {%2, %3}], [%1];" :: "l"(map), "r"(src), "r"(c0), "r"(c1) : "memory");
}

__global__ void __launch_bounds__(384, 1)
g_kernel(const __grid_constant__ GParams P, const bf16* __restrict__ x, const bf16* __restrict__ cvec, const bf16* __restrict__ w_mod, bf16* __restrict__ out, int nctas, int wait_r)
{
    using namespace gk;
    extern __shared__ __align__(1024) uint8_t smem[];
    const uint32_t sb = smem_u32(smem);
    const int tid = threadIdx.x, warp = tid >> 5, lane = tid & 31;
    const uint32_t b_full = sb + OFF_BAR, b_empty = b_full + 8 * STAGES, b_wfull = b_empty + 8 * STAGES, b_wempty = b_wfull + 16;
    const uint32_t b_cdone = b_wempty + 16, b_sfree = b_cdone + 16;
    volatile int* wslot = (volatile int*)(smem + OFF_BAR + 192);
    const uint32_t epoch = ld_relaxed(&g_epoch);
    const uint32_t e1 = epoch + 1;
    if (tid == 0) {
        wslot[4] = 0;
        for (int i = 0; i < STAGES; i++) { mbar_init(b_full + 8 * i, 1); mbar_init(b_empty + 8 * i, 8); }
        for (int i = 0; i < 2; i++) { mbar_init(b_wfull + 8 * i, 1); mbar_init(b_wempty + 8 * i, 9); mbar_init(b_cdone + 8 * i, 4); mbar_init(b_sfree + 8 * i, 1); }
        asm volatile("fence.mbarrier_init.release.cluster;" ::: "memory");
    }
    __syncthreads();

    if (warp < 4) {
        asm volatile("setmaxnreg.dec.sync.aligned.u32 40;");
        if (warp == 0 && lane == 0) {
            uint32_t stage = 0, sph = 1, wi = 0, wph = 1;
            bool low_left = true;
            uint32_t lx0 = 0, lx1 = 0, lx2 = 0;
            int lim = 0, issued = 0, nat = 0;
            volatile int* fin_cnt = wslot + 4;
            while (true) {
                Item it; it.type = T_END; it.rb = it.nt = it.ks = 0;
                int tk = 0; (void)tk;
                while (true) {
                    uint4 rd = ld_relaxed_v4(&g_st.ready[0]); const uint4 ex = ld_relaxed_v4(&g_st.exh[0]);
                    const uint32_t dat = nat < 16 ? ld_relaxed(&g_st.d_at[nat * 32]) : 0;
                    if (nat < 16 && dat == e1 * ((wait_r ? 112u : 48u) + (nat == 0 ? 32u : 0u))) { if (!(rd.x >> nat & 1)) publish_group(T_AT, nat, e1); nat++; }
                    { const int na = __popc(rd.x & 0xffffu); if (na > nat) nat = na; }
                    rd.x |= (1u << nat) - 1;
                    lx0 |= ex.x; lx1 |= ex.y; lx2 |= ex.z;
                    uint32_t a0 = rd.x & ~lx0, a1 = rd.y & ~lx1, a2 = rd.z & ~lx2;
                    bool got = false;
                    if (low_left && (int)rd.w < I_W + 96 + (nat + URGENT_LEAD) * 48 && (int)rd.w < N_LOW) a0 = a1 = a2 = 0;
                    if ((a0 | a1 | a2) && (rd.x >> (FINE_RB - 1) & 1) && *fin_cnt != issued) {
                        int l2 = 0; while (*fin_cnt != issued && ++l2 < SPIN_LIMIT) { }
                        continue;
                    }
                    while (a0 | a1 | a2) {
                        const int gi = a0 ? __ffs(a0) - 1 : (a1 ? 32 + __ffs(a1) - 1 : 64 + __ffs(a2) - 1);
                        const int ty = T_AT + (gi >> 4), rb = gi & 15, n = group_size(ty, rb);
                        const int i = (int)atomicAdd(&g_st.cnt[gi * 8], 1u);
                        const uint32_t bit = 1u << (gi & 31);
                        if (i >= n - 1) {
                            if (gi < 32) { lx0 |= bit; a0 &= ~bit; } else if (gi < 64) { lx1 |= bit; a1 &= ~bit; } else { lx2 |= bit; a2 &= ~bit; }
                            if (i == n - 1) asm volatile("red.relaxed.gpu.global.or.b32 [%0], %1;" :: "l"(&g_st.exh[gi >> 5]), "r"(bit) : "memory");
                        }
                        if (i < n) {
                            it.type = ty; it.rb = rb; it.nt = i;
                            if (ty == T_WO || ty == T_F2) { const int nn = n_nt(rb); it.ks = i / nn; it.nt = i - it.ks * nn; }
                            asm volatile("fence.acq_rel.gpu;" ::: "memory");
                            got = true; break;
                        }
                    }
                    if (got) {
                        break;
                    }
                    if (low_left && (int)rd.w < I_W + 96 + (nat + LOW_LEAD) * 48) {
                        const int lt = (int)atomicAdd(&g_st.lq_claim, 1u);
                        if (lt < N_LOW) {
                            it = decode_low(lt);
                            if (it.type == T_L1) wait_ge(&g_st.c_mod_a, e1 * 20);
                            else if (it.type != T_MOD) wait_ge(&g_st.f_h[it.rb * 32], e1 * 16);
                            break;
                        }
                        low_left = false;
                    }
                    if ((lx0 & lx1 & lx2) == 0xffffffffu) break;
                    if (!low_left && nat >= PRECLAIM_RB && (blockIdx.x % PRECLAIM_MOD) != 0) {
                        const uint32_t rdw[3] = {rd.x, rd.y, rd.z}, lxw[3] = {lx0, lx1, lx2};
                        int gsel = -1;
#pragma unroll
                        for (int rb = 15; rb >= PRECLAIM_RB; rb--) {
#pragma unroll
                            for (int k = 5; k >= 0; k--) {
                                const int gi = k * 16 + rb;
                                const bool rdy = rdw[gi >> 5] >> (gi & 31) & 1, exq = lxw[gi >> 5] >> (gi & 31) & 1;
                                const bool pre = k == 0 ? (nat == rb) : (rdw[(gi - 16) >> 5] >> ((gi - 16) & 31) & 1);
                                if (!rdy && !exq && pre) gsel = gi;
                            }
                        }
                        if (gsel >= 0) {
                            const int gi = gsel, ty = T_AT + (gi >> 4), rb = gi & 15, n = group_size(ty, rb);
                            const int i = (int)atomicAdd(&g_st.cnt[gi * 8], 1u);
                            const uint32_t bit = 1u << (gi & 31);
                            if (i >= n - 1) {
                                if (gi < 32) lx0 |= bit; else if (gi < 64) lx1 |= bit; else lx2 |= bit;
                                if (i == n - 1) asm volatile("red.relaxed.gpu.global.or.b32 [%0], %1;" :: "l"(&g_st.exh[gi >> 5]), "r"(bit) : "memory");
                            }
                            if (i < n) {
                                it.type = ty; it.rb = rb; it.nt = i;
                                if (ty == T_WO || ty == T_F2) { const int nn = n_nt(rb); it.ks = i / nn; it.nt = i - it.ks * nn; }
                                const uint32_t* dp = (ty == T_AT ? g_st.d_at : ty == T_WO ? g_st.c_at : ty == T_L2 ? g_st.c_wo : ty == T_F1 ? g_st.f_h2 : ty == T_F2 ? g_st.c_act : g_st.c_f2) + rb * 32;
                                const uint32_t dt = e1 * (ty == T_AT ? (wait_r ? 112u : 48u) : (uint32_t)group_size(ty - 1, rb));
                                int l3 = 0;
                                while ((int32_t)(ld_acquire(dp) - dt) < 0) { if (++l3 > SPIN_LIMIT) break; }
                                break;
                            }
                            continue;
                        }
                    }
                    __nanosleep(40);
                    if (++lim > SPIN_LIMIT) break;
                }
                issued++;
                if (it.type == T_L2) wait_ge(&g_st.c_mod_all, e1 * 60);
                asm volatile("fence.proxy.async.global;" ::: "memory");
                mbar_wait(b_wempty + 8 * wi, wph);
                wslot[wi] = pack_item(it);
                mbar_arrive(b_wfull + 8 * wi);
                if (++wi == 2) { wi = 0; wph ^= 1; }
                if (it.type == T_END) break;
                int nkb = 0, kb0 = 0;
                const CUtensorMap *mA = nullptr, *mB0 = nullptr, *mB1 = nullptr; int n0 = 0, n1 = 0, nbox = 4;
                switch (it.type) {
                    case T_KV: nkb = 10; mA = &P.tA_h;
                        if (it.ks) { mB0 = mB1 = (it.nt < 32) ? &P.tB_k : &P.tB_v; n0 = (it.nt & 31) * 128; n1 = n0 + 64; nbox = 2; }
                        else { mB0 = mB1 = (it.nt < 16) ? &P.tB_k : &P.tB_v; n0 = (it.nt & 15) * 256; n1 = n0 + 128; }
                        break;
                    case T_Q: nkb = 10; mA = &P.tA_h; mB0 = mB1 = &P.tB_q; n0 = it.nt * 256; n1 = n0 + 128; break;
                    case T_F1: nkb = 10; mA = &P.tA_h2; mB0 = &P.tB_g; mB1 = &P.tB_u; if (fine(it.rb)) { n0 = n1 = it.nt * 64; nbox = 2; } else n0 = n1 = it.nt * 128; break;
                    case T_WO: nkb = 64 / wo_split(it.rb); kb0 = it.ks * nkb; mA = &P.tA_o; mB0 = mB1 = &P.tB_o; n0 = red_col(it); if (is_wide(it)) n1 = n0 + 128; else { n1 = n0 + 64; nbox = 2; } break;
                    case T_F2: nkb = 27 / f2_split(it.rb); kb0 = it.ks * nkb; mA = &P.tA_act; mB0 = mB1 = &P.tB_d; n0 = red_col(it); if (is_wide(it)) n1 = n0 + 128; else { n1 = n0 + 64; nbox = 2; } break;
                    default: break;
                }
                if (it.type == T_AT) {
                    const int rp = reps(T_AT, it.rb);
#pragma unroll 1
                    for (int ii = 0; ii < 3 * rp; ii++) {
                        const int i = ii >= 3 ? ii - 3 : ii, hd = it.nt * rp + (ii >= 3);
                        mbar_wait(b_empty + 8 * stage, sph);
                        const uint32_t st = sb + stage * STAGE_BYTES, bar = b_full + 8 * stage;
                        mbar_expect_tx(bar, i ? 40960 : 32768);
                        const CUtensorMap* m = i == 0 ? &P.tL_q : (i == 1 ? &P.tL_k : &P.tL_v);
                        tma_load_2d(st + 16384, m, hd * 128, it.rb * 128, bar);
                        tma_load_2d(st + 32768, m, hd * 128 + 64, it.rb * 128, bar);
                        if (i) {
                            const CUtensorMap* mm = i == 1 ? &P.tL_km : &P.tL_vm;
                            tma_load_2d(st, mm, hd * 128, it.rb * 32, bar);
                            tma_load_2d(st + 4096, mm, hd * 128 + 64, it.rb * 32, bar);
                        }
                        if (++stage == STAGES) { stage = 0; sph ^= 1; }
                    }
                } else if (it.type == T_L1 || it.type == T_L2 || it.type == T_FIN) {
                    const int mode = it.type == T_L1 ? 0 : (it.type == T_L2 ? 1 : 2);
                    const uint32_t pbytes = mode == 0 ? 5120 : (mode == 1 ? 7680 : 2560);
                    const float* psrc = g_mod + (mode == 0 ? 0 : (mode == 1 ? 2 * 640 : 5 * 640));
                    const int rp = reps(it.type, it.rb);
#pragma unroll 1
                    for (int i = 0; i < rp; i++) {
                        mbar_wait(b_empty + 8 * stage, sph);
                        const uint32_t st = sb + stage * STAGE_BYTES, bar = b_full + 8 * stage;
                        const size_t ro = ((size_t)it.rb * 128 + (it.nt * rp + i) * 8) * 640;
                        mbar_expect_tx(bar, 10240 + (mode ? 20480 : 0) + pbytes);
                        bulk_load(st, (mode == 2 ? g_x1 : x) + ro, 10240, bar);
                        if (mode) bulk_load(st + 10240, g_slab + ro, 20480, bar);
                        bulk_load(st + 30720, psrc, pbytes, bar);
                        if (++stage == STAGES) { stage = 0; sph ^= 1; }
                    }
                }
                for (int kb = 0; kb < nkb; kb++) {
                    mbar_wait(b_empty + 8 * stage, sph);
                    const uint32_t st = sb + stage * STAGE_BYTES, bar = b_full + 8 * stage;
                    mbar_expect_tx(bar, 16384 + nbox * 8192);
                    const int k = (kb0 + kb) * 64;
                    tma_load_2d(st, mA, k, it.rb * 128, bar);
                    tma_load_2d(st + 16384, mB0, n0, k, bar);
                    if (nbox == 4) {
                        tma_load_2d(st + 16384 + 8192, mB0, n0 + 64, k, bar);
                        tma_load_2d(st + 16384 + 16384, mB1, n1, k, bar);
                        tma_load_2d(st + 16384 + 24576, mB1, n1 + 64, k, bar);
                    } else {
                        tma_load_2d(st + 16384 + 8192, mB1, n1, k, bar);
                    }
                    if (++stage == STAGES) { stage = 0; sph ^= 1; }
                }
            }
        } else if (warp == 1 && lane == 0) {
            uint32_t wi = 0, wph = 0, cph = 0;
            while (true) {
                mbar_wait(b_wfull + 8 * wi, wph);
                const Item it = unpack_item(wslot[wi]);
                mbar_arrive(b_wempty + 8 * wi);
                if (++wi == 2) { wi = 0; wph ^= 1; }
                if (it.type == T_END) break;
                asm volatile("fence.proxy.async.global;" ::: "memory");
                const bool red = it.type == T_WO || it.type == T_F2;
                const bool tma = it.type == T_KV || it.type == T_Q || it.type == T_F1 || it.type == T_AT || red;
                const bool narrow = it.type == T_F1 && fine(it.rb);
                const bool kvn = it.type == T_KV && it.ks;
                const int rounds = red ? (is_wide(it) ? 4 : 2) : (it.type == T_AT ? reps(T_AT, it.rb) : (((it.type == T_KV || it.type == T_Q) && !kvn) ? 2 : 1));
                const CUtensorMap* mS = it.type == T_F1 ? &P.tS_act : (it.type == T_AT ? &P.tS_o : (it.type == T_Q ? &P.tS_q : (it.nt < (kvn ? 32 : 16) ? &P.tS_k : &P.tS_v)));
                const int gcol = red ? red_col(it) : (narrow ? it.nt * 64 : (rounds == 1 ? (it.nt & 31) * 128 : (it.nt & 15) * 256));
                for (int rnd = 0; rnd < rounds; rnd++) {
                    for (int wg = 0; wg < 2; wg++) {
                        mbar_wait(b_cdone + 8 * wg, cph);
                        const uint32_t stg = sb + OFF_SCR + wg * 16384;
                        const int grow = it.rb * 128 + wg * 64;
                        if (red) {
                            tma_reduce_2d(&P.tR_acc, stg, gcol + rnd * 64, grow);
                            tma_reduce_2d(&P.tR_acc, stg + 8192, gcol + rnd * 64 + 32, grow);
                        } else if (tma) {
                            tma_store_2d(mS, stg, gcol + rnd * 128, grow);
                            if (!narrow) tma_store_2d(mS, stg + 8192, gcol + rnd * 128 + 64, grow);
                        }
                        if (tma) asm volatile("cp.async.bulk.commit_group;" ::: "memory");
                    }
                    cph ^= 1;
                    if (tma) asm volatile("cp.async.bulk.wait_group.read 0;" ::: "memory");
                    mbar_arrive(b_sfree); mbar_arrive(b_sfree + 8);
                }
                if (tma) { asm volatile("cp.async.bulk.wait_group 0;" ::: "memory"); asm volatile("fence.proxy.async.global;" ::: "memory"); }
                if (it.type <= T_KV) asm volatile("fence.acq_rel.gpu;" ::: "memory");
                uint32_t* cnt = nullptr; uint32_t tgt = 0; int nxt = -1;
                switch (it.type) {
                    case T_KV: if (kvn) st_relaxed_u32(&g_kvflag[it.nt], e1);
                        else { st_relaxed_u32(&g_kvflag[it.rb * 64 + it.nt * 2], e1); st_relaxed_u32(&g_kvflag[it.rb * 64 + it.nt * 2 + 1], e1); }
                    case T_Q: red_release_inc(&g_st.d_at[it.rb * 32]); break;
                    case T_MOD: if (it.nt < 20) red_add_relaxed(&g_st.c_mod_a, 1); red_add_relaxed(&g_st.c_mod_all, 1); break;
                    case T_L1: red_add_relaxed(&g_st.f_h[it.rb * 32], reps(T_L1, it.rb)); break;
                    case T_AT: cnt = &g_st.c_at[it.rb * 32]; tgt = group_size(T_AT, it.rb); nxt = T_WO; break;
                    case T_WO: cnt = &g_st.c_wo[it.rb * 32]; tgt = group_size(T_WO, it.rb); nxt = T_L2; break;
                    case T_L2: cnt = &g_st.f_h2[it.rb * 32]; tgt = group_size(T_L2, it.rb); nxt = T_F1; break;
                    case T_F1: cnt = &g_st.c_act[it.rb * 32]; tgt = group_size(T_F1, it.rb); nxt = T_F2; break;
                    case T_F2: cnt = &g_st.c_f2[it.rb * 32]; tgt = group_size(T_F2, it.rb); nxt = T_FIN; break;
                    default: break;
                }
                if (cnt) { if (atom_add_acqrel(cnt, 1) + 1 == e1 * tgt) publish_group(nxt, it.rb, e1); }
            }
            uint32_t old = atom_add_acqrel(&g_st.done, 1);
            if (old + 1 == e1 * (uint32_t)nctas) {
                for (int i = 0; i < 96; i++) g_st.cnt[i * 8] = 0;
                for (int i = 0; i < 3; i++) { g_st.ready[i] = 0; g_st.exh[i] = 0; }
                g_st.lq_claim = 0;
                st_release(&g_epoch, e1);
            }
        }
    } else {
        asm volatile("setmaxnreg.inc.sync.aligned.u32 232;");
        const int ct = tid - 128, cw = warp - 4, wg = cw >> 2;
        const int g = lane >> 2, t = lane & 3;
        uint32_t stage = 0, sph = 0, wi = 0, wph = 0, fph = 1; int ndone = 0;
        while (true) {
            if (ct == 0) wslot[4] = ndone;
            ndone++;
            mbar_wait(b_wfull + 8 * wi, wph);
            const Item it = unpack_item(wslot[wi]);
            __syncwarp();
            if (lane == 0) mbar_arrive(b_wempty + 8 * wi);
            if (++wi == 2) { wi = 0; wph ^= 1; }
            if (it.type == T_END) break;
            const bool narrow = (it.type == T_F1 && fine(it.rb)) || (it.type == T_KV && it.ks);
            if (is_wide(it)) {
                const bool red = it.type == T_WO || it.type == T_F2;
                const int nkb = it.type == T_WO ? 64 / wo_split(it.rb) : (it.type == T_F2 ? 27 / f2_split(it.rb) : 10);
                float d[128];
#pragma unroll
                for (int i = 0; i < 128; i++) d[i] = 0.f;
                for (int kb = 0; kb < nkb; kb++) {
                    mbar_wait(b_full + 8 * stage, sph);
                    const uint32_t st = sb + stage * STAGE_BYTES;
                    const uint64_t da = make_desc(st + wg * 8192, 16, 1024), db = make_desc(st + 16384, 8192, 1024);
                    wgmma_fence();
#pragma unroll
                    for (int k = 0; k < 4; k++) wgmma_n256(d, da + k * 2, db + k * 128, 1);
                    wgmma_commit();
                    wgmma_wait<1>();
                    if (kb > 0 && lane == 0) mbar_arrive(b_empty + 8 * ((stage + STAGES - 1) % STAGES));
                    if (++stage == STAGES) { stage = 0; sph ^= 1; }
                }
                wgmma_wait<0>();
                fence_acc<128>(d);
                if (lane == 0) mbar_arrive(b_empty + 8 * ((stage + STAGES - 1) % STAGES));
                if (red) {
                    const uint32_t sbase = sb + OFF_SCR + wg * 16384 + ((cw & 3) * 16 + g) * 128 + (t & 1) * 8;
#pragma unroll
                    for (int rnd = 0; rnd < 4; rnd++) {
                        mbar_wait(b_sfree + 8 * wg, fph); fph ^= 1;
#pragma unroll
                        for (int i = 0; i < 8; i++) {
                            const float* dd = d + rnd * 32 + i * 4;
                            const uint32_t a = sbase + (i >> 2) * 8192 + ((((2 * i + (t >> 1)) & 7) ^ (g & 7)) << 4);
                            sts64(a, __float_as_uint(dd[0]), __float_as_uint(dd[1]));
                            sts64(a + 1024, __float_as_uint(dd[2]), __float_as_uint(dd[3]));
                        }
                        asm volatile("fence.proxy.async.shared::cta;" ::: "memory");
                        __syncwarp();
                        if (lane == 0) mbar_arrive(b_cdone + 8 * wg);
                    }
                    continue;
                }
                const uint32_t sbase = sb + OFF_SCR + wg * 16384 + ((cw & 3) * 16 + ((lane >> 3) & 1) * 8 + (lane & 7)) * 128;
                const int sx = lane & 7, hi = lane >> 4;
                if (it.type == T_F1) {
#pragma unroll
                    for (int i = 0; i < 64; i++) d[i] = bf16r(gelu_tanh(bf16r(d[i]))) * bf16r(d[64 + i]);
                }
#pragma unroll
                for (int rnd = 0; rnd < 2; rnd++) {
                    if (rnd == 1 && it.type == T_F1) break;
                    mbar_wait(b_sfree + 8 * wg, fph); fph ^= 1;
#pragma unroll
                    for (int i = 0; i < 8; i++) {
                        const float* dd = d + rnd * 64 + i * 8;
                        const int chunk = (2 * i + hi) & 7;
                        stsm_x4(sbase + (i >> 2) * 8192 + ((chunk ^ sx) << 4), pack_bf16(dd[0], dd[1]), pack_bf16(dd[2], dd[3]), pack_bf16(dd[4], dd[5]), pack_bf16(dd[6], dd[7]));
                    }
                    asm volatile("fence.proxy.async.shared::cta;" ::: "memory");
                    __syncwarp();
                    if (lane == 0) mbar_arrive(b_cdone + 8 * wg);
                }
                continue;
            } else if (narrow) {
                float d[64];
#pragma unroll
                for (int i = 0; i < 64; i++) d[i] = 0.f;
                const int nkb = 10;
                for (int kb = 0; kb < nkb; kb++) {
                    mbar_wait(b_full + 8 * stage, sph);
                    const uint32_t st = sb + stage * STAGE_BYTES;
                    const uint64_t da = make_desc(st + wg * 8192, 16, 1024), db = make_desc(st + 16384, 8192, 1024);
                    wgmma_fence();
#pragma unroll
                    for (int k = 0; k < 4; k++) wgmma_n128(d, da + k * 2, db + k * 128, 1);
                    wgmma_commit();
                    wgmma_wait<1>();
                    if (kb > 0 && lane == 0) mbar_arrive(b_empty + 8 * ((stage + STAGES - 1) % STAGES));
                    if (++stage == STAGES) { stage = 0; sph ^= 1; }
                }
                wgmma_wait<0>();
                fence_acc<64>(d);
                if (lane == 0) mbar_arrive(b_empty + 8 * ((stage + STAGES - 1) % STAGES));
                {
                    const uint32_t sbase = sb + OFF_SCR + wg * 16384 + ((cw & 3) * 16 + ((lane >> 3) & 1) * 8 + (lane & 7)) * 128;
                    const bool f1 = it.type == T_F1;
                    if (f1) {
#pragma unroll
                        for (int i = 0; i < 32; i++) d[i] = bf16r(gelu_tanh(bf16r(d[i]))) * bf16r(d[32 + i]);
                    }
                    mbar_wait(b_sfree + 8 * wg, fph); fph ^= 1;
#pragma unroll
                    for (int i = 0; i < 8; i++) {
                        if (i >= 4 && f1) break;
                        const float* dd = d + i * 8;
                        const int chunk = (2 * i + (lane >> 4)) & 7;
                        stsm_x4(sbase + (i >> 2) * 8192 + ((chunk ^ (lane & 7)) << 4), pack_bf16(dd[0], dd[1]), pack_bf16(dd[2], dd[3]), pack_bf16(dd[4], dd[5]), pack_bf16(dd[6], dd[7]));
                    }
                    asm volatile("fence.proxy.async.shared::cta;" ::: "memory");
                }
            } else if (it.type == T_WO || it.type == T_F2) {
                float d[64];
#pragma unroll
                for (int i = 0; i < 64; i++) d[i] = 0.f;
                const int nkb = it.type == T_WO ? 64 / wo_split(it.rb) : 27 / f2_split(it.rb);
                for (int kb = 0; kb < nkb; kb++) {
                    mbar_wait(b_full + 8 * stage, sph);
                    const uint32_t st = sb + stage * STAGE_BYTES;
                    const uint64_t da = make_desc(st + wg * 8192, 16, 1024), db = make_desc(st + 16384, 8192, 1024);
                    wgmma_fence();
#pragma unroll
                    for (int k = 0; k < 4; k++) wgmma_n128(d, da + k * 2, db + k * 128, 1);
                    wgmma_commit();
                    wgmma_wait<1>();
                    if (kb > 0 && lane == 0) mbar_arrive(b_empty + 8 * ((stage + STAGES - 1) % STAGES));
                    if (++stage == STAGES) { stage = 0; sph ^= 1; }
                }
                wgmma_wait<0>();
                fence_acc<64>(d);
                if (lane == 0) mbar_arrive(b_empty + 8 * ((stage + STAGES - 1) % STAGES));
                {
                    const int r0 = (cw & 3) * 16 + g;
                    const uint32_t sbase = sb + OFF_SCR + wg * 16384 + r0 * 128 + (t & 1) * 8;
#pragma unroll
                    for (int rnd = 0; rnd < 2; rnd++) {
                        mbar_wait(b_sfree + 8 * wg, fph); fph ^= 1;
#pragma unroll
                        for (int i = 0; i < 8; i++) {
                            const float* dd = d + rnd * 32 + i * 4;
                            const uint32_t a = sbase + (i >> 2) * 8192 + ((((2 * i + (t >> 1)) & 7) ^ (g & 7)) << 4);
                            sts64(a, __float_as_uint(dd[0]), __float_as_uint(dd[1]));
                            sts64(a + 1024, __float_as_uint(dd[2]), __float_as_uint(dd[3]));
                        }
                        asm volatile("fence.proxy.async.shared::cta;" ::: "memory");
                        if (rnd == 0) { __syncwarp(); if (lane == 0) mbar_arrive(b_cdone + 8 * wg); }
                    }
                }
            } else if (it.type == T_AT) {
                const int rp = reps(T_AT, it.rb);
#pragma unroll 1
                for (int u = 0; u < rp; u++) {
                uint32_t p[6][2];
                float d[64];
                const uint32_t s0 = stage, s1 = (stage + 1) % STAGES, s2 = (stage + 2) % STAGES;
                mbar_wait(b_full + 8 * s0, sph);
                mbar_wait(b_full + 8 * s1, s1 < s0 ? sph ^ 1 : sph);
                attn_scores(sb + s0 * STAGE_BYTES + 16384, sb + s1 * STAGE_BYTES + 16384, sb + s1 * STAGE_BYTES, cw >> 1, cw & 1, lane, p);
                __syncwarp();
                if (lane == 0) { mbar_arrive(b_empty + 8 * s0); mbar_arrive(b_empty + 8 * s1); }
                mbar_wait(b_full + 8 * s2, s2 < s0 ? sph ^ 1 : sph);
                attn_pv(sb + s2 * STAGE_BYTES + 16384, sb + s2 * STAGE_BYTES, cw >> 1, lane, p, d);
                __syncwarp();
                if (lane == 0) mbar_arrive(b_empty + 8 * s2);
                stage += 3; if (stage >= STAGES) { stage -= STAGES; sph ^= 1; }
                const uint32_t sbase = sb + OFF_SCR + wg * 16384 + ((cw & 3) * 16 + ((lane >> 3) & 1) * 8 + (lane & 7)) * 128;
                mbar_wait(b_sfree + 8 * wg, fph); fph ^= 1;
#pragma unroll
                for (int i = 0; i < 8; i++) {
                    const float* dd = d + i * 8;
                    const int chunk = (2 * i + (lane >> 4)) & 7;
                    stsm_x4(sbase + (i >> 2) * 8192 + ((chunk ^ (lane & 7)) << 4), pack_bf16(dd[0], dd[1]), pack_bf16(dd[2], dd[3]), pack_bf16(dd[4], dd[5]), pack_bf16(dd[6], dd[7]));
                }
                asm volatile("fence.proxy.async.shared::cta;" ::: "memory");
                if (u + 1 < rp) { __syncwarp(); if (lane == 0) mbar_arrive(b_cdone + 8 * wg); }
                }
            } else if (it.type == T_L1 || it.type == T_L2 || it.type == T_FIN) {
                const int mode = it.type == T_L1 ? 0 : (it.type == T_L2 ? 1 : 2);
                const int rp = reps(it.type, it.rb);
#pragma unroll 1
                for (int i = 0; i < rp; i++) {
                    const size_t ro = ((size_t)it.rb * 128 + (it.nt * rp + i) * 8 + cw) * 640;
                    const uint32_t st = sb + stage * STAGE_BYTES;
                    mbar_wait(b_full + 8 * stage, sph);
                    row_item(mode, st + cw * 1280, st + 10240 + cw * 2560, st + 30720, b_empty + 8 * stage, g_slab + ro, (mode == 2 ? out : g_x1) + ro, (mode ? g_h2 : g_h) + ro, lane);
                    if (++stage == STAGES) { stage = 0; sph ^= 1; }
                }
            } else if (it.type == T_MOD) {
                const int kg = ct >> 3, c8 = ct & 7;
                float acc[8] = {0, 0, 0, 0, 0, 0, 0, 0};
                const bf16* wp = w_mod + (size_t)kg * 20 * 3840 + it.nt * 64 + c8 * 8;
                {
                    uint4 w[20]; float sl[20];
#pragma unroll
                    for (int i = 0; i < 20; i++) { w[i] = __ldg((const uint4*)(wp + (size_t)i * 3840)); sl[i] = __bfloat162float(cvec[kg * 20 + i]); }
#pragma unroll
                    for (int i = 0; i < 20; i++) {
                        const float s = bf16r(__fdividef(sl[i], 1.0f + __expf(-sl[i])));
                        acc[0] += s * __uint_as_float(w[i].x << 16); acc[1] += s * __uint_as_float(w[i].x & 0xffff0000u);
                        acc[2] += s * __uint_as_float(w[i].y << 16); acc[3] += s * __uint_as_float(w[i].y & 0xffff0000u);
                        acc[4] += s * __uint_as_float(w[i].z << 16); acc[5] += s * __uint_as_float(w[i].z & 0xffff0000u);
                        acc[6] += s * __uint_as_float(w[i].w << 16); acc[7] += s * __uint_as_float(w[i].w & 0xffff0000u);
                    }
                }
#pragma unroll
                for (int i = 0; i < 8; i++) { acc[i] += __shfl_xor_sync(0xffffffff, acc[i], 8); acc[i] += __shfl_xor_sync(0xffffffff, acc[i], 16); }
                float* scr = (float*)(smem + OFF_BAR + 256);
                bar_sync(3, 256);
                if (lane < 8) {
#pragma unroll
                    for (int i = 0; i < 8; i++) scr[cw * 64 + lane * 8 + i] = acc[i];
                }
                bar_sync(3, 256);
                if (ct < 64) {
                    float sum = 0;
#pragma unroll
                    for (int i = 0; i < 8; i++) sum += scr[i * 64 + ct];
                    g_mod[it.nt * 64 + ct] = bf16r(sum);
                }
            }
            if (it.type == T_MOD || it.type == T_L1 || it.type == T_L2 || it.type == T_FIN) { mbar_wait(b_sfree + 8 * wg, fph); fph ^= 1; }
            __syncwarp();
            if (lane == 0) mbar_arrive(b_cdone + 8 * wg);
        }
    }
}

typedef CUresult (*PFN_encodeTiled)(CUtensorMap*, CUtensorMapDataType, cuuint32_t, void*, const cuuint64_t*, const cuuint64_t*, const cuuint32_t*, const cuuint32_t*, CUtensorMapInterleave, CUtensorMapSwizzle, CUtensorMapL2promotion, CUtensorMapFloatOOBfill);

static void make_map(PFN_encodeTiled fn, CUtensorMap* m, const void* ptr, uint64_t inner, uint64_t outer, uint32_t box_inner, uint32_t box_outer, bool f32 = false) {
    cuuint64_t dims[2] = {inner, outer};
    cuuint64_t strides[1] = {inner * (f32 ? 4 : 2)};
    cuuint32_t box[2] = {box_inner, box_outer};
    cuuint32_t es[2] = {1, 1};
    fn(m, f32 ? CU_TENSOR_MAP_DATA_TYPE_FLOAT32 : CU_TENSOR_MAP_DATA_TYPE_BFLOAT16, 2, (void*)ptr, dims, strides, box, es, CU_TENSOR_MAP_INTERLEAVE_NONE, CU_TENSOR_MAP_SWIZZLE_128B, CU_TENSOR_MAP_L2_PROMOTION_L2_256B, CU_TENSOR_MAP_FLOAT_OOB_FILL_NONE);
}

#define G_LESS 0
static int g_dbg_mode = 0;

extern "C" void kernel_launch(void* const* d_in, const int* in_sizes, int n_in, void* d_out, int out_size) {
    const bf16* x = (const bf16*)d_in[0];
    const bf16* mem0 = (const bf16*)d_in[1];
    const bf16* Wq = (const bf16*)d_in[2];
    const bf16* Wk = (const bf16*)d_in[3];
    const bf16* Wv = (const bf16*)d_in[4];
    const bf16* Wo = (const bf16*)d_in[5];
    const bf16* Wg = (const bf16*)d_in[8];
    const bf16* Wu = (const bf16*)d_in[9];
    const bf16* Wd = (const bf16*)d_in[10];
    const bf16* cvec = (const bf16*)d_in[11];
    const bf16* wmod = (const bf16*)d_in[12];
    static PFN_encodeTiled fn = nullptr;
    static int nsm = 0;
    if (!fn) {
        cudaDriverEntryPointQueryResult qr;
        cudaGetDriverEntryPoint("cuTensorMapEncodeTiled", (void**)&fn, cudaEnableDefault, &qr);
        cudaFuncSetAttribute(r_kernel, cudaFuncAttributeMaxDynamicSharedMemorySize, rk::SMEM_BYTES);
        cudaFuncSetAttribute(r_kernel, cudaFuncAttributeNonPortableClusterSizeAllowed, 1);
        cudaFuncSetAttribute(g_kernel, cudaFuncAttributeMaxDynamicSharedMemorySize, gk::SMEM_BYTES);
        cudaDeviceGetAttribute(&nsm, cudaDevAttrMultiProcessorCount, 0);
    }
    void *ph, *po, *ph2, *pact, *pq, *pk, *pv;
    cudaGetSymbolAddress(&pq, g_q); cudaGetSymbolAddress(&pk, g_k); cudaGetSymbolAddress(&pv, g_v);
    cudaGetSymbolAddress(&ph, g_h); cudaGetSymbolAddress(&po, g_o); cudaGetSymbolAddress(&ph2, g_h2); cudaGetSymbolAddress(&pact, g_act);
    GParams P;
    make_map(fn, &P.tA_h, ph, 640, 2048, 64, 128);
    make_map(fn, &P.tA_o, po, 4096, 2048, 64, 128);
    make_map(fn, &P.tA_h2, ph2, 640, 2048, 64, 128);
    make_map(fn, &P.tA_act, pact, 1728, 2048, 64, 128);
    make_map(fn, &P.tB_q, Wq, 4096, 640, 64, 64);
    make_map(fn, &P.tB_k, Wk, 4096, 640, 64, 64);
    make_map(fn, &P.tB_v, Wv, 4096, 640, 64, 64);
    make_map(fn, &P.tB_o, Wo, 640, 4096, 64, 64);
    make_map(fn, &P.tB_g, Wg, 1728, 640, 64, 64);
    make_map(fn, &P.tB_u, Wu, 1728, 640, 64, 64);
    make_map(fn, &P.tB_d, Wd, 640, 1728, 64, 64);
    make_map(fn, &P.tS_q, pq, 4096, 2048, 64, 64);
    make_map(fn, &P.tS_k, pk, 4096, 2048, 64, 64);
    make_map(fn, &P.tS_v, pv, 4096, 2048, 64, 64);
    make_map(fn, &P.tS_act, pact, 1728, 2048, 64, 64);
    void *pkm, *pvm; cudaGetSymbolAddress(&pkm, g_km); cudaGetSymbolAddress(&pvm, g_vm);
    make_map(fn, &P.tS_o, po, 4096, 2048, 64, 64);
    make_map(fn, &P.tL_q, pq, 4096, 2048, 64, 128);
    make_map(fn, &P.tL_k, pk, 4096, 2048, 64, 128);
    make_map(fn, &P.tL_v, pv, 4096, 2048, 64, 128);
    make_map(fn, &P.tL_km, pkm, 4096, 512, 64, 32);
    make_map(fn, &P.tL_vm, pvm, 4096, 512, 64, 32);
    void* pacc; cudaGetSymbolAddress(&pacc, g_slab);
    make_map(fn, &P.tR_acc, pacc, 640, 2048, 32, 64, true);
    cudaStream_t st = cudaStreamPerThread;
    if (g_dbg_mode != 1) {
        cudaLaunchConfig_t cfg = {};
        cfg.gridDim = dim3(64); cfg.blockDim = dim3(256); cfg.dynamicSmemBytes = rk::SMEM_BYTES; cfg.stream = st;
        cudaLaunchAttribute at[1]; at[0].id = cudaLaunchAttributeClusterDimension; at[0].val.clusterDim.x = 16; at[0].val.clusterDim.y = 1; at[0].val.clusterDim.z = 1;
        cfg.attrs = at; cfg.numAttrs = 1;
        CUtensorMap tk, tv;
        make_map(fn, &tk, pk, 4096, 2048, 64, 32);
        make_map(fn, &tv, pv, 4096, 2048, 64, 32);
        cudaLaunchKernelEx(&cfg, r_kernel, tk, tv, mem0, Wq, Wk, Wv, Wo, 1);
    }
    {
        cudaLaunchConfig_t cfg = {};
        const int ng = g_dbg_mode == 1 ? nsm : nsm - G_LESS;
        cfg.gridDim = dim3(ng); cfg.blockDim = dim3(384); cfg.dynamicSmemBytes = gk::SMEM_BYTES; cfg.stream = st;
        cudaLaunchAttribute at[1]; at[0].id = cudaLaunchAttributeProgrammaticStreamSerialization; at[0].val.programmaticStreamSerializationAllowed = 1;
        cfg.attrs = at; cfg.numAttrs = g_dbg_mode == 1 ? 0 : 1;
        cudaLaunchKernelEx(&cfg, g_kernel, P, x, cvec, wmod, (bf16*)d_out, ng, g_dbg_mode == 1 ? 0 : 1);
    }
}
```

```cpp
#include <cuda_runtime.h>
#include <cuda_bf16.h>
#include <cuda.h>
#include <stdint.h>

typedef __nv_bfloat16 bf16;

__device__ __forceinline__ uint32_t smem_u32(const void* p) { return (uint32_t)__cvta_generic_to_shared(p); }
__device__ __forceinline__ uint32_t mapa_u32(uint32_t a, uint32_t r) { uint32_t o; asm volatile("mapa.shared::cluster.u32 %0, %1, %2;" : "=r"(o) : "r"(a), "r"(r)); return o; }
__device__ __forceinline__ void mbar_init(uint32_t bar, uint32_t cnt) { asm volatile("mbarrier.init.shared::cta.b64 [%0], %1;" :: "r"(bar), "r"(cnt) : "memory"); }
__device__ __forceinline__ void mbar_expect_tx(uint32_t bar, uint32_t bytes) { asm volatile("mbarrier.arrive.expect_tx.shared::cta.b64 _, [%0], %1;" :: "r"(bar), "r"(bytes) : "memory"); }
__device__ __forceinline__ void mbar_arrive(uint32_t bar) { asm volatile("mbarrier.arrive.shared::cta.b64 _, [%0];" :: "r"(bar) : "memory"); }
#define SPIN_LIMIT 400000
__device__ __forceinline__ bool mbar_try(uint32_t bar, uint32_t ph) {
    uint32_t ok;
    asm volatile("{ .reg .pred p; mbarrier.try_wait.parity.shared::cta.b64 p, [%1], %2; selp.u32 %0, 1, 0, p; }" : "=r"(ok) : "r"(bar), "r"(ph) : "memory");
    return ok;
}
__device__ __forceinline__ void mbar_wait(uint32_t bar, uint32_t ph) {
    if (mbar_try(bar, ph)) return;
#pragma unroll 1
    for (int lim = 0; lim < SPIN_LIMIT; lim++) if (mbar_try(bar, ph)) break;
}
__device__ __forceinline__ void mbar_wait_cluster(uint32_t bar, uint32_t ph) {
    uint32_t ok = 0; int lim = 0;
    while (true) {
        asm volatile("{ .reg .pred p; mbarrier.try_wait.parity.acquire.cluster.shared::cta.b64 p, [%1], %2; selp.u32 %0, 1, 0, p; }" : "=r"(ok) : "r"(bar), "r"(ph) : "memory");
        if (ok) break;
        if (++lim > SPIN_LIMIT) break;
    }
}
__device__ __forceinline__ void st_async_v4(uint32_t addr, uint32_t a, uint32_t b, uint32_t c, uint32_t d, uint32_t bar) {
    asm volatile("st.async.weak.shared::cluster.mbarrier::complete_tx::bytes.v4.b32 [%0], {%1,%2,%3,%4}, [%5];" :: "r"(addr), "r"(a), "r"(b), "r"(c), "r"(d), "r"(bar) : "memory");
}
__device__ __forceinline__ void ldsm_x4(uint32_t* r, uint32_t addr) {
    asm volatile("ldmatrix.sync.aligned.m8n8.x4.shared.b16 {%0,%1,%2,%3}, [%4];" : "=r"(r[0]), "=r"(r[1]), "=r"(r[2]), "=r"(r[3]) : "r"(addr) : "memory");
}
__device__ __forceinline__ void ldsm_x4_t(uint32_t* r, uint32_t addr) {
    asm volatile("ldmatrix.sync.aligned.m8n8.x4.trans.shared.b16 {%0,%1,%2,%3}, [%4];" : "=r"(r[0]), "=r"(r[1]), "=r"(r[2]), "=r"(r[3]) : "r"(addr) : "memory");
}
__device__ __forceinline__ void mma16816(float* d, const uint32_t* a, uint32_t b0, uint32_t b1) {
    asm volatile("mma.sync.aligned.m16n8k16.row.col.f32.bf16.bf16.f32 {%0,%1,%2,%3}, {%4,%5,%6,%7}, {%8,%9}, {%0,%1,%2,%3};"
        : "+f"(d[0]), "+f"(d[1]), "+f"(d[2]), "+f"(d[3]) : "r"(a[0]), "r"(a[1]), "r"(a[2]), "r"(a[3]), "r"(b0), "r"(b1));
}
__device__ __forceinline__ uint32_t pack_bf16(float lo, float hi) {
    uint32_t r; asm("cvt.rn.bf16x2.f32 %0, %1, %2;" : "=r"(r) : "f"(hi), "f"(lo)); return r;
}
__device__ __forceinline__ float bf16r(float x) { return __bfloat162float(__float2bfloat16_rn(x)); }
__device__ __forceinline__ uint4 lds128(uint32_t a) { uint4 v; asm volatile("ld.shared.v4.u32 {%0,%1,%2,%3}, [%4];" : "=r"(v.x), "=r"(v.y), "=r"(v.z), "=r"(v.w) : "r"(a) : "memory"); return v; }
__device__ __forceinline__ void sts128(uint32_t a, uint4 v) { asm volatile("st.shared.v4.u32 [%0], {%1,%2,%3,%4};" :: "r"(a), "r"(v.x), "r"(v.y), "r"(v.z), "r"(v.w) : "memory"); }
__device__ __forceinline__ void sts32(uint32_t a, uint32_t v) { asm volatile("st.shared.u32 [%0], %1;" :: "r"(a), "r"(v) : "memory"); }
__device__ __forceinline__ void sts64(uint32_t a, uint32_t x, uint32_t y) { asm volatile("st.shared.v2.u32 [%0], {%1,%2};" :: "r"(a), "r"(x), "r"(y) : "memory"); }
__device__ __forceinline__ void sts16(uint32_t a, uint16_t v) { asm volatile("st.shared.u16 [%0], %1;" :: "r"(a), "h"(v) : "memory"); }
__device__ __forceinline__ uint2 lds64(uint32_t a) { uint2 v; asm volatile("ld.shared.v2.u32 {%0,%1}, [%2];" : "=r"(v.x), "=r"(v.y) : "r"(a) : "memory"); return v; }
__device__ __forceinline__ void cp_async16(uint32_t dst, const void* src) { asm volatile("cp.async.cg.shared.global [%0], [%1], 16;" :: "r"(dst), "l"(src) : "memory"); }
__device__ __forceinline__ void cp_async_wait_all() { asm volatile("cp.async.wait_all;" ::: "memory"); }
__device__ __forceinline__ void bar_sync(int id, int n) { asm volatile("bar.sync %0, %1;" :: "r"(id), "r"(n) : "memory"); }
__device__ __forceinline__ uint4 ld_relaxed_v4(const void* p) {
    uint4 v; asm volatile("ld.relaxed.gpu.global.v4.u32 {%0,%1,%2,%3}, [%4];" : "=r"(v.x), "=r"(v.y), "=r"(v.z), "=r"(v.w) : "l"(p) : "memory"); return v;
}
__device__ __forceinline__ void st_relaxed_v4(void* p, uint4 v) {
    asm volatile("st.relaxed.gpu.global.v4.u32 [%0], {%1,%2,%3,%4};" :: "l"(p), "r"(v.x), "r"(v.y), "r"(v.z), "r"(v.w) : "memory");
}
__device__ __forceinline__ uint32_t ld_acquire(const uint32_t* p) { uint32_t v; asm volatile("ld.acquire.gpu.global.u32 %0, [%1];" : "=r"(v) : "l"(p) : "memory"); return v; }
__device__ __forceinline__ uint32_t ld_relaxed(const uint32_t* p) { uint32_t v; asm volatile("ld.relaxed.gpu.global.u32 %0, [%1];" : "=r"(v) : "l"(p) : "memory"); return v; }
__device__ __forceinline__ void st_release(uint32_t* p, uint32_t v) { asm volatile("st.release.gpu.global.u32 [%0], %1;" :: "l"(p), "r"(v) : "memory"); }
__device__ __forceinline__ void cluster_sync_all() {
    asm volatile("barrier.cluster.arrive.release.aligned;" ::: "memory");
    asm volatile("barrier.cluster.wait.acquire.aligned;" ::: "memory");
}

__device__ bf16 g_k[2048 * 4096];
__device__ bf16 g_v[2048 * 4096];
__device__ bf16 g_km[64 * 8 * 4096];
__device__ bf16 g_vm[64 * 8 * 4096];
__device__ uint4 g_gx[2][4][16][80];
__device__ uint32_t g_kvflag[16 * 64];
__device__ uint32_t g_epoch;
struct GState {
    uint32_t done, c_mod_a, c_mod_all, unused0;
    uint32_t pad0[28];
    uint32_t ready[3], lq_claim, exh[4];
    uint32_t pad1[24];
    uint32_t cnt[96 * 8];
    uint32_t f_h[16 * 32];
    uint32_t d_at[16 * 32];
    uint32_t c_at[16 * 32];
    uint32_t c_wo[16 * 32];
    uint32_t f_h2[16 * 32];
    uint32_t c_act[16 * 32];
    uint32_t c_f2[16 * 32];
};
__device__ GState g_st;
namespace gk {
enum { T_MOD, T_L1, T_KV, T_Q, T_AT, T_WO, T_L2, T_F1, T_F2, T_FIN, T_SKIP, T_END };
#define FINE_RB 13
__host__ __device__ __forceinline__ bool fine(int rb) { return rb >= FINE_RB; }
#define WO_FINE 16
#define WO_COARSE 4
__host__ __device__ __forceinline__ int wo_split(int rb) { return fine(rb) ? WO_FINE : WO_COARSE; }
__host__ __device__ __forceinline__ int f2_split(int rb) { return fine(rb) ? 9 : 3; }
__host__ __device__ __forceinline__ int n_nt(int rb) { return fine(rb) ? 5 : 3; }
__host__ __device__ __forceinline__ int n_f1(int rb) { return fine(rb) ? 27 : 14; }
__host__ __device__ __forceinline__ int group_size(int ty, int rb) {
    switch (ty) {
        case T_AT: return fine(rb) ? 32 : 16;
        case T_WO: return n_nt(rb) * wo_split(rb);
        case T_F1: return n_f1(rb);
        case T_F2: return n_nt(rb) * f2_split(rb);
        default: return fine(rb) ? 16 : 8;
    }
}
__host__ __device__ __forceinline__ int reps(int ty, int rb) { return (ty == T_L1 ? rb >= 3 : !fine(rb)) ? 2 : 1; }
}
__device__ __forceinline__ uint32_t atom_add_acqrel(uint32_t* p, uint32_t v) {
    uint32_t o; asm volatile("atom.acq_rel.gpu.global.add.u32 %0, [%1], %2;" : "=r"(o) : "l"(p), "r"(v) : "memory"); return o;
}
__device__ __forceinline__ void red_release_inc(uint32_t* p) { asm volatile("red.release.gpu.global.add.u32 [%0], 1;" :: "l"(p) : "memory"); }
__device__ __forceinline__ void publish_group(int ty, int rb, uint32_t) {
    const int gi = (ty - gk::T_AT) * 16 + rb;
    asm volatile("red.release.gpu.global.or.b32 [%0], %1;" :: "l"(&g_st.ready[gi >> 5]), "r"(1u << (gi & 31)) : "memory");
}
#define RT(i)

#define POLL_DELAY 300
#define MEMSH 1
namespace rk {
constexpr int MEM_STRIDE = 1296;
constexpr int T_STRIDE = 272;
constexpr int OFF_W = 0;
constexpr int OFF_KX = 163840;
constexpr int OFF_VX = OFF_KX + 8192;
constexpr int OFF_MEM = OFF_VX + 8192;
constexpr int OFF_Q = OFF_MEM + 10240;
constexpr int OFF_KM = OFF_Q + 8 * T_STRIDE;
constexpr int OFF_VM = OFF_KM + 8 * T_STRIDE;
constexpr int OFF_O = OFF_VM + 8 * T_STRIDE;
constexpr int OFF_SC = OFF_O + 8 * T_STRIDE;
constexpr int OFF_RED = OFF_SC + 8 * 56 * 4;
constexpr int OFF_RS = OFF_RED + 6144;
constexpr int OFF_ST = OFF_RS + 8 * 80 * 16;
constexpr int OFF_BAR = OFF_ST + 640;
constexpr int OFF_TL = OFF_BAR + 128;
constexpr int SMEM_BYTES = OFF_TL + 512;

__device__ __forceinline__ uint32_t ldg_nc(const void* p) { uint32_t v; asm volatile("ld.global.nc.u32 %0, [%1];" : "=r"(v) : "l"(p)); return v; }
__device__ __forceinline__ void load_raw(uint32_t* a, const bf16* __restrict__ W, int ld, int ka, int kb, int cb, int g, int t) {
    const bf16* p = W + (uint32_t)((ka + 2 * t) * ld + cb + 2 * g);
    const bf16* q = W + (uint32_t)((kb + 2 * t) * ld + cb + 2 * g);
    a[0] = ldg_nc(p); a[1] = ldg_nc(p + ld); a[2] = ldg_nc(q); a[3] = ldg_nc(q + ld);
}
__device__ __forceinline__ void fix_frag(uint32_t* a) {
    const uint32_t w0 = a[0], w1 = a[1], w2 = a[2], w3 = a[3];
    a[0] = __byte_perm(w0, w1, 0x5410); a[1] = __byte_perm(w0, w1, 0x7632);
    a[2] = __byte_perm(w2, w3, 0x5410); a[3] = __byte_perm(w2, w3, 0x7632);
}
__device__ __forceinline__ int chunk_src(int d, int kh, int n) { return (d - 8 * kh - n / 5) & 15; }
__device__ __forceinline__ int chunk_col(int d, int kh, int n) { const int s = chunk_src(d, kh, n); return 320 * (s & 1) + 40 * (s >> 1) + 8 * (n % 5); }
}

#define RSTEP 20
#define TL(i)
#define TG(i)

__device__ __forceinline__ void tma_load_2d(uint32_t dst, const CUtensorMap* map, int c0, int c1, uint32_t bar) {
    asm volatile("cp.async.bulk.tensor.2d.shared::cluster.global.mbarrier::complete_tx::bytes [%0], [%1, {%3, %4}], [%2];"
        :: "r"(dst), "l"(map), "r"(bar), "r"(c0), "r"(c1) : "memory");
}
__device__ __forceinline__ uint32_t movmatrix_t(uint32_t a) { uint32_t d; asm volatile("movmatrix.sync.aligned.m8n8.trans.b16 %0, %1;" : "=r"(d) : "r"(a)); return d; }
__device__ __forceinline__ void stg128(void* p, uint4 v) { asm volatile("st.global.v4.u32 [%0], {%1,%2,%3,%4};" :: "l"(p), "r"(v.x), "r"(v.y), "r"(v.z), "r"(v.w) : "memory"); }

__global__ void __launch_bounds__(256, 1)
r_kernel(const __grid_constant__ CUtensorMap tmK, const __grid_constant__ CUtensorMap tmV, const bf16* __restrict__ mem0, const bf16* __restrict__ Wq, const bf16* __restrict__ Wk, const bf16* __restrict__ Wv, const bf16* __restrict__ Wo, int wait_kv)
{
    using namespace rk;
    extern __shared__ __align__(1024) uint8_t smem[];
    const uint32_t sb = smem_u32(smem);
    const int tid = threadIdx.x, warp = tid >> 5, lane = tid & 31, g = lane >> 2, t = lane & 3;
    uint32_t rank, cid;
    asm volatile("mov.u32 %0, %%cluster_ctarank;" : "=r"(rank));
    asm volatile("mov.u32 %0, %%clusterid.x;" : "=r"(cid));
    const int hh = rank >> 1, j = rank & 1, h = cid * 8 + hh;
    const int kh = warp & 1, mb = warp >> 1;
    const uint32_t b_mem = sb + OFF_BAR, b_qkv = b_mem + 64, b_rs = b_mem + 72, b_kv = b_mem + 80;

    RT(64);
    asm volatile("griddepcontrol.launch_dependents;");
    const uint32_t epoch = ld_relaxed(&g_epoch);

    if (tid == 0) {
        for (int i = 0; i < 8; i++) mbar_init(b_mem + 8 * i, 1);
        mbar_init(b_qkv, 9); mbar_init(b_rs, 1); mbar_init(b_kv, 1);
        asm volatile("fence.mbarrier_init.release.cluster;" ::: "memory");
    }
    const uint32_t wsm = sb + OFF_W + (warp < 4 ? warp * 22528 : 4 * 22528 + (warp - 4) * 18432) + lane * 16;
    {
        const size_t co = (size_t)h * 128 + 64 * j;
        for (int i = tid; i < 640; i += 256) {
            asm volatile("prefetch.global.L2 [%0];" :: "l"(Wv + (size_t)i * 4096 + co));
            asm volatile("prefetch.global.L2 [%0];" :: "l"(Wo + ((size_t)h * 128 + i / 5) * 640 + 320 * j + (i % 5) * 64));
            asm volatile("prefetch.global.L2 [%0];" :: "l"(Wq + (size_t)i * 4096 + co));
            asm volatile("prefetch.global.L2 [%0];" :: "l"(Wk + (size_t)i * 4096 + co));
        }
    }
    uint32_t wq[20][4], wk[20][4];
    {
        const int cb = h * 128 + 64 * j + 16 * mb;
#pragma unroll
        for (int i = 0; i < 20; i++) load_raw(wq[i], Wv, 4096, chunk_col(rank, kh, 2 * i), chunk_col(rank, kh, 2 * i + 1), cb, g, t);
        const bf16* Woh = Wo + (size_t)h * 128 * 640;
        const int c3 = 320 * j + 16 * warp;
#pragma unroll
        for (int i = 0; i < 16; i++) load_raw(wk[i], Woh, 640, (i & 7) * 16, (i & 7) * 16 + 8, c3 + 128 * (i >> 3), g, t);
#pragma unroll
        for (int i = 0; i < 20; i++) { fix_frag(wq[i]); sts128(wsm + i * 512, make_uint4(wq[i][0], wq[i][1], wq[i][2], wq[i][3])); }
        if (warp < 4) {
#pragma unroll
            for (int i = 0; i < 8; i++) load_raw(wq[i], Woh, 640, i * 16, i * 16 + 8, c3 + 256, g, t);
        }
#pragma unroll
        for (int i = 0; i < 16; i++) { fix_frag(wk[i]); sts128(wsm + (20 + i) * 512, make_uint4(wk[i][0], wk[i][1], wk[i][2], wk[i][3])); }
#pragma unroll
        for (int i = 0; i < 20; i++) load_raw(wk[i], Wk, 4096, chunk_col(rank, kh, 2 * i), chunk_col(rank, kh, 2 * i + 1), cb, g, t);
        if (warp < 4) {
#pragma unroll
            for (int i = 0; i < 8; i++) { fix_frag(wq[i]); sts128(wsm + (36 + i) * 512, make_uint4(wq[i][0], wq[i][1], wq[i][2], wq[i][3])); }
        }
#pragma unroll
        for (int i = 0; i < 20; i++) load_raw(wq[i], Wq, 4096, chunk_col(rank, kh, 2 * i), chunk_col(rank, kh, 2 * i + 1), cb, g, t);
#pragma unroll
        for (int i = 0; i < 20; i++) { fix_frag(wk[i]); fix_frag(wq[i]); }
    }
    for (int i = tid; i < 640; i += 256) {
        int row = i / 80, c = i % 80;
        uint4 v = __ldg((const uint4*)(mem0 + row * 640 + c * 8));
        const int jj = c / 40, h5 = (c % 40) / 5;
        sts128(sb + OFF_MEM + (((int)rank - (2 * h5 + jj)) & 15) * 640 + row * 80 + (c % 5) * 16, v);
    }
    auto prefetch_kv = [&](int s) {
        if ((wait_kv & 1) && (s & 3) == 0) {
            const uint32_t* fk = &g_kvflag[(s >> 2) * 64 + h];
            int lim = 0;
            while (ld_acquire(fk) != epoch + 1) { if (++lim > SPIN_LIMIT) break; }
            while (ld_acquire(fk + 32) != epoch + 1) { if (++lim > SPIN_LIMIT) break; }
            asm volatile("fence.proxy.async.global;" ::: "memory");
        }
        mbar_expect_tx(b_kv, 16384);
        tma_load_2d(sb + OFF_KX, &tmK, h * 128, s * 32, b_kv);
        tma_load_2d(sb + OFF_KX + 4096, &tmK, h * 128 + 64, s * 32, b_kv);
        tma_load_2d(sb + OFF_VX, &tmV, h * 128, s * 32, b_kv);
        tma_load_2d(sb + OFF_VX + 4096, &tmV, h * 128 + 64, s * 32, b_kv);
    };
    __syncthreads();
    RT(65);
    __syncthreads();
    cluster_sync_all();

    const float scale = 0.08838834764831845f;
#define LAUNDER() int tid_ = threadIdx.x; asm volatile("" : "+r"(tid_)); const int warp = tid_ >> 5, lane = tid_ & 31, g = lane >> 2, t = lane & 3; (void)g; (void)t; (void)warp;
#define WSM() (sb + OFF_W + (warp < 4 ? warp * 22528 : 4 * 22528 + (warp - 4) * 18432) + lane * 16)

#pragma unroll 1
    for (int s = 0; s < 64; s++) {
        const uint32_t ph = s & 1;
        RT(s);
        {
            LAUNDER();
            TL(0);
            const int kh = warp & 1, mb = warp >> 1;
            const uint32_t wsm = WSM();
            const uint32_t mb0 = sb + OFF_MEM + kh * 5120 + (lane & 7) * 80 + (lane >> 3) * 16;
            const uint32_t mb1 = mb0 + ((lane >> 3) >= 1 ? 560 : 0), mb2 = mb0 + ((lane >> 3) >= 2 ? 560 : 0), mb3 = mb0 + ((lane >> 3) >= 3 ? 560 : 0);
            auto baddr = [&](int it) {
                const int r5 = (4 * it) % 5, c = ((4 * it) / 5) * 640 + r5 * 16;
                return (r5 <= 1 ? mb0 : (r5 == 4 ? mb1 : (r5 == 3 ? mb2 : mb3))) + c;
            };
            uint4 va[6];
            va[0] = lds128(wsm); va[1] = lds128(wsm + 512); va[2] = lds128(wsm + 1024); va[3] = lds128(wsm + 1536);
            if (s > 0) mbar_wait(b_mem, ph ^ 1);
            TL(1); TG(15);
            float aq0[4] = {0, 0, 0, 0}, aq1[4] = {0, 0, 0, 0}, ak0[4] = {0, 0, 0, 0}, ak1[4] = {0, 0, 0, 0}, av0[4] = {0, 0, 0, 0}, av1[4] = {0, 0, 0, 0};
            uint32_t b[3][4];
            ldsm_x4(b[0], baddr(0)); ldsm_x4(b[1], baddr(1));
            if (tid_ == 0) {
                mbar_expect_tx(b_qkv, 3072);
                if (s < 63) mbar_expect_tx(b_rs, 10240);
            }
#pragma unroll
            for (int i = 0; i < 10; i++) {
                if (i + 2 < 10) {
                    const int it = i + 2, sl = ((4 * it + 3) / 5) >> MEMSH, slp = ((4 * (it - 1) + 3) / 5) >> MEMSH;
                    if (sl != slp && s > 0) mbar_wait(b_mem + 8 * sl, ph ^ 1);
                    ldsm_x4(b[(i + 2) % 3], baddr(i + 2));
                    va[(2 * i + 4) % 6] = lds128(wsm + (2 * i + 4) * 512); va[(2 * i + 5) % 6] = lds128(wsm + (2 * i + 5) * 512);
                }
                const uint32_t* bb = b[i % 3];
                mma16816(aq0, wq[2 * i], bb[0], bb[1]); mma16816(ak0, wk[2 * i], bb[0], bb[1]); mma16816(av0, (uint32_t*)&va[(2 * i) % 6], bb[0], bb[1]);
                mma16816(aq1, wq[2 * i + 1], bb[2], bb[3]); mma16816(ak1, wk[2 * i + 1], bb[2], bb[3]); mma16816(av1, (uint32_t*)&va[(2 * i + 1) % 6], bb[2], bb[3]);
            }
            float snd[4], fin[4];
#pragma unroll
            for (int i = 0; i < 4; i++) { float q = aq0[i] + aq1[i], k = ak0[i] + ak1[i]; snd[i] = kh ? q : k; fin[i] = kh ? k : q; av0[i] += av1[i]; }
            sts128(sb + OFF_RED + tid_ * 16, make_uint4(__float_as_uint(snd[0]), __float_as_uint(snd[1]), __float_as_uint(snd[2]), __float_as_uint(snd[3])));
            sts64(sb + OFF_RED + 4096 + tid_ * 8, __float_as_uint(kh ? av0[0] : av0[1]), __float_as_uint(kh ? av0[2] : av0[3]));
            bar_sync(1 + mb, 64);
            uint4 r = lds128(sb + OFF_RED + (tid_ ^ 32) * 16);
            uint2 r2 = lds64(sb + OFF_RED + 4096 + (tid_ ^ 32) * 8);
            fin[0] += __uint_as_float(r.x); fin[1] += __uint_as_float(r.y); fin[2] += __uint_as_float(r.z); fin[3] += __uint_as_float(r.w);
            float f0 = (kh ? av0[1] : av0[0]) + __uint_as_float(r2.x), f1 = (kh ? av0[3] : av0[2]) + __uint_as_float(r2.y);
            TL(2);
            const uint32_t cofs = (64 * j + 16 * mb) * 2;
            const uint32_t buf = sb + (kh ? OFF_KM : OFF_Q) + cofs;
            sts32(buf + (2 * t) * T_STRIDE + g * 4, pack_bf16(fin[0], fin[2]));
            sts32(buf + (2 * t + 1) * T_STRIDE + g * 4, pack_bf16(fin[1], fin[3]));
            sts32(sb + OFF_VM + cofs + (2 * t + kh) * T_STRIDE + g * 4, pack_bf16(f0, f1));
            __syncwarp();
            if (lane < 24) {
                const uint32_t peer_off = mapa_u32(sb, rank ^ 1) - sb;
                const int row = lane < 16 ? (lane >> 1) : 2 * ((lane - 16) >> 1) + kh;
                const uint32_t a = (lane < 16 ? buf : sb + OFF_VM + cofs) + row * T_STRIDE + (lane & 1) * 16;
                uint4 v = lds128(a);
                st_async_v4(a + peer_off, v.x, v.y, v.z, v.w, b_qkv + peer_off);
                if ((kh || lane >= 16) && !(wait_kv & 8)) {
                    bf16* dst = (lane < 16 ? g_km : g_vm) + ((uint32_t)(s * 8 + row) * 4096u + h * 128 + 64 * j + 16 * mb + (lane & 1) * 8);
                    stg128(dst, v);
                }
            }
            if (lane == 0) mbar_arrive(b_qkv);
            if (s == 0 && tid_ == 224) prefetch_kv(0);
            TL(3);
        }
        if (s == 63) {
            __syncthreads();
            if (threadIdx.x == 0 && (wait_kv & 1)) red_release_inc(&g_st.d_at[15 * 32]);
            break;
        }
        uint4 wa[8];
        {
            LAUNDER();
            const uint32_t wsm = WSM();
            if (!(wait_kv & 2) || s == 0) mbar_wait(b_kv, ph);
            if (warp >= 4 && warp < 7) {
                const int kw = warp - 4;
                uint32_t ka[8][4];
                if (kw < 2) {
                    const uint32_t kaddr = sb + OFF_KX + (16 * kw + (lane & 15)) * 128;
#pragma unroll
                    for (int i = 0; i < 8; i++) ldsm_x4(ka[i], kaddr + (i >> 2) * 4096 + ((((2 * i + (lane >> 4)) & 7) ^ (lane & 7)) << 4));
                    mbar_wait(b_qkv, ph);
                } else {
                    mbar_wait(b_qkv, ph);
                    const uint32_t kaddr = sb + OFF_KM + (lane & 7) * T_STRIDE + (lane >> 4) * 16;
#pragma unroll
                    for (int i = 0; i < 8; i++) ldsm_x4(ka[i], kaddr + i * 32);
                }
                TL(5);
                const uint32_t qa = sb + OFF_Q + (lane & 7) * T_STRIDE + (lane >> 3) * 16;
                uint32_t qb[4][4];
#pragma unroll
                for (int i = 0; i < 4; i++) ldsm_x4(qb[i], qa + i * 64);
                float s0[4] = {0, 0, 0, 0}, s1[4] = {0, 0, 0, 0}, s2[4] = {0, 0, 0, 0}, s3[4] = {0, 0, 0, 0};
                mma16816(s0, ka[0], qb[0][0], qb[0][1]); mma16816(s1, ka[1], qb[0][2], qb[0][3]);
                mma16816(s2, ka[2], qb[1][0], qb[1][1]); mma16816(s3, ka[3], qb[1][2], qb[1][3]);
                mma16816(s0, ka[4], qb[2][0], qb[2][1]); mma16816(s1, ka[5], qb[2][2], qb[2][3]);
                mma16816(s2, ka[6], qb[3][0], qb[3][1]); mma16816(s3, ka[7], qb[3][2], qb[3][3]);
                const uint32_t sc = sb + OFF_SC + (16 * kw + g) * 4 + (2 * t) * 224;
                sts32(sc, __float_as_uint(bf16r(bf16r((s0[0] + s1[0]) + (s2[0] + s3[0])) * scale)));
                sts32(sc + 224, __float_as_uint(bf16r(bf16r((s0[1] + s1[1]) + (s2[1] + s3[1])) * scale)));
                if (kw < 2) {
                    sts32(sc + 32, __float_as_uint(bf16r(bf16r((s0[2] + s1[2]) + (s2[2] + s3[2])) * scale)));
                    sts32(sc + 32 + 224, __float_as_uint(bf16r(bf16r((s0[3] + s1[3]) + (s2[3] + s3[3])) * scale)));
                }
                asm volatile("bar.arrive 6, 224;" ::: "memory");
                TL(4);
#pragma unroll
                for (int i = 0; i < 8; i++) wa[i] = lds128(wsm + (20 + i) * 512);
            } else {
#pragma unroll
                for (int i = 0; i < 8; i++) wa[i] = lds128(wsm + (20 + i) * 512);
                if (warp < 4) {
                    mbar_wait(b_qkv, ph);
                    uint32_t a0[2][4], a1[2][4], a2[2][4];
#pragma unroll
                    for (int u = 0; u < 2; u++) {
                        const int et = warp + 4 * u;
                        const uint32_t vx = sb + OFF_VX + u * 4096 + ((lane >> 4) * 8 + (lane & 7)) * 128 + ((((2 * warp + ((lane >> 3) & 1)) & 7) ^ (lane & 7)) << 4);
                        ldsm_x4_t(a0[u], vx); ldsm_x4_t(a1[u], vx + 16 * 128);
                        ldsm_x4_t(a2[u], sb + OFF_VM + (lane & 7) * T_STRIDE + (16 * et + ((lane >> 3) & 1) * 8) * 2);
                    }
                    bar_sync(6, 224);
                    TL(6);
                    float x[10];
#pragma unroll
                    for (int i = 0; i < 5; i++) { uint2 v = lds64(sb + OFF_SC + g * 224 + (8 * i + 2 * t) * 4); x[2 * i] = __uint_as_float(v.x); x[2 * i + 1] = __uint_as_float(v.y); }
                    float m = fmaxf(fmaxf(fmaxf(x[0], x[1]), fmaxf(x[2], x[3])), fmaxf(fmaxf(x[4], x[5]), fmaxf(x[6], x[7])));
                    m = fmaxf(m, fmaxf(x[8], x[9]));
                    m = fmaxf(m, __shfl_xor_sync(0xffffffff, m, 1)); m = fmaxf(m, __shfl_xor_sync(0xffffffff, m, 2));
                    float sum0 = 0, sum1 = 0;
#pragma unroll
                    for (int i = 0; i < 5; i++) { x[2 * i] = __expf(x[2 * i] - m); sum0 += x[2 * i]; x[2 * i + 1] = __expf(x[2 * i + 1] - m); sum1 += x[2 * i + 1]; }
                    float sum = sum0 + sum1;
                    sum += __shfl_xor_sync(0xffffffff, sum, 1); sum += __shfl_xor_sync(0xffffffff, sum, 2);
                    float inv = __fdividef(1.0f, sum);
                    if (inv == 123.f) TL(14);
                    TL(4);
                    uint32_t pb[5];
#pragma unroll
                    for (int i = 0; i < 5; i++) pb[i] = pack_bf16(x[2 * i] * inv, x[2 * i + 1] * inv);
#pragma unroll
                    for (int u = 0; u < 2; u++) {
                        float o0[4] = {0, 0, 0, 0}, o1[4] = {0, 0, 0, 0}, o2[4] = {0, 0, 0, 0};
                        mma16816(o0, a0[u], pb[0], pb[1]); mma16816(o1, a1[u], pb[2], pb[3]); mma16816(o2, a2[u], pb[4], 0u);
                        const uint32_t lo = movmatrix_t(pack_bf16((o0[0] + o1[0]) + o2[0], (o0[1] + o1[1]) + o2[1]));
                        const uint32_t hi = movmatrix_t(pack_bf16((o0[2] + o1[2]) + o2[2], (o0[3] + o1[3]) + o2[3]));
                        const uint32_t oa = sb + OFF_O + g * T_STRIDE + (16 * (warp + 4 * u) + 2 * t) * 2;
                        sts32(oa, lo); sts32(oa + 16, hi);
                    }
                    TL(5);
                } else {
                    if (lane < (8 >> MEMSH)) mbar_expect_tx(b_mem + 8 * lane, 1280 << MEMSH);
                }
            }
        }
        __syncthreads();
        {
            LAUNDER();
            TL(7);
            const uint32_t wsm = WSM();
            uint32_t ob[16];
            const uint32_t oa = sb + OFF_O + (lane & 7) * T_STRIDE + (lane >> 3) * 16;
#pragma unroll
            for (int i = 0; i < 4; i++) ldsm_x4(ob + 4 * i, oa + i * 64);
            const uint32_t rs_base = OFF_RS + hh * 1280 + t * 16;
            const int ntile = warp < 4 ? 3 : 2;
#pragma unroll 1
            for (int tl = 0; tl < ntile; tl++) {
                float d0[4] = {0, 0, 0, 0}, d1[4] = {0, 0, 0, 0}, d2[4] = {0, 0, 0, 0}, d3[4] = {0, 0, 0, 0};
                const bool more = tl + 1 < ntile;
                const uint32_t nx = wsm + (28 + 8 * tl) * 512;
                mma16816(d0, (uint32_t*)&wa[0], ob[0], ob[1]);   if (more) wa[0] = lds128(nx);
                mma16816(d1, (uint32_t*)&wa[1], ob[2], ob[3]);   if (more) wa[1] = lds128(nx + 512);
                mma16816(d2, (uint32_t*)&wa[2], ob[4], ob[5]);   if (more) wa[2] = lds128(nx + 1024);
                mma16816(d3, (uint32_t*)&wa[3], ob[6], ob[7]);   if (more) wa[3] = lds128(nx + 1536);
                mma16816(d0, (uint32_t*)&wa[4], ob[8], ob[9]);   if (more) wa[4] = lds128(nx + 2048);
                mma16816(d1, (uint32_t*)&wa[5], ob[10], ob[11]); if (more) wa[5] = lds128(nx + 2560);
                mma16816(d2, (uint32_t*)&wa[6], ob[12], ob[13]); if (more) wa[6] = lds128(nx + 3072);
                mma16816(d3, (uint32_t*)&wa[7], ob[14], ob[15]); if (more) wa[7] = lds128(nx + 3584);
                const int col = 16 * (warp + 8 * tl) + 2 * g; const int own = col / 40; const int cp = (col - own * 40) >> 1;
                const uint32_t dbase = mapa_u32(sb, 2 * own + j);
                st_async_v4(dbase + rs_base + cp * 64, __float_as_uint((d0[0] + d1[0]) + (d2[0] + d3[0])), __float_as_uint((d0[1] + d1[1]) + (d2[1] + d3[1])),
                            __float_as_uint((d0[2] + d1[2]) + (d2[2] + d3[2])), __float_as_uint((d0[3] + d1[3]) + (d2[3] + d3[3])), dbase + OFF_BAR + 72);
            }
            TL(8);
        }
        {
            LAUNDER();
            if (warp >= 5) {
                const int x = tid_ - 160;
                const int ot = x < 80 ? x : 79;
                const uint32_t gs = epoch * 64 + s; const uint32_t tag = (gs + 1) & 15u; const int slot = gs & 1;
                uint4* gp = &g_gx[slot][0][rank][ot];
                mbar_wait(b_rs, ph);
                TL(9); TG(12);
                uint4 u[8];
#pragma unroll
                for (int q = 0; q < 8; q++) u[q] = lds128(sb + OFF_RS + q * 1280 + ot * 16);
                float4 a;
                a.x = ((__uint_as_float(u[0].x) + __uint_as_float(u[1].x)) + (__uint_as_float(u[2].x) + __uint_as_float(u[3].x))) + ((__uint_as_float(u[4].x) + __uint_as_float(u[5].x)) + (__uint_as_float(u[6].x) + __uint_as_float(u[7].x)));
                a.y = ((__uint_as_float(u[0].y) + __uint_as_float(u[1].y)) + (__uint_as_float(u[2].y) + __uint_as_float(u[3].y))) + ((__uint_as_float(u[4].y) + __uint_as_float(u[5].y)) + (__uint_as_float(u[6].y) + __uint_as_float(u[7].y)));
                a.z = ((__uint_as_float(u[0].z) + __uint_as_float(u[1].z)) + (__uint_as_float(u[2].z) + __uint_as_float(u[3].z))) + ((__uint_as_float(u[4].z) + __uint_as_float(u[5].z)) + (__uint_as_float(u[6].z) + __uint_as_float(u[7].z)));
                a.w = ((__uint_as_float(u[0].w) + __uint_as_float(u[1].w)) + (__uint_as_float(u[2].w) + __uint_as_float(u[3].w))) + ((__uint_as_float(u[4].w) + __uint_as_float(u[5].w)) + (__uint_as_float(u[6].w) + __uint_as_float(u[7].w)));
                uint4 mine = make_uint4((__float_as_uint(a.x) & ~15u) | tag, (__float_as_uint(a.y) & ~15u) | tag, (__float_as_uint(a.z) & ~15u) | tag, (__float_as_uint(a.w) & ~15u) | tag);
                if (x < 80) st_relaxed_v4(gp + cid * 1280, mine);
                { uint32_t c0, c1; asm volatile("mov.u32 %0, %%clock;" : "=r"(c0) :: "memory"); do { asm volatile("mov.u32 %0, %%clock;" : "=r"(c1) :: "memory"); } while (c1 - c0 < POLL_DELAY); }
                uint4 v[3];
                const uint4* rp0 = gp + (cid ^ 1) * 1280; const uint4* rp1 = gp + (cid ^ 2) * 1280; const uint4* rp2 = gp + (cid ^ 3) * 1280;
                int lim = 0;
                while (true) {
                    v[0] = ld_relaxed_v4(rp0); v[1] = ld_relaxed_v4(rp1); v[2] = ld_relaxed_v4(rp2);
                    uint32_t bad = 0;
#pragma unroll
                    for (int c = 0; c < 3; c++) bad |= (v[c].x ^ tag) | (v[c].y ^ tag) | (v[c].z ^ tag) | (v[c].w ^ tag);
                    if ((bad & 15u) == 0) break;
                    if (++lim > SPIN_LIMIT) break;
                }
                float f0 = (__uint_as_float(mine.x) + __uint_as_float(v[0].x)) + (__uint_as_float(v[1].x) + __uint_as_float(v[2].x));
                float f1 = (__uint_as_float(mine.y) + __uint_as_float(v[0].y)) + (__uint_as_float(v[1].y) + __uint_as_float(v[2].y));
                float f2 = (__uint_as_float(mine.z) + __uint_as_float(v[0].z)) + (__uint_as_float(v[1].z) + __uint_as_float(v[2].z));
                float f3 = (__uint_as_float(mine.w) + __uint_as_float(v[0].w)) + (__uint_as_float(v[1].w) + __uint_as_float(v[2].w));
                const int cp = ot >> 2, tt = ot & 3;
                sts32(sb + OFF_ST + (2 * tt) * 80 + cp * 4, pack_bf16(f0, f2));
                sts32(sb + OFF_ST + (2 * tt + 1) * 80 + cp * 4, pack_bf16(f1, f3));
                TL(10); TG(13);
                bar_sync(5, 128);
                if (x < 80) {
                    const int c = x % 40, d0 = x / 40;
                    uint4 w = lds128(sb + OFF_ST + c * 16);
                    const uint32_t off = OFF_MEM + d0 * 5120 + c * 16;
#pragma unroll
                    for (int i = 0; i < 8; i++) {
                        const uint32_t rb = mapa_u32(sb, (d0 * 8 + i + rank) & 15);
                        st_async_v4(rb + off + i * 640, w.x, w.y, w.z, w.w, rb + OFF_BAR + 8 * (i >> MEMSH));
                    }
                }
            } else if (warp == 4) {
                if (lane == 0 && (s & 3) == 3 && (wait_kv & 1)) red_release_inc(&g_st.d_at[(s >> 2) * 32]);
                __syncwarp();
            } else if (warp == 3) {
                bar_sync(5, 128);
                if (lane == 0 && s < 62 && !(wait_kv & 2)) prefetch_kv(s + 1);
                __syncwarp();
            }
            TL(11);
        }
    }
    cluster_sync_all();
}

__device__ float g_mod[3840];
__device__ bf16 g_h[2048 * 640];
__device__ bf16 g_q[2048 * 4096];
__device__ bf16 g_o[2048 * 4096];
__device__ bf16 g_x1[2048 * 640];
__device__ bf16 g_h2[2048 * 640];
__device__ bf16 g_act[2048 * 1728];
__device__ float g_slab[2048 * 640];

namespace gk {
#define NSTAGES 3
constexpr int STAGES = NSTAGES;
constexpr int STAGE_BYTES = 49152;
constexpr int OFF_SCR = STAGES * STAGE_BYTES;
constexpr int OFF_BAR = OFF_SCR + 65536;
constexpr int SMEM_BYTES = OFF_BAR + 256 + 2048;
#define PRECLAIM_MOD 2
#define PRECLAIM_RB 15
#define URGENT_LEAD 1
#define LOW_LEAD 16
constexpr int N_MOD = 60, N_L1 = 48 + 13 * 8, N_KV = 32, N_Q = 16;
constexpr int I_L1 = N_MOD, I_W = I_L1 + N_L1;
constexpr int N_LOW = I_W + 16 * (N_KV + N_Q) + 32;
constexpr int NFINE = 16 - FINE_RB;
constexpr int N_HIGH = 16 * (32 + 16 + 16) + (16 - NFINE) * (3 * WO_COARSE + 14 + 9) + NFINE * (5 * WO_FINE + 27 + 45);
struct Item { int type, rb, nt, ks; };
__host__ __device__ inline Item decode_low(int t) {
    Item it; it.rb = 0; it.nt = 0; it.ks = 0;
    if (t < I_L1) { it.type = T_MOD; it.nt = t; return it; }
    if (t < I_L1 + 16) { it.type = T_L1; it.rb = 0; it.nt = t - I_L1; return it; }
    if (t < I_L1 + 80) { it.type = T_KV; it.rb = 0; it.nt = t - I_L1 - 16; it.ks = 1; return it; }
    if (t < I_L1 + 112) { it.type = T_L1; it.rb = (t - I_L1 - 64) >> 4; it.nt = (t - I_L1 - 64) & 15; return it; }
    if (t < I_L1 + 144) { it.type = T_KV; it.rb = 1; it.nt = t - I_L1 - 112; return it; }
    if (t < I_W + 96) { it.type = T_L1; it.rb = 3 + ((t - I_L1 - 144) >> 3); it.nt = (t - I_L1 - 144) & 7; return it; }
    t -= I_W + 96;
    if (t < 14 * 48) { const int w = t / 48; t -= w * 48; if (t < 16) { it.type = T_Q; it.rb = w; it.nt = t; } else { it.type = T_KV; it.rb = w + 2; it.nt = t - 16; } return it; }
    t -= 14 * 48;
    it.type = T_Q; it.rb = 14 + (t >> 4); it.nt = t & 15; return it;
}
__device__ __forceinline__ bool is_wide(const Item& it) {
    if (it.type == T_KV || it.type == T_Q) return it.ks == 0;
    if (it.type == T_F1) return !fine(it.rb);
    if (it.type == T_WO || it.type == T_F2) return !fine(it.rb) && it.nt < 2;
    return false;
}
__device__ __forceinline__ int red_col(const Item& it) { return fine(it.rb) ? it.nt * 128 : it.nt * 256; }
__device__ __forceinline__ int pack_item(const Item& it) { return it.type | (it.rb << 4) | (it.nt << 8) | (it.ks << 16); }
__device__ __forceinline__ Item unpack_item(int v) { Item it; it.type = v & 15; it.rb = (v >> 4) & 15; it.nt = (v >> 8) & 255; it.ks = (v >> 16) & 255; return it; }
}

struct GParams {
    CUtensorMap tA_h, tA_o, tA_h2, tA_act, tB_q, tB_k, tB_v, tB_o, tB_g, tB_u, tB_d, tS_q, tS_k, tS_v, tS_act, tS_o, tL_q, tL_k, tL_v, tL_km, tL_vm, tR_acc;
};

__device__ __forceinline__ void wait_ge(const uint32_t* p, uint32_t target) {
    int lim = 0;
    while ((int32_t)(ld_acquire(p) - target) < 0) { __nanosleep(64); if (++lim > SPIN_LIMIT) break; }
}
__device__ __forceinline__ void red_add_relaxed(uint32_t* p, uint32_t v) { asm volatile("red.relaxed.gpu.global.add.u32 [%0], %1;" :: "l"(p), "r"(v) : "memory"); }
__device__ __forceinline__ void st_relaxed_u32(uint32_t* p, uint32_t v) { asm volatile("st.relaxed.gpu.global.u32 [%0], %1;" :: "l"(p), "r"(v) : "memory"); }
__device__ __forceinline__ void red_add_release(uint32_t* p, uint32_t v) { asm volatile("red.release.gpu.global.add.u32 [%0], %1;" :: "l"(p), "r"(v) : "memory"); }

__device__ __forceinline__ void wgmma_fence() { asm volatile("wgmma.fence.sync.aligned;" ::: "memory"); }
__device__ __forceinline__ void wgmma_commit() { asm volatile("wgmma.commit_group.sync.aligned;" ::: "memory"); }
template<int N> __device__ __forceinline__ void wgmma_wait() { asm volatile("wgmma.wait_group.sync.aligned %0;" :: "n"(N) : "memory"); }

template<int N> __device__ __forceinline__ void fence_acc(float* d) {
#pragma unroll
    for (int i = 0; i < N; i++) asm volatile("" : "+f"(d[i]) :: "memory");
}
#define ACC8(b) "+f"(d[b]), "+f"(d[b+1]), "+f"(d[b+2]), "+f"(d[b+3]), "+f"(d[b+4]), "+f"(d[b+5]), "+f"(d[b+6]), "+f"(d[b+7])
#define ACC32(b) ACC8(b), ACC8(b+8), ACC8(b+16), ACC8(b+24)
__device__ __forceinline__ void wgmma_n128(float* d, uint64_t da, uint64_t db, int scale_d) {
    asm volatile("{ .reg .pred p; setp.ne.b32 p, %66, 0;\n"
        "wgmma.mma_async.sync.aligned.m64n128k16.f32.bf16.bf16 {%0,%1,%2,%3,%4,%5,%6,%7,%8,%9,%10,%11,%12,%13,%14,%15,%16,%17,%18,%19,%20,%21,%22,%23,%24,%25,%26,%27,%28,%29,%30,%31,"
        "%32,%33,%34,%35,%36,%37,%38,%39,%40,%41,%42,%43,%44,%45,%46,%47,%48,%49,%50,%51,%52,%53,%54,%55,%56,%57,%58,%59,%60,%61,%62,%63}, %64, %65, p, 1, 1, 0, 1; }"
        : ACC32(0), ACC32(32) : "l"(da), "l"(db), "r"(scale_d));
}
__device__ __forceinline__ void wgmma_n256(float* d, uint64_t da, uint64_t db, int scale_d) {
    asm volatile("{ .reg .pred p; setp.ne.b32 p, %130, 0;\n"
        "wgmma.mma_async.sync.aligned.m64n256k16.f32.bf16.bf16 {%0,%1,%2,%3,%4,%5,%6,%7,%8,%9,%10,%11,%12,%13,%14,%15,%16,%17,%18,%19,%20,%21,%22,%23,%24,%25,%26,%27,%28,%29,%30,%31,"
        "%32,%33,%34,%35,%36,%37,%38,%39,%40,%41,%42,%43,%44,%45,%46,%47,%48,%49,%50,%51,%52,%53,%54,%55,%56,%57,%58,%59,%60,%61,%62,%63,"
        "%64,%65,%66,%67,%68,%69,%70,%71,%72,%73,%74,%75,%76,%77,%78,%79,%80,%81,%82,%83,%84,%85,%86,%87,%88,%89,%90,%91,%92,%93,%94,%95,"
        "%96,%97,%98,%99,%100,%101,%102,%103,%104,%105,%106,%107,%108,%109,%110,%111,%112,%113,%114,%115,%116,%117,%118,%119,%120,%121,%122,%123,%124,%125,%126,%127}, %128, %129, p, 1, 1, 0, 1; }"
        : ACC32(0), ACC32(32), ACC32(64), ACC32(96) : "l"(da), "l"(db), "r"(scale_d));
}
__device__ __forceinline__ uint64_t make_desc(uint32_t addr, uint32_t lbo, uint32_t sbo) {
    return (uint64_t)((addr & 0x3FFFF) >> 4) | ((uint64_t)(lbo >> 4) << 16) | ((uint64_t)(sbo >> 4) << 32) | ((uint64_t)1 << 62);
}

__device__ __forceinline__ float div_fix(float a, float b, float rb) { float q = a * rb; float r = fmaf(-q, b, a); return fmaf(r, rb, q); }
__device__ __forceinline__ void row_item(int mode, uint32_t sx, uint32_t sa, uint32_t sp, uint32_t bar_empty, float* __restrict__ acc, bf16* __restrict__ yout, bf16* __restrict__ out, int lane) {
    float x[20];
#pragma unroll
    for (int i = 0; i < 5; i++) {
        const uint2 v = lds64(sx + i * 256 + lane * 8);
        x[4 * i] = __uint_as_float(v.x << 16); x[4 * i + 1] = __uint_as_float(v.x & 0xffff0000u);
        x[4 * i + 2] = __uint_as_float(v.y << 16); x[4 * i + 3] = __uint_as_float(v.y & 0xffff0000u);
    }
    if (mode) {
#pragma unroll
        for (int i = 0; i < 5; i++) {
            const uint4 a = lds128(sa + i * 512 + lane * 16), gt = lds128(sp + i * 512 + lane * 16);
            x[4 * i] = bf16r(x[4 * i] + bf16r(__uint_as_float(gt.x) * bf16r(__uint_as_float(a.x)))); x[4 * i + 1] = bf16r(x[4 * i + 1] + bf16r(__uint_as_float(gt.y) * bf16r(__uint_as_float(a.y))));
            x[4 * i + 2] = bf16r(x[4 * i + 2] + bf16r(__uint_as_float(gt.z) * bf16r(__uint_as_float(a.z)))); x[4 * i + 3] = bf16r(x[4 * i + 3] + bf16r(__uint_as_float(gt.w) * bf16r(__uint_as_float(a.w))));
            *(uint2*)(yout + i * 128 + lane * 4) = make_uint2(pack_bf16(x[4 * i], x[4 * i + 1]), pack_bf16(x[4 * i + 2], x[4 * i + 3]));
        }
        sp += 2560;
    }
    if (mode != 2) {
#pragma unroll
        for (int i = 0; i < 5; i++) *(float4*)(acc + i * 128 + lane * 4) = make_float4(0.f, 0.f, 0.f, 0.f);
    }
    if (mode != 2) {
        float s = 0;
#pragma unroll
        for (int i = 0; i < 20; i++) s += x[i];
#pragma unroll
        for (int o = 16; o; o >>= 1) s += __shfl_xor_sync(0xffffffff, s, o);
        const float mean = s * (1.0f / 640.0f);
        float q = 0;
#pragma unroll
        for (int i = 0; i < 20; i++) { float d = x[i] - mean; q += d * d; }
#pragma unroll
        for (int o = 16; o; o >>= 1) q += __shfl_xor_sync(0xffffffff, q, o);
        const float m16 = bf16r(mean);
        const float sd = bf16r(sqrtf(bf16r(bf16r(q * (1.0f / 640.0f)) + 1e-5f)));
        const float rs = __frcp_rn(sd);
#pragma unroll
        for (int i = 0; i < 5; i++) {
            const uint4 sh = lds128(sp + i * 512 + lane * 16), sc = lds128(sp + 2560 + i * 512 + lane * 16);
            float y0 = bf16r(bf16r(div_fix(bf16r(x[4 * i] - m16), sd, rs)) * bf16r(1.0f + __uint_as_float(sc.x))) + __uint_as_float(sh.x);
            float y1 = bf16r(bf16r(div_fix(bf16r(x[4 * i + 1] - m16), sd, rs)) * bf16r(1.0f + __uint_as_float(sc.y))) + __uint_as_float(sh.y);
            float y2 = bf16r(bf16r(div_fix(bf16r(x[4 * i + 2] - m16), sd, rs)) * bf16r(1.0f + __uint_as_float(sc.z))) + __uint_as_float(sh.z);
            float y3 = bf16r(bf16r(div_fix(bf16r(x[4 * i + 3] - m16), sd, rs)) * bf16r(1.0f + __uint_as_float(sc.w))) + __uint_as_float(sh.w);
            *(uint2*)(out + i * 128 + lane * 4) = make_uint2(pack_bf16(y0, y1), pack_bf16(y2, y3));
        }
    }
    __syncwarp();
    if (lane == 0) mbar_arrive(bar_empty);
}

__device__ __forceinline__ float gelu_tanh(float x) {
    float u2 = x * fmaf(x * x, 2.0f * 0.7978845608028654f * 0.044715f * 1.4426950408889634f, 2.0f * 0.7978845608028654f * 1.4426950408889634f);
    float e; asm("ex2.approx.ftz.f32 %0, %1;" : "=f"(e) : "f"(-u2));
    return __fdividef(x, 1.0f + e);
}
__device__ __forceinline__ uint4 ldg128(const void* p) { uint4 v; asm volatile("ld.global.v4.u32 {%0,%1,%2,%3}, [%4];" : "=r"(v.x), "=r"(v.y), "=r"(v.z), "=r"(v.w) : "l"(p) : "memory"); return v; }
__device__ __forceinline__ float4 ldcg_f4(const float* p) { float4 v; asm volatile("ld.global.cg.v4.f32 {%0,%1,%2,%3}, [%4];" : "=f"(v.x), "=f"(v.y), "=f"(v.z), "=f"(v.w) : "l"(p) : "memory"); return v; }
__device__ __forceinline__ uint4 ldcg128(const void* p) { uint4 v; asm volatile("ld.global.cg.v4.u32 {%0,%1,%2,%3}, [%4];" : "=r"(v.x), "=r"(v.y), "=r"(v.z), "=r"(v.w) : "l"(p) : "memory"); return v; }

__device__ __forceinline__ void attn_scores(uint32_t sq, uint32_t sk, uint32_t skm, int sg, int mt, int lane, uint32_t (&p)[6][2]) {
    const int g = lane >> 2, t = lane & 3, l7 = lane & 7;
    float s[5][4];
#pragma unroll
    for (int kt = 0; kt < 5; kt++) s[kt][0] = s[kt][1] = s[kt][2] = s[kt][3] = 0.f;
    const uint32_t qrow = sq + (sg * 32 + mt * 16 + (lane & 15)) * 128;
    const uint32_t krow = sk + (sg * 32 + l7) * 128, kmrow = skm + (sg * 8 + l7) * 128;
#pragma unroll
    for (int c = 0; c < 4; c++) {
        uint32_t a0[4], a1[4];
        ldsm_x4(a0, qrow + (c >> 1) * 16384 + ((((4 * c + (lane >> 4)) & 7) ^ l7) << 4));
        ldsm_x4(a1, qrow + (c >> 1) * 16384 + ((((4 * c + 2 + (lane >> 4)) & 7) ^ l7) << 4));
        const uint32_t sw = (((4 * c + (lane >> 3)) & 7) ^ l7) << 4;
#pragma unroll
        for (int kt = 0; kt < 5; kt++) {
            uint32_t b[4];
            ldsm_x4(b, kt == 0 ? kmrow + (c >> 1) * 4096 + sw : krow + (kt - 1) * 1024 + (c >> 1) * 16384 + sw);
            mma16816(s[kt], a0, b[0], b[1]); mma16816(s[kt], a1, b[2], b[3]);
        }
    }
    const float scale = 0.08838834764831845f;
    const int r0 = mt * 16 + g, r1 = r0 + 8;
    float m0 = -INFINITY, m1 = -INFINITY;
#pragma unroll
    for (int kt = 0; kt < 5; kt++) {
#pragma unroll
        for (int i = 0; i < 4; i++) {
            float v = bf16r(bf16r(s[kt][i]) * scale);
            if (kt > 0) { int key = (kt - 1) * 8 + 2 * t + (i & 1); if (key > (i < 2 ? r0 : r1)) v = -1.0e9f; }
            s[kt][i] = v;
            if (i < 2) m0 = fmaxf(m0, v); else m1 = fmaxf(m1, v);
        }
    }
    m0 = fmaxf(m0, __shfl_xor_sync(0xffffffff, m0, 1)); m0 = fmaxf(m0, __shfl_xor_sync(0xffffffff, m0, 2));
    m1 = fmaxf(m1, __shfl_xor_sync(0xffffffff, m1, 1)); m1 = fmaxf(m1, __shfl_xor_sync(0xffffffff, m1, 2));
    float l0 = 0, l1 = 0;
#pragma unroll
    for (int kt = 0; kt < 5; kt++) {
        s[kt][0] = __expf(s[kt][0] - m0); s[kt][1] = __expf(s[kt][1] - m0); l0 += s[kt][0] + s[kt][1];
        s[kt][2] = __expf(s[kt][2] - m1); s[kt][3] = __expf(s[kt][3] - m1); l1 += s[kt][2] + s[kt][3];
    }
    l0 += __shfl_xor_sync(0xffffffff, l0, 1); l0 += __shfl_xor_sync(0xffffffff, l0, 2);
    l1 += __shfl_xor_sync(0xffffffff, l1, 1); l1 += __shfl_xor_sync(0xffffffff, l1, 2);
    const float i0 = __fdividef(1.0f, l0), i1 = __fdividef(1.0f, l1);
#pragma unroll
    for (int kt = 0; kt < 5; kt++) { p[kt][0] = pack_bf16(s[kt][0] * i0, s[kt][1] * i0); p[kt][1] = pack_bf16(s[kt][2] * i1, s[kt][3] * i1); }
    p[5][0] = p[5][1] = 0;
}
__device__ __forceinline__ void attn_pv(uint32_t sv, uint32_t svm, int sg, int lane, const uint32_t (&p)[6][2], float* d) {
    const int l7 = lane & 7, hi = (lane >> 3) & 1, ec = lane >> 4;
    const uint32_t r0 = hi ? sv + (sg * 32 + l7) * 128 : svm + (sg * 8 + l7) * 128;
    const uint32_t sub0 = hi ? 16384 : 4096;
    const uint32_t r1 = sv + (sg * 32 + 8 + hi * 8 + l7) * 128;
    const uint32_t r2 = sv + (sg * 32 + 24 + l7) * 128;
#pragma unroll
    for (int i = 0; i < 8; i++) {
        const uint32_t sw = (((2 * i + ec) & 7) ^ l7) << 4;
        uint32_t b0[4], b1[4], b2[4];
        ldsm_x4_t(b0, r0 + (i >> 2) * sub0 + sw); ldsm_x4_t(b1, r1 + (i >> 2) * 16384 + sw); ldsm_x4_t(b2, r2 + (i >> 2) * 16384 + sw);
        float* o0 = d + 8 * i; float* o1 = o0 + 4;
        o0[0] = o0[1] = o0[2] = o0[3] = o1[0] = o1[1] = o1[2] = o1[3] = 0.f;
        { uint32_t a[4] = {p[0][0], p[0][1], p[1][0], p[1][1]}; mma16816(o0, a, b0[0], b0[1]); mma16816(o1, a, b0[2], b0[3]); }
        { uint32_t a[4] = {p[2][0], p[2][1], p[3][0], p[3][1]}; mma16816(o0, a, b1[0], b1[1]); mma16816(o1, a, b1[2], b1[3]); }
        { uint32_t a[4] = {p[4][0], p[4][1], p[5][0], p[5][1]}; mma16816(o0, a, b2[0], b2[1]); mma16816(o1, a, b2[2], b2[3]); }
    }
}
__device__ __forceinline__ void bulk_load(uint32_t dst, const void* src, uint32_t bytes, uint32_t bar) {
    asm volatile("cp.async.bulk.shared::cluster.global.mbarrier::complete_tx::bytes [%0], [%1], %2, [%3];" :: "r"(dst), "l"(src), "r"(bytes), "r"(bar) : "memory");
}

__device__ __forceinline__ void stsm_x4(uint32_t addr, uint32_t a, uint32_t b, uint32_t c, uint32_t d) {
    asm volatile("stmatrix.sync.aligned.m8n8.x4.shared.b16 [%0], {%1,%2,%3,%4};" :: "r"(addr), "r"(a), "r"(b), "r"(c), "r"(d) : "memory");
}
__device__ __forceinline__ void tma_reduce_2d(const CUtensorMap* map, uint32_t src, int c0, int c1) {
    asm volatile("cp.reduce.async.bulk.tensor.2d.global.shared::cta.add.tile.bulk_group [%0, {%2, %3}], [%1];" :: "l"(map), "r"(src), "r"(c0), "r"(c1) : "memory");
}
__device__ __forceinline__ void tma_store_2d(const CUtensorMap* map, uint32_t src, int c0, int c1) {
    asm volatile("cp.async.bulk.tensor.2d.global.shared::cta.bulk_group [%0, {%2, %3}], [%1];" :: "l"(map), "r"(src), "r"(c0), "r"(c1) : "memory");
}

__global__ void __launch_bounds__(384, 1)
g_kernel(const __grid_constant__ GParams P, const bf16* __restrict__ x, const bf16* __restrict__ cvec, const bf16* __restrict__ w_mod, bf16* __restrict__ out, int nctas, int wait_r)
{
    using namespace gk;
    extern __shared__ __align__(1024) uint8_t smem[];
    const uint32_t sb = smem_u32(smem);
    const int tid = threadIdx.x, warp = tid >> 5, lane = tid & 31;
    const uint32_t b_full = sb + OFF_BAR, b_empty = b_full + 8 * STAGES, b_wfull = b_empty + 8 * STAGES, b_wempty = b_wfull + 16;
    const uint32_t b_cdone = b_wempty + 16, b_sfree = b_cdone + 32;
    volatile int* wslot = (volatile int*)(smem + OFF_BAR + 192);
    const uint32_t epoch = ld_relaxed(&g_epoch);
    const uint32_t e1 = epoch + 1;
    if (tid == 0) {
        wslot[4] = 0;
        for (int i = 0; i < STAGES; i++) { mbar_init(b_full + 8 * i, 1); mbar_init(b_empty + 8 * i, 8); }
        for (int i = 0; i < 2; i++) { mbar_init(b_wfull + 8 * i, 1); mbar_init(b_wempty + 8 * i, 9); }
        for (int i = 0; i < 4; i++) { mbar_init(b_cdone + 8 * i, 4); mbar_init(b_sfree + 8 * i, 1); }
        asm volatile("fence.mbarrier_init.release.cluster;" ::: "memory");
    }
    __syncthreads();

    if (warp < 4) {
        asm volatile("setmaxnreg.dec.sync.aligned.u32 40;");
        if (warp == 0 && lane == 0) {
            uint32_t stage = 0, sph = 1, wi = 0, wph = 1;
            bool low_left = true;
            uint32_t lx0 = 0, lx1 = 0, lx2 = 0;
            int lim = 0, issued = 0, nat = 0;
            volatile int* fin_cnt = wslot + 4;
            while (true) {
                Item it; it.type = T_END; it.rb = it.nt = it.ks = 0;
                int tk = 0; (void)tk;
                while (true) {
                    uint4 rd = ld_relaxed_v4(&g_st.ready[0]); const uint4 ex = ld_relaxed_v4(&g_st.exh[0]);
                    const uint32_t dat = nat < 16 ? ld_relaxed(&g_st.d_at[nat * 32]) : 0;
                    if (nat < 16 && dat == e1 * ((wait_r ? 112u : 48u) + (nat == 0 ? 32u : 0u))) { if (!(rd.x >> nat & 1)) publish_group(T_AT, nat, e1); nat++; }
                    { const int na = __popc(rd.x & 0xffffu); if (na > nat) nat = na; }
                    rd.x |= (1u << nat) - 1;
                    lx0 |= ex.x; lx1 |= ex.y; lx2 |= ex.z;
                    uint32_t a0 = rd.x & ~lx0, a1 = rd.y & ~lx1, a2 = rd.z & ~lx2;
                    bool got = false;
                    if (low_left && (int)rd.w < I_W + 96 + (nat + URGENT_LEAD) * 48 && (int)rd.w < N_LOW) a0 = a1 = a2 = 0;
                    if ((a0 | a1 | a2) && (rd.x >> (FINE_RB - 1) & 1) && *fin_cnt != issued) {
                        int l2 = 0; while (*fin_cnt != issued && ++l2 < SPIN_LIMIT) { }
                        continue;
                    }
                    while (a0 | a1 | a2) {
                        const int gi = a0 ? __ffs(a0) - 1 : (a1 ? 32 + __ffs(a1) - 1 : 64 + __ffs(a2) - 1);
                        const int ty = T_AT + (gi >> 4), rb = gi & 15, n = group_size(ty, rb);
                        const int i = (int)atomicAdd(&g_st.cnt[gi * 8], 1u);
                        const uint32_t bit = 1u << (gi & 31);
                        if (i >= n - 1) {
                            if (gi < 32) { lx0 |= bit; a0 &= ~bit; } else if (gi < 64) { lx1 |= bit; a1 &= ~bit; } else { lx2 |= bit; a2 &= ~bit; }
                            if (i == n - 1) asm volatile("red.relaxed.gpu.global.or.b32 [%0], %1;" :: "l"(&g_st.exh[gi >> 5]), "r"(bit) : "memory");
                        }
                        if (i < n) {
                            it.type = ty; it.rb = rb; it.nt = i;
                            if (ty == T_WO || ty == T_F2) { const int nn = n_nt(rb); it.ks = i / nn; it.nt = i - it.ks * nn; }
                            asm volatile("fence.acq_rel.gpu;" ::: "memory");
                            got = true; break;
                        }
                    }
                    if (got) {
                        break;
                    }
                    if (low_left && (int)rd.w < I_W + 96 + (nat + LOW_LEAD) * 48) {
                        const int lt = (int)atomicAdd(&g_st.lq_claim, 1u);
                        if (lt < N_LOW) {
                            it = decode_low(lt);
                            if (it.type == T_L1) wait_ge(&g_st.c_mod_a, e1 * 20);
                            else if (it.type != T_MOD) wait_ge(&g_st.f_h[it.rb * 32], e1 * 16);
                            break;
                        }
                        low_left = false;
                    }
                    if ((lx0 & lx1 & lx2) == 0xffffffffu) break;
                    if (!low_left && nat >= PRECLAIM_RB && (blockIdx.x % PRECLAIM_MOD) != 0) {
                        const uint32_t rdw[3] = {rd.x, rd.y, rd.z}, lxw[3] = {lx0, lx1, lx2};
                        int gsel = -1;
#pragma unroll
                        for (int rb = 15; rb >= PRECLAIM_RB; rb--) {
#pragma unroll
                            for (int k = 5; k >= 0; k--) {
                                const int gi = k * 16 + rb;
                                const bool rdy = rdw[gi >> 5] >> (gi & 31) & 1, exq = lxw[gi >> 5] >> (gi & 31) & 1;
                                const bool pre = k == 0 ? (nat == rb) : (rdw[(gi - 16) >> 5] >> ((gi - 16) & 31) & 1);
                                if (!rdy && !exq && pre) gsel = gi;
                            }
                        }
                        if (gsel >= 0) {
                            const int gi = gsel, ty = T_AT + (gi >> 4), rb = gi & 15, n = group_size(ty, rb);
                            const int i = (int)atomicAdd(&g_st.cnt[gi * 8], 1u);
                            const uint32_t bit = 1u << (gi & 31);
                            if (i >= n - 1) {
                                if (gi < 32) lx0 |= bit; else if (gi < 64) lx1 |= bit; else lx2 |= bit;
                                if (i == n - 1) asm volatile("red.relaxed.gpu.global.or.b32 [%0], %1;" :: "l"(&g_st.exh[gi >> 5]), "r"(bit) : "memory");
                            }
                            if (i < n) {
                                it.type = ty; it.rb = rb; it.nt = i;
                                if (ty == T_WO || ty == T_F2) { const int nn = n_nt(rb); it.ks = i / nn; it.nt = i - it.ks * nn; }
                                const uint32_t* dp = (ty == T_AT ? g_st.d_at : ty == T_WO ? g_st.c_at : ty == T_L2 ? g_st.c_wo : ty == T_F1 ? g_st.f_h2 : ty == T_F2 ? g_st.c_act : g_st.c_f2) + rb * 32;
                                const uint32_t dt = e1 * (ty == T_AT ? (wait_r ? 112u : 48u) : (uint32_t)group_size(ty - 1, rb));
                                int l3 = 0;
                                while ((int32_t)(ld_acquire(dp) - dt) < 0) { if (++l3 > SPIN_LIMIT) break; }
                                break;
                            }
                            continue;
                        }
                    }
                    __nanosleep(40);
                    if (++lim > SPIN_LIMIT) break;
                }
                issued++;
                if (it.type == T_L2) wait_ge(&g_st.c_mod_all, e1 * 60);
                asm volatile("fence.proxy.async.global;" ::: "memory");
                mbar_wait(b_wempty + 8 * wi, wph);
                wslot[wi] = pack_item(it);
                mbar_arrive(b_wfull + 8 * wi);
                if (++wi == 2) { wi = 0; wph ^= 1; }
                if (it.type == T_END) break;
                int nkb = 0, kb0 = 0;
                const CUtensorMap *mA = nullptr, *mB0 = nullptr, *mB1 = nullptr; int n0 = 0, n1 = 0, nbox = 4;
                switch (it.type) {
                    case T_KV: nkb = 10; mA = &P.tA_h;
                        if (it.ks) { mB0 = mB1 = (it.nt < 32) ? &P.tB_k : &P.tB_v; n0 = (it.nt & 31) * 128; n1 = n0 + 64; nbox = 2; }
                        else { mB0 = mB1 = (it.nt < 16) ? &P.tB_k : &P.tB_v; n0 = (it.nt & 15) * 256; n1 = n0 + 128; }
                        break;
                    case T_Q: nkb = 10; mA = &P.tA_h; mB0 = mB1 = &P.tB_q; n0 = it.nt * 256; n1 = n0 + 128; break;
                    case T_F1: nkb = 10; mA = &P.tA_h2; mB0 = &P.tB_g; mB1 = &P.tB_u; if (fine(it.rb)) { n0 = n1 = it.nt * 64; nbox = 2; } else n0 = n1 = it.nt * 128; break;
                    case T_WO: nkb = 64 / wo_split(it.rb); kb0 = it.ks * nkb; mA = &P.tA_o; mB0 = mB1 = &P.tB_o; n0 = red_col(it); if (is_wide(it)) n1 = n0 + 128; else { n1 = n0 + 64; nbox = 2; } break;
                    case T_F2: nkb = 27 / f2_split(it.rb); kb0 = it.ks * nkb; mA = &P.tA_act; mB0 = mB1 = &P.tB_d; n0 = red_col(it); if (is_wide(it)) n1 = n0 + 128; else { n1 = n0 + 64; nbox = 2; } break;
                    default: break;
                }
                if (it.type == T_AT) {
                    const int rp = reps(T_AT, it.rb);
#pragma unroll 1
                    for (int ii = 0; ii < 3 * rp; ii++) {
                        const int i = ii >= 3 ? ii - 3 : ii, hd = it.nt * rp + (ii >= 3);
                        mbar_wait(b_empty + 8 * stage, sph);
                        const uint32_t st = sb + stage * STAGE_BYTES, bar = b_full + 8 * stage;
                        mbar_expect_tx(bar, i ? 40960 : 32768);
                        const CUtensorMap* m = i == 0 ? &P.tL_q : (i == 1 ? &P.tL_k : &P.tL_v);
                        tma_load_2d(st + 16384, m, hd * 128, it.rb * 128, bar);
                        tma_load_2d(st + 32768, m, hd * 128 + 64, it.rb * 128, bar);
                        if (i) {
                            const CUtensorMap* mm = i == 1 ? &P.tL_km : &P.tL_vm;
                            tma_load_2d(st, mm, hd * 128, it.rb * 32, bar);
                            tma_load_2d(st + 4096, mm, hd * 128 + 64, it.rb * 32, bar);
                        }
                        if (++stage == STAGES) { stage = 0; sph ^= 1; }
                    }
                } else if (it.type == T_L1 || it.type == T_L2 || it.type == T_FIN) {
                    const int mode = it.type == T_L1 ? 0 : (it.type == T_L2 ? 1 : 2);
                    const uint32_t pbytes = mode == 0 ? 5120 : (mode == 1 ? 7680 : 2560);
                    const float* psrc = g_mod + (mode == 0 ? 0 : (mode == 1 ? 2 * 640 : 5 * 640));
                    const int rp = reps(it.type, it.rb);
#pragma unroll 1
                    for (int i = 0; i < rp; i++) {
                        mbar_wait(b_empty + 8 * stage, sph);
                        const uint32_t st = sb + stage * STAGE_BYTES, bar = b_full + 8 * stage;
                        const size_t ro = ((size_t)it.rb * 128 + (it.nt * rp + i) * 8) * 640;
                        mbar_expect_tx(bar, 10240 + (mode ? 20480 : 0) + pbytes);
                        bulk_load(st, (mode == 2 ? g_x1 : x) + ro, 10240, bar);
                        if (mode) bulk_load(st + 10240, g_slab + ro, 20480, bar);
                        bulk_load(st + 30720, psrc, pbytes, bar);
                        if (++stage == STAGES) { stage = 0; sph ^= 1; }
                    }
                }
                for (int kb = 0; kb < nkb; kb++) {
                    mbar_wait(b_empty + 8 * stage, sph);
                    const uint32_t st = sb + stage * STAGE_BYTES, bar = b_full + 8 * stage;
                    mbar_expect_tx(bar, 16384 + nbox * 8192);
                    const int k = (kb0 + kb) * 64;
                    tma_load_2d(st, mA, k, it.rb * 128, bar);
                    tma_load_2d(st + 16384, mB0, n0, k, bar);
                    if (nbox == 4) {
                        tma_load_2d(st + 16384 + 8192, mB0, n0 + 64, k, bar);
                        tma_load_2d(st + 16384 + 16384, mB1, n1, k, bar);
                        tma_load_2d(st + 16384 + 24576, mB1, n1 + 64, k, bar);
                    } else {
                        tma_load_2d(st + 16384 + 8192, mB1, n1, k, bar);
                    }
                    if (++stage == STAGES) { stage = 0; sph ^= 1; }
                }
            }
        } else if (warp == 1 && lane == 0) {
            uint32_t wi = 0, wph = 0, rc = 0; int pend = -1;
            while (true) {
                mbar_wait(b_wfull + 8 * wi, wph);
                const Item it = unpack_item(wslot[wi]);
                mbar_arrive(b_wempty + 8 * wi);
                if (++wi == 2) { wi = 0; wph ^= 1; }
                if (it.type == T_END) break;
                asm volatile("fence.proxy.async.global;" ::: "memory");
                const bool red = it.type == T_WO || it.type == T_F2;
                const bool tma = it.type == T_KV || it.type == T_Q || it.type == T_F1 || it.type == T_AT || red;
                const bool narrow = it.type == T_F1 && fine(it.rb);
                const bool kvn = it.type == T_KV && it.ks;
                const int rounds = red ? (is_wide(it) ? 4 : 2) : (it.type == T_AT ? reps(T_AT, it.rb) : (((it.type == T_KV || it.type == T_Q) && !kvn) ? 2 : 1));
                const CUtensorMap* mS = it.type == T_F1 ? &P.tS_act : (it.type == T_AT ? &P.tS_o : (it.type == T_Q ? &P.tS_q : (it.nt < (kvn ? 32 : 16) ? &P.tS_k : &P.tS_v)));
                const int gcol = red ? red_col(it) : (narrow ? it.nt * 64 : (rounds == 1 ? (it.nt & 31) * 128 : (it.nt & 15) * 256));
                for (int rnd = 0; rnd < rounds; rnd++) {
                    for (int wg = 0; wg < 2; wg++) {
                        mbar_wait(b_cdone + 8 * (2 * wg + (rc & 1)), (rc >> 1) & 1);
                        const uint32_t stg = sb + OFF_SCR + (2 * wg + (rc & 1)) * 16384;
                        const int grow = it.rb * 128 + wg * 64;
                        if (red) {
                            tma_reduce_2d(&P.tR_acc, stg, gcol + rnd * 64, grow);
                            tma_reduce_2d(&P.tR_acc, stg + 8192, gcol + rnd * 64 + 32, grow);
                        } else if (tma) {
                            tma_store_2d(mS, stg, gcol + rnd * 128, grow);
                            if (!narrow) tma_store_2d(mS, stg + 8192, gcol + rnd * 128 + 64, grow);
                        }
                    }
                    if (tma) asm volatile("cp.async.bulk.commit_group;" ::: "memory");
                    if (pend >= 0) {
                        asm volatile("cp.async.bulk.wait_group.read 1;" ::: "memory");
                        mbar_arrive(b_sfree + 8 * pend); mbar_arrive(b_sfree + 8 * (2 + pend)); pend = -1;
                    }
                    if (tma) pend = rc & 1; else { mbar_arrive(b_sfree + 8 * (rc & 1)); mbar_arrive(b_sfree + 8 * (2 + (rc & 1))); }
                    rc++;
                }
                if (tma) {
                    asm volatile("cp.async.bulk.wait_group.read 0;" ::: "memory");
                    mbar_arrive(b_sfree + 8 * pend); mbar_arrive(b_sfree + 8 * (2 + pend)); pend = -1;
                    asm volatile("cp.async.bulk.wait_group 0;" ::: "memory"); asm volatile("fence.proxy.async.global;" ::: "memory");
                }
                if (it.type <= T_KV) asm volatile("fence.acq_rel.gpu;" ::: "memory");
                uint32_t* cnt = nullptr; uint32_t tgt = 0; int nxt = -1;
                switch (it.type) {
                    case T_KV: if (kvn) st_relaxed_u32(&g_kvflag[it.nt], e1);
                        else { st_relaxed_u32(&g_kvflag[it.rb * 64 + it.nt * 2], e1); st_relaxed_u32(&g_kvflag[it.rb * 64 + it.nt * 2 + 1], e1); }
                    case T_Q: red_release_inc(&g_st.d_at[it.rb * 32]); break;
                    case T_MOD: if (it.nt < 20) red_add_relaxed(&g_st.c_mod_a, 1); red_add_relaxed(&g_st.c_mod_all, 1); break;
                    case T_L1: red_add_relaxed(&g_st.f_h[it.rb * 32], reps(T_L1, it.rb)); break;
                    case T_AT: cnt = &g_st.c_at[it.rb * 32]; tgt = group_size(T_AT, it.rb); nxt = T_WO; break;
                    case T_WO: cnt = &g_st.c_wo[it.rb * 32]; tgt = group_size(T_WO, it.rb); nxt = T_L2; break;
                    case T_L2: cnt = &g_st.f_h2[it.rb * 32]; tgt = group_size(T_L2, it.rb); nxt = T_F1; break;
                    case T_F1: cnt = &g_st.c_act[it.rb * 32]; tgt = group_size(T_F1, it.rb); nxt = T_F2; break;
                    case T_F2: cnt = &g_st.c_f2[it.rb * 32]; tgt = group_size(T_F2, it.rb); nxt = T_FIN; break;
                    default: break;
                }
                if (cnt) { if (atom_add_acqrel(cnt, 1) + 1 == e1 * tgt) publish_group(nxt, it.rb, e1); }
            }
            uint32_t old = atom_add_acqrel(&g_st.done, 1);
            if (old + 1 == e1 * (uint32_t)nctas) {
                for (int i = 0; i < 96; i++) g_st.cnt[i * 8] = 0;
                for (int i = 0; i < 3; i++) { g_st.ready[i] = 0; g_st.exh[i] = 0; }
                g_st.lq_claim = 0;
                st_release(&g_epoch, e1);
            }
        }
    } else {
        asm volatile("setmaxnreg.inc.sync.aligned.u32 232;");
        const int ct = tid - 128, cw = warp - 4, wg = cw >> 2;
        const int g = lane >> 2, t = lane & 3;
        uint32_t stage = 0, sph = 0, wi = 0, wph = 0, rc = 0; int ndone = 0;
#define ACQ() mbar_wait(b_sfree + 8 * (2 * wg + (rc & 1)), ((rc >> 1) & 1) ^ 1); const uint32_t so = (rc & 1) * 16384; (void)so;
#define DONE() do { __syncwarp(); if (lane == 0) mbar_arrive(b_cdone + 8 * (2 * wg + (rc & 1))); rc++; } while (0)
        while (true) {
            if (ct == 0) wslot[4] = ndone;
            ndone++;
            mbar_wait(b_wfull + 8 * wi, wph);
            const Item it = unpack_item(wslot[wi]);
            __syncwarp();
            if (lane == 0) mbar_arrive(b_wempty + 8 * wi);
            if (++wi == 2) { wi = 0; wph ^= 1; }
            if (it.type == T_END) break;
            const bool narrow = (it.type == T_F1 && fine(it.rb)) || (it.type == T_KV && it.ks);
            if (is_wide(it)) {
                const bool red = it.type == T_WO || it.type == T_F2;
                const int nkb = it.type == T_WO ? 64 / wo_split(it.rb) : (it.type == T_F2 ? 27 / f2_split(it.rb) : 10);
                float d[128];
#pragma unroll
                for (int i = 0; i < 128; i++) d[i] = 0.f;
                for (int kb = 0; kb < nkb; kb++) {
                    mbar_wait(b_full + 8 * stage, sph);
                    const uint32_t st = sb + stage * STAGE_BYTES;
                    const uint64_t da = make_desc(st + wg * 8192, 16, 1024), db = make_desc(st + 16384, 8192, 1024);
                    wgmma_fence();
#pragma unroll
                    for (int k = 0; k < 4; k++) wgmma_n256(d, da + k * 2, db + k * 128, 1);
                    wgmma_commit();
                    wgmma_wait<1>();
                    if (kb > 0 && lane == 0) mbar_arrive(b_empty + 8 * ((stage + STAGES - 1) % STAGES));
                    if (++stage == STAGES) { stage = 0; sph ^= 1; }
                }
                wgmma_wait<0>();
                fence_acc<128>(d);
                if (lane == 0) mbar_arrive(b_empty + 8 * ((stage + STAGES - 1) % STAGES));
                if (red) {
                    const uint32_t sbase = sb + OFF_SCR + wg * 32768 + ((cw & 3) * 16 + g) * 128 + (t & 1) * 8;
#pragma unroll
                    for (int rnd = 0; rnd < 4; rnd++) {
                        ACQ();
#pragma unroll
                        for (int i = 0; i < 8; i++) {
                            const float* dd = d + rnd * 32 + i * 4;
                            const uint32_t a = sbase + so + (i >> 2) * 8192 + ((((2 * i + (t >> 1)) & 7) ^ (g & 7)) << 4);
                            sts64(a, __float_as_uint(dd[0]), __float_as_uint(dd[1]));
                            sts64(a + 1024, __float_as_uint(dd[2]), __float_as_uint(dd[3]));
                        }
                        asm volatile("fence.proxy.async.shared::cta;" ::: "memory");
                        DONE();
                    }
                    continue;
                }
                const uint32_t sbase = sb + OFF_SCR + wg * 32768 + ((cw & 3) * 16 + ((lane >> 3) & 1) * 8 + (lane & 7)) * 128;
                const int sx = lane & 7, hi = lane >> 4;
                if (it.type == T_F1) {
#pragma unroll
                    for (int i = 0; i < 64; i++) d[i] = bf16r(gelu_tanh(bf16r(d[i]))) * bf16r(d[64 + i]);
                }
#pragma unroll
                for (int rnd = 0; rnd < 2; rnd++) {
                    if (rnd == 1 && it.type == T_F1) break;
                    ACQ();
#pragma unroll
                    for (int i = 0; i < 8; i++) {
                        const float* dd = d + rnd * 64 + i * 8;
                        const int chunk = (2 * i + hi) & 7;
                        stsm_x4(sbase + so + (i >> 2) * 8192 + ((chunk ^ sx) << 4), pack_bf16(dd[0], dd[1]), pack_bf16(dd[2], dd[3]), pack_bf16(dd[4], dd[5]), pack_bf16(dd[6], dd[7]));
                    }
                    asm volatile("fence.proxy.async.shared::cta;" ::: "memory");
                    DONE();
                }
                continue;
            } else if (narrow) {
                float d[64];
#pragma unroll
                for (int i = 0; i < 64; i++) d[i] = 0.f;
                const int nkb = 10;
                for (int kb = 0; kb < nkb; kb++) {
                    mbar_wait(b_full + 8 * stage, sph);
                    const uint32_t st = sb + stage * STAGE_BYTES;
                    const uint64_t da = make_desc(st + wg * 8192, 16, 1024), db = make_desc(st + 16384, 8192, 1024);
                    wgmma_fence();
#pragma unroll
                    for (int k = 0; k < 4; k++) wgmma_n128(d, da + k * 2, db + k * 128, 1);
                    wgmma_commit();
                    wgmma_wait<1>();
                    if (kb > 0 && lane == 0) mbar_arrive(b_empty + 8 * ((stage + STAGES - 1) % STAGES));
                    if (++stage == STAGES) { stage = 0; sph ^= 1; }
                }
                wgmma_wait<0>();
                fence_acc<64>(d);
                if (lane == 0) mbar_arrive(b_empty + 8 * ((stage + STAGES - 1) % STAGES));
                {
                    const uint32_t sbase = sb + OFF_SCR + wg * 32768 + ((cw & 3) * 16 + ((lane >> 3) & 1) * 8 + (lane & 7)) * 128;
                    const bool f1 = it.type == T_F1;
                    if (f1) {
#pragma unroll
                        for (int i = 0; i < 32; i++) d[i] = bf16r(gelu_tanh(bf16r(d[i]))) * bf16r(d[32 + i]);
                    }
                    ACQ();
#pragma unroll
                    for (int i = 0; i < 8; i++) {
                        if (i >= 4 && f1) break;
                        const float* dd = d + i * 8;
                        const int chunk = (2 * i + (lane >> 4)) & 7;
                        stsm_x4(sbase + so + (i >> 2) * 8192 + ((chunk ^ (lane & 7)) << 4), pack_bf16(dd[0], dd[1]), pack_bf16(dd[2], dd[3]), pack_bf16(dd[4], dd[5]), pack_bf16(dd[6], dd[7]));
                    }
                    asm volatile("fence.proxy.async.shared::cta;" ::: "memory");
                }
            } else if (it.type == T_WO || it.type == T_F2) {
                float d[64];
#pragma unroll
                for (int i = 0; i < 64; i++) d[i] = 0.f;
                const int nkb = it.type == T_WO ? 64 / wo_split(it.rb) : 27 / f2_split(it.rb);
                for (int kb = 0; kb < nkb; kb++) {
                    mbar_wait(b_full + 8 * stage, sph);
                    const uint32_t st = sb + stage * STAGE_BYTES;
                    const uint64_t da = make_desc(st + wg * 8192, 16, 1024), db = make_desc(st + 16384, 8192, 1024);
                    wgmma_fence();
#pragma unroll
                    for (int k = 0; k < 4; k++) wgmma_n128(d, da + k * 2, db + k * 128, 1);
                    wgmma_commit();
                    wgmma_wait<1>();
                    if (kb > 0 && lane == 0) mbar_arrive(b_empty + 8 * ((stage + STAGES - 1) % STAGES));
                    if (++stage == STAGES) { stage = 0; sph ^= 1; }
                }
                wgmma_wait<0>();
                fence_acc<64>(d);
                if (lane == 0) mbar_arrive(b_empty + 8 * ((stage + STAGES - 1) % STAGES));
                {
                    const int r0 = (cw & 3) * 16 + g;
                    const uint32_t sbase = sb + OFF_SCR + wg * 32768 + r0 * 128 + (t & 1) * 8;
#pragma unroll
                    for (int rnd = 0; rnd < 2; rnd++) {
                        ACQ();
#pragma unroll
                        for (int i = 0; i < 8; i++) {
                            const float* dd = d + rnd * 32 + i * 4;
                            const uint32_t a = sbase + so + (i >> 2) * 8192 + ((((2 * i + (t >> 1)) & 7) ^ (g & 7)) << 4);
                            sts64(a, __float_as_uint(dd[0]), __float_as_uint(dd[1]));
                            sts64(a + 1024, __float_as_uint(dd[2]), __float_as_uint(dd[3]));
                        }
                        asm volatile("fence.proxy.async.shared::cta;" ::: "memory");
                        if (rnd == 0) DONE();
                    }
                }
            } else if (it.type == T_AT) {
                const int rp = reps(T_AT, it.rb);
#pragma unroll 1
                for (int u = 0; u < rp; u++) {
                uint32_t p[6][2];
                float d[64];
                const uint32_t s0 = stage, s1 = (stage + 1) % STAGES, s2 = (stage + 2) % STAGES;
                mbar_wait(b_full + 8 * s0, sph);
                mbar_wait(b_full + 8 * s1, s1 < s0 ? sph ^ 1 : sph);
                attn_scores(sb + s0 * STAGE_BYTES + 16384, sb + s1 * STAGE_BYTES + 16384, sb + s1 * STAGE_BYTES, cw >> 1, cw & 1, lane, p);
                __syncwarp();
                if (lane == 0) { mbar_arrive(b_empty + 8 * s0); mbar_arrive(b_empty + 8 * s1); }
                mbar_wait(b_full + 8 * s2, s2 < s0 ? sph ^ 1 : sph);
                attn_pv(sb + s2 * STAGE_BYTES + 16384, sb + s2 * STAGE_BYTES, cw >> 1, lane, p, d);
                __syncwarp();
                if (lane == 0) mbar_arrive(b_empty + 8 * s2);
                stage += 3; if (stage >= STAGES) { stage -= STAGES; sph ^= 1; }
                const uint32_t sbase = sb + OFF_SCR + wg * 32768 + ((cw & 3) * 16 + ((lane >> 3) & 1) * 8 + (lane & 7)) * 128;
                ACQ();
#pragma unroll
                for (int i = 0; i < 8; i++) {
                    const float* dd = d + i * 8;
                    const int chunk = (2 * i + (lane >> 4)) & 7;
                    stsm_x4(sbase + so + (i >> 2) * 8192 + ((chunk ^ (lane & 7)) << 4), pack_bf16(dd[0], dd[1]), pack_bf16(dd[2], dd[3]), pack_bf16(dd[4], dd[5]), pack_bf16(dd[6], dd[7]));
                }
                asm volatile("fence.proxy.async.shared::cta;" ::: "memory");
                if (u + 1 < rp) DONE();
                }
            } else if (it.type == T_L1 || it.type == T_L2 || it.type == T_FIN) {
                const int mode = it.type == T_L1 ? 0 : (it.type == T_L2 ? 1 : 2);
                const int rp = reps(it.type, it.rb);
#pragma unroll 1
                for (int i = 0; i < rp; i++) {
                    const size_t ro = ((size_t)it.rb * 128 + (it.nt * rp + i) * 8 + cw) * 640;
                    const uint32_t st = sb + stage * STAGE_BYTES;
                    mbar_wait(b_full + 8 * stage, sph);
                    row_item(mode, st + cw * 1280, st + 10240 + cw * 2560, st + 30720, b_empty + 8 * stage, g_slab + ro, (mode == 2 ? out : g_x1) + ro, (mode ? g_h2 : g_h) + ro, lane);
                    if (++stage == STAGES) { stage = 0; sph ^= 1; }
                }
            } else if (it.type == T_MOD) {
                const int kg = ct >> 3, c8 = ct & 7;
                float acc[8] = {0, 0, 0, 0, 0, 0, 0, 0};
                const bf16* wp = w_mod + (size_t)kg * 20 * 3840 + it.nt * 64 + c8 * 8;
                {
                    uint4 w[20]; float sl[20];
#pragma unroll
                    for (int i = 0; i < 20; i++) { w[i] = __ldg((const uint4*)(wp + (size_t)i * 3840)); sl[i] = __bfloat162float(cvec[kg * 20 + i]); }
#pragma unroll
                    for (int i = 0; i < 20; i++) {
                        const float s = bf16r(__fdividef(sl[i], 1.0f + __expf(-sl[i])));
                        acc[0] += s * __uint_as_float(w[i].x << 16); acc[1] += s * __uint_as_float(w[i].x & 0xffff0000u);
                        acc[2] += s * __uint_as_float(w[i].y << 16); acc[3] += s * __uint_as_float(w[i].y & 0xffff0000u);
                        acc[4] += s * __uint_as_float(w[i].z << 16); acc[5] += s * __uint_as_float(w[i].z & 0xffff0000u);
                        acc[6] += s * __uint_as_float(w[i].w << 16); acc[7] += s * __uint_as_float(w[i].w & 0xffff0000u);
                    }
                }
#pragma unroll
                for (int i = 0; i < 8; i++) { acc[i] += __shfl_xor_sync(0xffffffff, acc[i], 8); acc[i] += __shfl_xor_sync(0xffffffff, acc[i], 16); }
                float* scr = (float*)(smem + OFF_BAR + 256);
                bar_sync(3, 256);
                if (lane < 8) {
#pragma unroll
                    for (int i = 0; i < 8; i++) scr[cw * 64 + lane * 8 + i] = acc[i];
                }
                bar_sync(3, 256);
                if (ct < 64) {
                    float sum = 0;
#pragma unroll
                    for (int i = 0; i < 8; i++) sum += scr[i * 64 + ct];
                    g_mod[it.nt * 64 + ct] = bf16r(sum);
                }
            }
            if (it.type == T_MOD || it.type == T_L1 || it.type == T_L2 || it.type == T_FIN) { ACQ(); }
            DONE();
        }
    }
}

typedef CUresult (*PFN_encodeTiled)(CUtensorMap*, CUtensorMapDataType, cuuint32_t, void*, const cuuint64_t*, const cuuint64_t*, const cuuint32_t*, const cuuint32_t*, CUtensorMapInterleave, CUtensorMapSwizzle, CUtensorMapL2promotion, CUtensorMapFloatOOBfill);

static void make_map(PFN_encodeTiled fn, CUtensorMap* m, const void* ptr, uint64_t inner, uint64_t outer, uint32_t box_inner, uint32_t box_outer, bool f32 = false) {
    cuuint64_t dims[2] = {inner, outer};
    cuuint64_t strides[1] = {inner * (f32 ? 4 : 2)};
    cuuint32_t box[2] = {box_inner, box_outer};
    cuuint32_t es[2] = {1, 1};
    fn(m, f32 ? CU_TENSOR_MAP_DATA_TYPE_FLOAT32 : CU_TENSOR_MAP_DATA_TYPE_BFLOAT16, 2, (void*)ptr, dims, strides, box, es, CU_TENSOR_MAP_INTERLEAVE_NONE, CU_TENSOR_MAP_SWIZZLE_128B, CU_TENSOR_MAP_L2_PROMOTION_L2_256B, CU_TENSOR_MAP_FLOAT_OOB_FILL_NONE);
}

#define G_LESS 0
static int g_dbg_mode = 0;

extern "C" void kernel_launch(void* const* d_in, const int* in_sizes, int n_in, void* d_out, int out_size) {
    const bf16* x = (const bf16*)d_in[0];
    const bf16* mem0 = (const bf16*)d_in[1];
    const bf16* Wq = (const bf16*)d_in[2];
    const bf16* Wk = (const bf16*)d_in[3];
    const bf16* Wv = (const bf16*)d_in[4];
    const bf16* Wo = (const bf16*)d_in[5];
    const bf16* Wg = (const bf16*)d_in[8];
    const bf16* Wu = (const bf16*)d_in[9];
    const bf16* Wd = (const bf16*)d_in[10];
    const bf16* cvec = (const bf16*)d_in[11];
    const bf16* wmod = (const bf16*)d_in[12];
    static PFN_encodeTiled fn = nullptr;
    static int nsm = 0;
    if (!fn) {
        cudaDriverEntryPointQueryResult qr;
        cudaGetDriverEntryPoint("cuTensorMapEncodeTiled", (void**)&fn, cudaEnableDefault, &qr);
        cudaFuncSetAttribute(r_kernel, cudaFuncAttributeMaxDynamicSharedMemorySize, rk::SMEM_BYTES);
        cudaFuncSetAttribute(r_kernel, cudaFuncAttributeNonPortableClusterSizeAllowed, 1);
        cudaFuncSetAttribute(g_kernel, cudaFuncAttributeMaxDynamicSharedMemorySize, gk::SMEM_BYTES);
        cudaDeviceGetAttribute(&nsm, cudaDevAttrMultiProcessorCount, 0);
    }
    void *ph, *po, *ph2, *pact, *pq, *pk, *pv;
    cudaGetSymbolAddress(&pq, g_q); cudaGetSymbolAddress(&pk, g_k); cudaGetSymbolAddress(&pv, g_v);
    cudaGetSymbolAddress(&ph, g_h); cudaGetSymbolAddress(&po, g_o); cudaGetSymbolAddress(&ph2, g_h2); cudaGetSymbolAddress(&pact, g_act);
    GParams P;
    make_map(fn, &P.tA_h, ph, 640, 2048, 64, 128);
    make_map(fn, &P.tA_o, po, 4096, 2048, 64, 128);
    make_map(fn, &P.tA_h2, ph2, 640, 2048, 64, 128);
    make_map(fn, &P.tA_act, pact, 1728, 2048, 64, 128);
    make_map(fn, &P.tB_q, Wq, 4096, 640, 64, 64);
    make_map(fn, &P.tB_k, Wk, 4096, 640, 64, 64);
    make_map(fn, &P.tB_v, Wv, 4096, 640, 64, 64);
    make_map(fn, &P.tB_o, Wo, 640, 4096, 64, 64);
    make_map(fn, &P.tB_g, Wg, 1728, 640, 64, 64);
    make_map(fn, &P.tB_u, Wu, 1728, 640, 64, 64);
    make_map(fn, &P.tB_d, Wd, 640, 1728, 64, 64);
    make_map(fn, &P.tS_q, pq, 4096, 2048, 64, 64);
    make_map(fn, &P.tS_k, pk, 4096, 2048, 64, 64);
    make_map(fn, &P.tS_v, pv, 4096, 2048, 64, 64);
    make_map(fn, &P.tS_act, pact, 1728, 2048, 64, 64);
    void *pkm, *pvm; cudaGetSymbolAddress(&pkm, g_km); cudaGetSymbolAddress(&pvm, g_vm);
    make_map(fn, &P.tS_o, po, 4096, 2048, 64, 64);
    make_map(fn, &P.tL_q, pq, 4096, 2048, 64, 128);
    make_map(fn, &P.tL_k, pk, 4096, 2048, 64, 128);
    make_map(fn, &P.tL_v, pv, 4096, 2048, 64, 128);
    make_map(fn, &P.tL_km, pkm, 4096, 512, 64, 32);
    make_map(fn, &P.tL_vm, pvm, 4096, 512, 64, 32);
    void* pacc; cudaGetSymbolAddress(&pacc, g_slab);
    make_map(fn, &P.tR_acc, pacc, 640, 2048, 32, 64, true);
    cudaStream_t st = cudaStreamPerThread;
    if (g_dbg_mode != 1) {
        cudaLaunchConfig_t cfg = {};
        cfg.gridDim = dim3(64); cfg.blockDim = dim3(256); cfg.dynamicSmemBytes = rk::SMEM_BYTES; cfg.stream = st;
        cudaLaunchAttribute at[1]; at[0].id = cudaLaunchAttributeClusterDimension; at[0].val.clusterDim.x = 16; at[0].val.clusterDim.y = 1; at[0].val.clusterDim.z = 1;
        cfg.attrs = at; cfg.numAttrs = 1;
        CUtensorMap tk, tv;
        make_map(fn, &tk, pk, 4096, 2048, 64, 32);
        make_map(fn, &tv, pv, 4096, 2048, 64, 32);
        cudaLaunchKernelEx(&cfg, r_kernel, tk, tv, mem0, Wq, Wk, Wv, Wo, 1);
    }
    {
        cudaLaunchConfig_t cfg = {};
        const int ng = g_dbg_mode == 1 ? nsm : nsm - G_LESS;
        cfg.gridDim = dim3(ng); cfg.blockDim = dim3(384); cfg.dynamicSmemBytes = gk::SMEM_BYTES; cfg.stream = st;
        cudaLaunchAttribute at[1]; at[0].id = cudaLaunchAttributeProgrammaticStreamSerialization; at[0].val.programmaticStreamSerializationAllowed = 1;
        cfg.attrs = at; cfg.numAttrs = g_dbg_mode == 1 ? 0 : 1;
        cudaLaunchKernelEx(&cfg, g_kernel, P, x, cvec, wmod, (bf16*)d_out, ng, g_dbg_mode == 1 ? 0 : 1);
    }
}
```
